```python
import torch

def _softmax(x, axis=-1):
    return torch.softmax(x, dim=axis)

def _gelu(x):
    return torch.nn.functional.gelu(x, approximate='tanh')

def _silu(x):
    return torch.nn.functional.silu(x)

def _sigmoid(x):
    return torch.sigmoid(x)

def _layernorm(x, axis=-1, eps=1e-05):
    m = x.mean(dim=axis, keepdim=True)
    v = x.var(dim=axis, keepdim=True, unbiased=False)
    return (x - m) / torch.sqrt(v + eps)

def _scatter_add(tgt, idx, src, axis=0):
    return tgt.clone().index_add_(axis, idx, src)

def _segment_sum(src, seg, n):
    out = torch.zeros((n,) + src.shape[1:], dtype=src.dtype)
    return out.index_add_(0, seg, src)

def _pad(x, pw):
    flat = tuple((v for pair in reversed(pw) for v in pair))
    return torch.nn.functional.pad(x, flat)
kernel_name = 'standalone__neighborhood_dinat__vision'

def setup_inputs():

    _w = lambda a: (lambda t: t.to(torch.bfloat16) if t.is_floating_point() else t)(torch.as_tensor(a))
    ks, dil, nh = (7, 2, 4)
    H = W = max(ks * dil, 224 // dil * dil)
    C = max(nh, 192 // nh * nh)
    return {'x': _w((lambda *s: torch.randn(*s, dtype=torch.bfloat16) * 0.2)(1, H, W, C)), 'wqkv': _w((lambda *s: torch.randn(*s, dtype=torch.bfloat16) * 0.2)(C, 3 * C)), 'wo': _w((lambda *s: torch.randn(*s, dtype=torch.bfloat16) * 0.4)(C, C)), 'rpb': _w((lambda *s: torch.randn(*s, dtype=torch.bfloat16) * 0.4)(nh, 2 * ks - 1, 2 * ks - 1))}

def reference(x, wqkv, wo, rpb):
    B, H, W, C = x.shape
    ks, dil, nh = (7, 2, 4)
    hd = C // nh
    scale = hd ** (-0.5)
    qkv = (x @ wqkv).reshape(B, H, W, 3, nh, hd)
    q = qkv[:, :, :, 0].clone()
    k = qkv[:, :, :, 1].clone()
    v = qkv[:, :, :, 2].clone()
    ih = torch.arange(H)
    iw = torch.arange(W)
    m = torch.arange(ks)
    sh = torch.clip(ih // dil - ks // 2, 0, H // dil - ks)
    sw = torch.clip(iw // dil - ks // 2, 0, W // dil - ks)
    kh = (sh[:, None] + m[None, :]) * dil + (ih % dil)[:, None]
    kw = (sw[:, None] + m[None, :]) * dil + (iw % dil)[:, None]
    rh = sh[:, None] + m[None, :] - (ih // dil)[:, None] + (ks - 1)
    rw = sw[:, None] + m[None, :] - (iw // dil)[:, None] + (ks - 1)
    ih4 = kh[:, :, None, None].clone()
    iw4 = kw[None, None, :, :].clone()
    kg = (lambda x, *d: x.permute(*d))(k[:, ih4, iw4, :, :], 0, 1, 3, 5, 2, 4, 6).reshape(B, H, W, nh, ks * ks, hd)
    vg = (lambda x, *d: x.permute(*d))(v[:, ih4, iw4, :, :], 0, 1, 3, 5, 2, 4, 6).reshape(B, H, W, nh, ks * ks, hd)
    bg = (lambda x, *d: x.permute(*d))(rpb[:, rh[:, :, None, None], rw[None, None, :, :]], 1, 3, 0, 2, 4).reshape(1, H, W, nh, ks * ks)
    logits = torch.einsum('bhwnd,bhwnkd->bhwnk', q, kg) * scale + bg
    attn = _softmax(logits, axis=-1)
    out = torch.einsum('bhwnk,bhwnkd->bhwnd', attn, vg).reshape(B, H, W, C)
    return out @ wo
```

```cpp
#include <cuda_runtime.h>
#include <cuda_bf16.h>
#include <cuda.h>
#include <stdint.h>

#define DEVI __device__ __forceinline__

namespace nat {

DEVI uint32_t smem_u32(const void* p) { return (uint32_t)__cvta_generic_to_shared(p); }

DEVI void mbar_init(uint32_t bar, uint32_t count) {
  asm volatile("mbarrier.init.shared::cta.b64 [%0], %1;" ::"r"(bar), "r"(count) : "memory");
}
DEVI void mbar_expect_tx(uint32_t bar, uint32_t bytes) {
  asm volatile("mbarrier.arrive.expect_tx.shared::cta.b64 _, [%0], %1;" ::"r"(bar), "r"(bytes) : "memory");
}
DEVI void mbar_arrive(uint32_t bar) {
  asm volatile("mbarrier.arrive.shared::cta.b64 _, [%0];" ::"r"(bar) : "memory");
}
DEVI bool mbar_try_wait(uint32_t bar, uint32_t parity) {
  uint32_t ok;
  asm volatile(
      "{\n.reg .pred p;\nmbarrier.try_wait.parity.shared::cta.b64 p, [%1], %2;\nselp.u32 %0, 1, 0, p;\n}\n"
      : "=r"(ok)
      : "r"(bar), "r"(parity)
      : "memory");
  return ok != 0;
}
DEVI bool mbar_test_wait(uint32_t bar, uint32_t parity) {
  uint32_t ok;
  asm volatile(
      "{\n.reg .pred p;\nmbarrier.test_wait.parity.shared::cta.b64 p, [%1], %2;\nselp.u32 %0, 1, 0, p;\n}\n"
      : "=r"(ok)
      : "r"(bar), "r"(parity)
      : "memory");
  return ok != 0;
}
#define BAIL(code) __trap()
#define LIMIT (1u << 20)
DEVI void mbar_wait(uint32_t bar, uint32_t parity) {
  uint32_t it = 0;
  while (!mbar_try_wait(bar, parity)) {
    if (++it > LIMIT) { BAIL(bar & 0xfffff); break; }
  }
}
DEVI void fence_mbar_init() { asm volatile("fence.mbarrier_init.release.cluster;" ::: "memory"); }

DEVI void tma_load_2d(uint32_t dst, const CUtensorMap* tm, uint32_t bar, int c0, int c1) {
  asm volatile(
      "cp.async.bulk.tensor.2d.shared::cluster.global.mbarrier::complete_tx::bytes [%0], [%1, {%3, %4}], [%2];"
      ::"r"(dst), "l"(tm), "r"(bar), "r"(c0), "r"(c1)
      : "memory");
}
DEVI void tma_store_5d(const CUtensorMap* tm, uint32_t src, int c0, int c1, int c2, int c3, int c4) {
  asm volatile("cp.async.bulk.tensor.5d.global.shared::cta.bulk_group [%0, {%2, %3, %4, %5, %6}], [%1];"
               ::"l"(tm), "r"(src), "r"(c0), "r"(c1), "r"(c2), "r"(c3), "r"(c4)
               : "memory");
}
DEVI void bulk_wait_read() { asm volatile("cp.async.bulk.wait_group.read 0;" ::: "memory"); }
DEVI void tma_load_4d(uint32_t dst, const CUtensorMap* tm, uint32_t bar, int c0, int c1, int c2, int c3) {
  asm volatile(
      "cp.async.bulk.tensor.4d.shared::cluster.global.mbarrier::complete_tx::bytes [%0], [%1, {%3, %4, %5, %6}], [%2];"
      ::"r"(dst), "l"(tm), "r"(bar), "r"(c0), "r"(c1), "r"(c2), "r"(c3)
      : "memory");
}
DEVI void tma_load_5d(uint32_t dst, const CUtensorMap* tm, uint32_t bar, int c0, int c1, int c2, int c3, int c4) {
  asm volatile(
      "cp.async.bulk.tensor.5d.shared::cluster.global.mbarrier::complete_tx::bytes [%0], [%1, {%3, %4, %5, %6, %7}], [%2];"
      ::"r"(dst), "l"(tm), "r"(bar), "r"(c0), "r"(c1), "r"(c2), "r"(c3), "r"(c4)
      : "memory");
}
DEVI void tma_prefetch_5d(const CUtensorMap* tm, int c0, int c1, int c2, int c3, int c4) {
  asm volatile("cp.async.bulk.prefetch.tensor.5d.L2.global [%0, {%1, %2, %3, %4, %5}];"
               ::"l"(tm), "r"(c0), "r"(c1), "r"(c2), "r"(c3), "r"(c4)
               : "memory");
}
DEVI void bulk_load(uint32_t dst, const void* src, uint32_t bytes, uint32_t bar) {
  asm volatile("cp.async.bulk.shared::cluster.global.mbarrier::complete_tx::bytes [%0], [%1], %2, [%3];"
               ::"r"(dst), "l"(src), "r"(bytes), "r"(bar) : "memory");
}
DEVI void bulk_store(void* dst, uint32_t src, uint32_t bytes) {
  asm volatile("cp.async.bulk.global.shared::cta.bulk_group [%0], [%1], %2;" ::"l"(dst), "r"(src), "r"(bytes) : "memory");
}
DEVI void bulk_commit() { asm volatile("cp.async.bulk.commit_group;" ::: "memory"); }
template <int N>
DEVI void bulk_wait() { asm volatile("cp.async.bulk.wait_group %0;" ::"n"(N) : "memory"); }

template <int N>
DEVI void reg_dec() { asm volatile("setmaxnreg.dec.sync.aligned.u32 %0;" ::"n"(N)); }
template <int N>
DEVI void reg_inc() { asm volatile("setmaxnreg.inc.sync.aligned.u32 %0;" ::"n"(N)); }

DEVI void wg_fence() { asm volatile("wgmma.fence.sync.aligned;" ::: "memory"); }
DEVI void wg_commit() { asm volatile("wgmma.commit_group.sync.aligned;" ::: "memory"); }
template <int N>
DEVI void wg_wait() { asm volatile("wgmma.wait_group.sync.aligned %0;" ::"n"(N) : "memory"); }
template <int N>
DEVI void fence_regs(float (&d)[N]) {
#pragma unroll
  for (int i = 0; i < N; i++) asm volatile("" : "+f"(d[i])::"memory");
}

DEVI uint64_t make_desc(uint32_t addr, uint32_t lbo, uint32_t sbo, uint32_t swz) {
  return (uint64_t)((addr & 0x3FFFFu) >> 4) | ((uint64_t)((lbo & 0x3FFFFu) >> 4) << 16) |
         ((uint64_t)((sbo & 0x3FFFFu) >> 4) << 32) | ((uint64_t)swz << 62);
}

DEVI uint32_t pack_bf16(float lo, float hi) {
  uint32_t r;
  asm("cvt.rn.bf16x2.f32 %0, %1, %2;" : "=r"(r) : "f"(hi), "f"(lo));
  return r;
}
DEVI float ex2(float x) {
  float r;
  asm("ex2.approx.ftz.f32 %0, %1;" : "=f"(r) : "f"(x));
  return r;
}
DEVI float rcp_approx(float x) {
  float r;
  asm("rcp.approx.ftz.f32 %0, %1;" : "=f"(r) : "f"(x));
  return r;
}
DEVI uint32_t movmatrix_t(uint32_t a) {
  uint32_t r;
  asm("movmatrix.sync.aligned.m8n8.trans.b16 %0, %1;" : "=r"(r) : "r"(a));
  return r;
}
DEVI void ldmatrix_x4(uint32_t (&r)[4], uint32_t addr) {
  asm volatile("ldmatrix.sync.aligned.m8n8.x4.shared.b16 {%0, %1, %2, %3}, [%4];"
               : "=r"(r[0]), "=r"(r[1]), "=r"(r[2]), "=r"(r[3]) : "r"(addr) : "memory");
}
DEVI void ldmatrix_x4(uint32_t& r0, uint32_t& r1, uint32_t& r2, uint32_t& r3, uint32_t addr) {
  asm volatile("ldmatrix.sync.aligned.m8n8.x4.shared.b16 {%0, %1, %2, %3}, [%4];"
               : "=r"(r0), "=r"(r1), "=r"(r2), "=r"(r3) : "r"(addr) : "memory");
}
DEVI void ldmatrix_x2(uint32_t& r0, uint32_t& r1, uint32_t addr) {
  asm volatile("ldmatrix.sync.aligned.m8n8.x2.shared.b16 {%0, %1}, [%2];"
               : "=r"(r0), "=r"(r1) : "r"(addr) : "memory");
}
DEVI void ldmatrix_x4_t(uint32_t (&r)[4], uint32_t addr) {
  asm volatile("ldmatrix.sync.aligned.m8n8.x4.trans.shared.b16 {%0, %1, %2, %3}, [%4];"
               : "=r"(r[0]), "=r"(r[1]), "=r"(r[2]), "=r"(r[3]) : "r"(addr) : "memory");
}
DEVI void stmatrix_x4(uint32_t addr, uint32_t r0, uint32_t r1, uint32_t r2, uint32_t r3) {
  asm volatile("stmatrix.sync.aligned.m8n8.x4.shared.b16 [%0], {%1, %2, %3, %4};"
               ::"r"(addr), "r"(r0), "r"(r1), "r"(r2), "r"(r3) : "memory");
}
DEVI void mma16816(float (&d)[4], const uint32_t (&a)[4], uint32_t b0, uint32_t b1) {
  asm volatile("mma.sync.aligned.m16n8k16.row.col.f32.bf16.bf16.f32 {%0, %1, %2, %3}, {%4, %5, %6, %7}, {%8, %9}, {%0, %1, %2, %3};"
               : "+f"(d[0]), "+f"(d[1]), "+f"(d[2]), "+f"(d[3])
               : "r"(a[0]), "r"(a[1]), "r"(a[2]), "r"(a[3]), "r"(b0), "r"(b1));
}
DEVI void mma16816_z(float (&d)[4], const uint32_t (&a)[4], uint32_t b0, uint32_t b1) {
  asm volatile("mma.sync.aligned.m16n8k16.row.col.f32.bf16.bf16.f32 {%0, %1, %2, %3}, {%4, %5, %6, %7}, {%8, %9}, {%10, %10, %10, %10};"
               : "=f"(d[0]), "=f"(d[1]), "=f"(d[2]), "=f"(d[3])
               : "r"(a[0]), "r"(a[1]), "r"(a[2]), "r"(a[3]), "r"(b0), "r"(b1), "f"(0.f));
}
DEVI void mma16816_c(float (&d)[4], const uint32_t (&a)[4], uint32_t b0, uint32_t b1, const float (&c)[4]) {
  asm volatile("mma.sync.aligned.m16n8k16.row.col.f32.bf16.bf16.f32 {%0, %1, %2, %3}, {%4, %5, %6, %7}, {%8, %9}, {%10, %11, %12, %13};"
               : "=f"(d[0]), "=f"(d[1]), "=f"(d[2]), "=f"(d[3])
               : "r"(a[0]), "r"(a[1]), "r"(a[2]), "r"(a[3]), "r"(b0), "r"(b1), "f"(c[0]), "f"(c[1]), "f"(c[2]), "f"(c[3]));
}
template <int BIT>
DEVI void sel2(uint32_t mask, float& r0, float& r1, float a0, float a1, float b0, float b1) {
  asm("{\n.reg .pred p;\n.reg .b32 t;\nand.b32 t, %2, %7;\nsetp.ne.b32 p, t, 0;\nselp.f32 %0, %3, %5, p;\nselp.f32 %1, %4, %6, p;\n}"
      : "=f"(r0), "=f"(r1) : "r"(mask), "f"(a0), "f"(a1), "f"(b0), "f"(b1), "n"(BIT));
}
template <int BIT>
DEVI void split2(uint32_t mask, uint32_t& r0, uint32_t& r1, uint32_t v) {
  asm("{\n.reg .pred p;\n.reg .b32 t;\nand.b32 t, %2, %4;\nsetp.ne.b32 p, t, 0;\nselp.b32 %0, %3, 0, p;\nselp.b32 %1, 0, %3, p;\n}"
      : "=r"(r0), "=r"(r1) : "r"(mask), "r"(v), "n"(BIT));
}
DEVI void red_max(uint32_t* p, uint32_t v) {
  asm volatile("red.relaxed.gpu.global.max.u32 [%0], %1;" ::"l"(p), "r"(v) : "memory");
}
DEVI uint4 ldg128(const void* p) {
  uint4 v;
  asm volatile("ld.global.nc.v4.u32 {%0, %1, %2, %3}, [%4];" : "=r"(v.x), "=r"(v.y), "=r"(v.z), "=r"(v.w) : "l"(p));
  return v;
}
DEVI uint32_t ld_acquire(const uint32_t* p) {
  uint32_t v;
  asm volatile("ld.acquire.gpu.global.u32 %0, [%1];" : "=r"(v) : "l"(p) : "memory");
  return v;
}
DEVI uint32_t ld_relaxed(const uint32_t* p) {
  uint32_t v;
  asm volatile("ld.relaxed.gpu.global.u32 %0, [%1];" : "=r"(v) : "l"(p) : "memory");
  return v;
}
DEVI void st_relaxed(uint32_t* p, uint32_t v) {
  asm volatile("st.relaxed.gpu.global.u32 [%0], %1;" ::"l"(p), "r"(v) : "memory");
}
DEVI void st_release(uint32_t* p, uint32_t v) {
  asm volatile("st.release.gpu.global.u32 [%0], %1;" ::"l"(p), "r"(v) : "memory");
}
DEVI void fence_gpu() { asm volatile("fence.acq_rel.gpu;" ::: "memory"); }
DEVI uint32_t lds32(uint32_t addr) {
  uint32_t v;
  asm volatile("ld.shared.u32 %0, [%1];" : "=r"(v) : "r"(addr) : "memory");
  return v;
}
DEVI void sts32(uint32_t addr, uint32_t v) {
  asm volatile("st.shared.u32 [%0], %1;" ::"r"(addr), "r"(v) : "memory");
}
DEVI void sts128(uint32_t addr, uint4 v) {
  asm volatile("st.shared.v4.u32 [%0], {%1, %2, %3, %4};" ::"r"(addr), "r"(v.x), "r"(v.y), "r"(v.z), "r"(v.w) : "memory");
}
DEVI void named_bar_arrive(int id, int n) { asm volatile("bar.arrive %0, %1;" ::"r"(id), "r"(n) : "memory"); }
DEVI void named_bar_sync(int id, int n) { asm volatile("bar.sync %0, %1;" ::"r"(id), "r"(n) : "memory"); }
DEVI void fence_proxy_async() { asm volatile("fence.proxy.async.shared::cta;" ::: "memory"); }
DEVI void fence_proxy_async_global() { asm volatile("fence.proxy.async.global;" ::: "memory"); }
DEVI int clampi(int v, int lo, int hi) { return v < lo ? lo : (v > hi ? hi : v); }

template <int TA, int TB> DEVI void wgmma_m64n144k16_ss(float (&d)[72], uint64_t descA, uint64_t descB, int scaleD) {
  asm volatile("{\n.reg .pred p;\nsetp.ne.b32 p, %74, 0;\nwgmma.mma_async.sync.aligned.m64n144k16.f32.bf16.bf16 {%0, %1, %2, %3, %4, %5, %6, %7, %8, %9, %10, %11, %12, %13, %14, %15, %16, %17, %18, %19, %20, %21, %22, %23, %24, %25, %26, %27, %28, %29, %30, %31, %32, %33, %34, %35, %36, %37, %38, %39, %40, %41, %42, %43, %44, %45, %46, %47, %48, %49, %50, %51, %52, %53, %54, %55, %56, %57, %58, %59, %60, %61, %62, %63, %64, %65, %66, %67, %68, %69, %70, %71}, %72, %73, p, 1, 1, %75, %76;\n}\n"
    : "+f"(d[0]), "+f"(d[1]), "+f"(d[2]), "+f"(d[3]), "+f"(d[4]), "+f"(d[5]), "+f"(d[6]), "+f"(d[7]), "+f"(d[8]), "+f"(d[9]), "+f"(d[10]), "+f"(d[11]), "+f"(d[12]), "+f"(d[13]), "+f"(d[14]), "+f"(d[15]), "+f"(d[16]), "+f"(d[17]), "+f"(d[18]), "+f"(d[19]), "+f"(d[20]), "+f"(d[21]), "+f"(d[22]), "+f"(d[23]), "+f"(d[24]), "+f"(d[25]), "+f"(d[26]), "+f"(d[27]), "+f"(d[28]), "+f"(d[29]), "+f"(d[30]), "+f"(d[31]), "+f"(d[32]), "+f"(d[33]), "+f"(d[34]), "+f"(d[35]), "+f"(d[36]), "+f"(d[37]), "+f"(d[38]), "+f"(d[39]), "+f"(d[40]), "+f"(d[41]), "+f"(d[42]), "+f"(d[43]), "+f"(d[44]), "+f"(d[45]), "+f"(d[46]), "+f"(d[47]), "+f"(d[48]), "+f"(d[49]), "+f"(d[50]), "+f"(d[51]), "+f"(d[52]), "+f"(d[53]), "+f"(d[54]), "+f"(d[55]), "+f"(d[56]), "+f"(d[57]), "+f"(d[58]), "+f"(d[59]), "+f"(d[60]), "+f"(d[61]), "+f"(d[62]), "+f"(d[63]), "+f"(d[64]), "+f"(d[65]), "+f"(d[66]), "+f"(d[67]), "+f"(d[68]), "+f"(d[69]), "+f"(d[70]), "+f"(d[71])
    : "l"(descA), "l"(descB), "r"(scaleD), "n"(TA), "n"(TB));
}

template <int TA, int TB> DEVI void wgmma_m64n192k16_ss(float (&d)[96], uint64_t descA, uint64_t descB, int scaleD) {
  asm volatile("{\n.reg .pred p;\nsetp.ne.b32 p, %98, 0;\nwgmma.mma_async.sync.aligned.m64n192k16.f32.bf16.bf16 {%0, %1, %2, %3, %4, %5, %6, %7, %8, %9, %10, %11, %12, %13, %14, %15, %16, %17, %18, %19, %20, %21, %22, %23, %24, %25, %26, %27, %28, %29, %30, %31, %32, %33, %34, %35, %36, %37, %38, %39, %40, %41, %42, %43, %44, %45, %46, %47, %48, %49, %50, %51, %52, %53, %54, %55, %56, %57, %58, %59, %60, %61, %62, %63, %64, %65, %66, %67, %68, %69, %70, %71, %72, %73, %74, %75, %76, %77, %78, %79, %80, %81, %82, %83, %84, %85, %86, %87, %88, %89, %90, %91, %92, %93, %94, %95}, %96, %97, p, 1, 1, %99, %100;\n}\n"
    : "+f"(d[0]), "+f"(d[1]), "+f"(d[2]), "+f"(d[3]), "+f"(d[4]), "+f"(d[5]), "+f"(d[6]), "+f"(d[7]), "+f"(d[8]), "+f"(d[9]), "+f"(d[10]), "+f"(d[11]), "+f"(d[12]), "+f"(d[13]), "+f"(d[14]), "+f"(d[15]), "+f"(d[16]), "+f"(d[17]), "+f"(d[18]), "+f"(d[19]), "+f"(d[20]), "+f"(d[21]), "+f"(d[22]), "+f"(d[23]), "+f"(d[24]), "+f"(d[25]), "+f"(d[26]), "+f"(d[27]), "+f"(d[28]), "+f"(d[29]), "+f"(d[30]), "+f"(d[31]), "+f"(d[32]), "+f"(d[33]), "+f"(d[34]), "+f"(d[35]), "+f"(d[36]), "+f"(d[37]), "+f"(d[38]), "+f"(d[39]), "+f"(d[40]), "+f"(d[41]), "+f"(d[42]), "+f"(d[43]), "+f"(d[44]), "+f"(d[45]), "+f"(d[46]), "+f"(d[47]), "+f"(d[48]), "+f"(d[49]), "+f"(d[50]), "+f"(d[51]), "+f"(d[52]), "+f"(d[53]), "+f"(d[54]), "+f"(d[55]), "+f"(d[56]), "+f"(d[57]), "+f"(d[58]), "+f"(d[59]), "+f"(d[60]), "+f"(d[61]), "+f"(d[62]), "+f"(d[63]), "+f"(d[64]), "+f"(d[65]), "+f"(d[66]), "+f"(d[67]), "+f"(d[68]), "+f"(d[69]), "+f"(d[70]), "+f"(d[71]), "+f"(d[72]), "+f"(d[73]), "+f"(d[74]), "+f"(d[75]), "+f"(d[76]), "+f"(d[77]), "+f"(d[78]), "+f"(d[79]), "+f"(d[80]), "+f"(d[81]), "+f"(d[82]), "+f"(d[83]), "+f"(d[84]), "+f"(d[85]), "+f"(d[86]), "+f"(d[87]), "+f"(d[88]), "+f"(d[89]), "+f"(d[90]), "+f"(d[91]), "+f"(d[92]), "+f"(d[93]), "+f"(d[94]), "+f"(d[95])
    : "l"(descA), "l"(descB), "r"(scaleD), "n"(TA), "n"(TB));
}

template <int TA, int TB> DEVI void wgmma_m64n48k16_ss(float (&d)[24], uint64_t descA, uint64_t descB, int scaleD) {
  asm volatile("{\n.reg .pred p;\nsetp.ne.b32 p, %26, 0;\nwgmma.mma_async.sync.aligned.m64n48k16.f32.bf16.bf16 {%0, %1, %2, %3, %4, %5, %6, %7, %8, %9, %10, %11, %12, %13, %14, %15, %16, %17, %18, %19, %20, %21, %22, %23}, %24, %25, p, 1, 1, %27, %28;\n}\n"
    : "+f"(d[0]), "+f"(d[1]), "+f"(d[2]), "+f"(d[3]), "+f"(d[4]), "+f"(d[5]), "+f"(d[6]), "+f"(d[7]), "+f"(d[8]), "+f"(d[9]), "+f"(d[10]), "+f"(d[11]), "+f"(d[12]), "+f"(d[13]), "+f"(d[14]), "+f"(d[15]), "+f"(d[16]), "+f"(d[17]), "+f"(d[18]), "+f"(d[19]), "+f"(d[20]), "+f"(d[21]), "+f"(d[22]), "+f"(d[23])
    : "l"(descA), "l"(descB), "r"(scaleD), "n"(TA), "n"(TB));
}

constexpr int kS = 112;
constexpr int kStripCtas = 112;
constexpr int kProjCtas = 20;
constexpr int kThreads = 512;
constexpr int kArr = 29;
constexpr int kSteps = 28;
constexpr int kTiles = kSteps * 28;
constexpr int kOTileBytes = 64 * 192 * 2;
#define DEV_NB 6
constexpr int kTailBands = DEV_NB;
constexpr int kProjTiles = (kSteps - kTailBands) * 28;
constexpr int kHaloBytes = 3 * 784 - 16, kHaloPitch = 2432;

__device__ __align__(1024) uint8_t g_o[(size_t)kTiles * kOTileBytes];
__device__ __align__(1024) uint8_t g_halo[(size_t)kStripCtas * 2 * kArr * kHaloPitch];
__device__ uint32_t g_hflag[kStripCtas * 32];
__device__ uint32_t g_oflag[28 * 32];
__device__ uint32_t g_epoch[132 * 32];

namespace ka {
constexpr int kWAtom = 192 * 32;
constexpr int kWBytes = 9 * kWAtom;
constexpr int kXBytes = 64 * 384;
constexpr int kXStages = 2;
constexpr int kCol = 784;
constexpr int kQCol = 400;
constexpr int kQOff = 22 * kCol;
constexpr int kSlot = 23680;
constexpr int kOffX = kWBytes;
constexpr int kOffRing = kOffX + kXStages * kXBytes;
constexpr int kOffWo = kOffX + kXBytes;
constexpr int kOffStage = kOffWo + 3 * kWAtom;
DEVI uint32_t tail_buf(int i) { return i == 2 ? kOffX : i * kOTileBytes; }
constexpr int kOffBar = kOffRing + 5 * kSlot;
constexpr int kBarX = 0, kBarXe = 256, kBarWr = 512, kBarFull = 768, kBarT = 1024, kBarTe = 1152, kBarO = 1280, kBarW = 1536;
constexpr int kSmemBytes = kOffBar + 1536 + 16;
#define DEV_D 5
constexpr int kD = DEV_D;
#define DEV_PFA 4
constexpr int kPrefetch = DEV_PFA;
#define DEV_BARPOS 1
#define DEV_VPOS 2
#define DEV_LOCK 1
#define DEV_VWAIT 0
#define DEV_STAG 0
#define DEV_NS 100
#define POLL ld_acquire
#define DEV_HSUM 1
#define SUM(x) x
#define DEV_ORD 1
#define DEV_NV 0
#define DEV_FB 0
#define FENCE_A sched_fence(s.junk)
#define FENCE_B
static_assert(kD <= 5 && kD >= 2, "ring");
}

namespace kb {
constexpr int kWoBlk = 192 * 128;
constexpr int kStages = 6;
constexpr int kOffA = 3 * kWoBlk;
constexpr int kOffBar = kOffA + kStages * kOTileBytes;
constexpr int kSmemBytes = kOffBar + 128;
}

constexpr int kSmemBytes = ka::kSmemBytes > kb::kSmemBytes ? ka::kSmemBytes : kb::kSmemBytes;
static_assert(kSmemBytes <= 232448, "smem");

#define TRACE(idx)
#define GT(i)
#define TRACEB TRACE

DEVI void mbar_wait_sleep(uint32_t bar, uint32_t parity) {
  uint32_t it = 0;
  while (!mbar_test_wait(bar, parity)) {
    if (DEV_NS) __nanosleep(DEV_NS);
    if (++it > LIMIT) { BAIL(bar & 0xfffff); break; }
  }
}

struct AttnState {
  uint32_t kf[5][3][4];
  uint32_t vf[5][3][4];
  float bias[5][4];
  uint32_t p[5][2];
  uint32_t q[6];
  float sum0, sum1;
  uint32_t kaddr, vaddr, qaddr, bar, junk, fence;
  uint32_t pm;
  uint32_t* optr;
};

#define ATRACE(k)
#define TRBASE (sbase + kTraceOff)

DEVI uint32_t sched_fence() {
  uint32_t t;
  asm volatile("mov.u32 %0, %clock;" : "=r"(t)::"memory");
  return t;
}

DEVI void store_o(AttnState& s, float (&o)[3][4], float i0, float i1, int g) {
  if (g >= 0) {
#pragma unroll
    for (int mt = 0; mt < 3; mt++) {
      s.optr[(2 * mt) * 32] = pack_bf16(o[mt][0] * i0, o[mt][1] * i1);
      s.optr[(2 * mt + 1) * 32] = pack_bf16(o[mt][2] * i0, o[mt][3] * i1);
    }
    __syncwarp();
    if (s.pm & 64) mbar_arrive(s.bar + ka::kBarO + 8 * g);
  }
  s.optr += 28 * kOTileBytes / 4;
}

template <int PH>
DEVI void load_q(AttnState& s) {
  const uint32_t qa = s.qaddr + PH * ka::kSlot - (PH == 4 && (s.pm & 128) ? 5 * ka::kSlot : 0);
  ldmatrix_x4(s.q[0], s.q[1], s.q[2], s.q[3], qa);
  ldmatrix_x2(s.q[4], s.q[5], qa + 64);
}

template <int PH>
DEVI void load_k(AttnState& s) {
  constexpr int R = (2 * PH) % 5, SL = ((PH + 1) % 5) * ka::kSlot;
#pragma unroll
  for (int ks = 0; ks < 3; ks++) ldmatrix_x4(s.kf[(R + 3) % 5][ks], s.kaddr + SL + ks * 32);
#pragma unroll
  for (int ks = 0; ks < 3; ks++) ldmatrix_x4(s.kf[(R + 4) % 5][ks], s.kaddr + SL + 384 + ks * 32);
}

template <int PH>
DEVI void attn_step(AttnState& s, int g, int warp) {
  using namespace ka;
  constexpr int R = (2 * PH) % 5, N0 = (R + 3) % 5, N1 = (R + 4) % 5;
  constexpr int SL = ((PH + 1) % 5) * kSlot;
  named_bar_sync(7, 256);
  if (PH == 0 && g == 0) {
    mbar_wait(s.bar + kBarFull, 0);
#pragma unroll
    for (int k = 0; k < 3; k++) {
      ldmatrix_x4(s.kf[1][k], s.kaddr + k * 32);
      ldmatrix_x4(s.kf[2][k], s.kaddr + 384 + k * 32);
      ldmatrix_x4_t(s.vf[1][k], s.vaddr + k * 32);
      ldmatrix_x4_t(s.vf[2][k], s.vaddr + 384 + k * 32);
    }
  }
  mbar_wait(s.bar + kBarFull + 8 * (PH == 4 && g < 0 ? -1 : g + 1), 0);
  ATRACE(0);
  float t[5][4], o[3][4], z[4];
  const uint32_t ones[4] = {0x3F803F80u, s.kaddr, 0x3F803F80u, s.vaddr};
#define PV(i) _Pragma("unroll") for (int mt = 0; mt < 3; mt++) mma16816(o[mt], s.vf[(R + 3 + (i)) % 5][mt], s.p[i][0], s.p[i][1]); \
              SUM(mma16816(z, ones, s.p[i][0], s.p[i][1]);)
#define QK0(i) mma16816_c(t[i], s.kf[(R + (i)) % 5][0], s.q[0], s.q[1], s.bias[i]);
#define QK(i, ks) mma16816(t[i], s.kf[(R + (i)) % 5][ks], s.q[2 * (ks)], s.q[2 * (ks) + 1]);
#define LDV(n) ldmatrix_x4_t(s.vf[(n) < 3 ? N0 : N1][(n) % 3], s.vaddr + SL + ((n) / 3) * 384 + ((n) % 3) * 32);
#define LDK(n) ldmatrix_x4(s.kf[(n) & 1 ? N1 : N0][(n) >> 1], s.kaddr + SL + ((n) & 1) * 384 + ((n) >> 1) * 32);
  load_q<PH>(s);
  LDK(0)
#pragma unroll
  for (int mt = 0; mt < 3; mt++) mma16816_z(o[mt], s.vf[N0][mt], s.p[0][0], s.p[0][1]);
  SUM(mma16816_z(z, ones, s.p[0][0], s.p[0][1]);)
  const uint32_t g0 = sched_fence();
  LDK(1) LDK(2)
  PV(1)
  const uint32_t g1 = sched_fence();
  LDK(3) LDK(4)
  PV(2)
  const uint32_t g2 = sched_fence();
  LDK(5)
  if (DEV_NV < 6) LDV(5)
  PV(3)
  QK0(0) QK0(1) QK0(2)
  const uint32_t g3 = sched_fence();
  if (DEV_NV < 5) LDV(4)
  if (DEV_NV < 4) LDV(3)
  PV(4)
  QK(0, 1) QK(1, 1) QK(2, 1)
  const uint32_t f1 = sched_fence();
  s.junk ^= s.fence ^ g0 ^ g1 ^ g2 ^ g3;
  if (DEV_NV < 3) LDV(2)
  if (DEV_NV < 2) LDV(1)
  if (DEV_NV < 1) LDV(0)
  QK0(3) QK0(4) QK(0, 2) QK(1, 2) QK(2, 2)
  QK(3, 1) QK(4, 1)
  QK(3, 2) QK(4, 2)
  const uint32_t f2 = sched_fence();
  named_bar_arrive(2 + PH, 384);
  s.fence = sched_fence();
  ATRACE(1);
  uint32_t pm = s.pm;
  if (PH == 0 && g == 0) pm &= ~0x3Fu;
  if (PH == 2 && g == kSteps - 1) pm |= 0x3Fu;
  float x[7][2];
  sel2<1>(pm, x[0][0], x[0][1], t[0][0], t[0][1], t[3][2], t[3][3]);
  sel2<2>(pm, x[1][0], x[1][1], t[0][2], t[0][3], t[4][0], t[4][1]);
  sel2<4>(pm, x[2][0], x[2][1], t[1][0], t[1][1], t[4][2], t[4][3]);
#pragma unroll
  for (int e = 0; e < 2; e++) {
    x[3][e] = t[1][2 + e]; x[4][e] = t[2][e]; x[5][e] = t[2][2 + e]; x[6][e] = t[3][e];
  }
  float m0 = fmaxf(fmaxf(fmaxf(x[0][0], x[1][0]), fmaxf(x[2][0], x[3][0])), fmaxf(fmaxf(x[4][0], x[5][0]), x[6][0]));
  float m1 = fmaxf(fmaxf(fmaxf(x[0][1], x[1][1]), fmaxf(x[2][1], x[3][1])), fmaxf(fmaxf(x[4][1], x[5][1]), x[6][1]));
#pragma unroll
  for (int d = 4; d <= 16; d <<= 1) {
    m0 = fmaxf(m0, __shfl_xor_sync(0xffffffffu, m0, d));
    m1 = fmaxf(m1, __shfl_xor_sync(0xffffffffu, m1, d));
  }
  uint32_t f4 = 0;
  if (DEV_NV > 0) {
    f4 = sched_fence();
    LDV(0)
    if (DEV_NV > 1) LDV(1)
    if (DEV_NV > 2) LDV(2)
    if (DEV_NV > 3) LDV(3)
    if (DEV_NV > 4) LDV(4)
    if (DEV_NV > 5) LDV(5)
  }
  const float c = 0.14433756729740643f * 1.4426950408889634f;
  const float n0 = -m0 * c, n1 = -m1 * c;
  uint32_t pt[7];
#pragma unroll
  for (int i = 0; i < 7; i++) {
    const float e0 = ex2(fmaf(x[i][0], c, n0)), e1 = ex2(fmaf(x[i][1], c, n1));
    pt[i] = movmatrix_t(pack_bf16(e0, e1));
  }
  split2<8>(pm, s.p[0][0], s.p[3][1], pt[0]);
  split2<16>(pm, s.p[0][1], s.p[4][0], pt[1]);
  split2<32>(pm, s.p[1][0], s.p[4][1], pt[2]);
  s.p[1][1] = pt[3]; s.p[2][0] = pt[4]; s.p[2][1] = pt[5]; s.p[3][0] = pt[6];
#pragma unroll
  for (int i = 0; i < 5; i++) asm volatile("" : "+r"(s.p[i][0]), "+r"(s.p[i][1])::"memory");
  store_o(s, o, rcp_approx(z[0]), rcp_approx(z[1]), g - 1);
  s.junk ^= f1 ^ f2;
  s.fence ^= f4;
  asm volatile("" : "+r"(s.junk)::"memory");
  ATRACE(2);
}

__global__ void __launch_bounds__(kThreads, 1)
nat_kernel(const __grid_constant__ CUtensorMap tm_x, const __grid_constant__ CUtensorMap tm_wo,
           const __grid_constant__ CUtensorMap tm_out, const __nv_bfloat16* __restrict__ wqkv,
           const __nv_bfloat16* __restrict__ wo, const __nv_bfloat16* __restrict__ rpb, __nv_bfloat16* __restrict__ out) {
  extern __shared__ __align__(1024) uint8_t smem_raw[];
  const uint32_t sbase = smem_u32(smem_raw);
  if (sbase & 1023u) __trap();
  const int warp = __shfl_sync(0xffffffffu, (int)(threadIdx.x >> 5), 0), lane = threadIdx.x & 31;
  const int wg = warp >> 2, wl = warp & 3;
  const int cta = blockIdx.x;
  const bool strip_cta = cta < kStripCtas;
  const int head = cta & 3, ps = cta >> 2, par = ps / 7, strip = ps - 7 * par;
  if (threadIdx.x == 0) TRACE(0);
  if (threadIdx.x == 480) GT(0);

  if (strip_cta) {
    using namespace ka;
    const uint32_t bar = sbase + kOffBar;
    uint4 v[9];
    const int wk = (int)threadIdx.x / 6, wu = (int)threadIdx.x - 6 * wk;
    if (warp < 12) {
      const uint8_t* src = reinterpret_cast<const uint8_t*>(wqkv) + wk * 1152 + head * 96 + wu * 16;
#pragma unroll
      for (int i = 0; i < 9; i++) v[i] = ldg128(src + (i / 3) * 64 * 1152 + (i % 3) * 384);
    }
    if (warp == 0) TRACE(4);
    if (lane == 0) {
      const uint32_t b0 = bar + 8 * (warp ^ 12);
      mbar_init(b0 + kBarX, 1);
      if (warp >= 12) {
        const int a = warp ^ 12;
        if (a < kXStages) {
          mbar_expect_tx(b0 + kBarX, kXBytes);
          tma_load_5d(sbase + kOffX + a * kXBytes, &tm_x, b0 + kBarX, 0, 16 * strip, 4 * a - 1, 3 * (par & 1), par >> 1);
        }
      }
      mbar_init(b0 + kBarT, 1);
      mbar_init(b0 + kBarTe, 4);
      mbar_init(b0 + kBarX + 128, 1);
#pragma unroll
      for (int h = 0; h < 256; h += 128) {
        mbar_init(b0 + kBarXe + h, 4);
        mbar_init(b0 + kBarWr + h, h && warp == 3 ? 1 : 4);
        mbar_init(b0 + kBarFull + h, 2);
        mbar_init(b0 + kBarO + h, 8);
      }
      if (warp == 3) mbar_arrive(bar + kBarFull - 8);
      fence_mbar_init();
    }
    __syncwarp();
#pragma unroll
    for (int i = 0; i < 3; i++)
      if (i * 512 + threadIdx.x < kQOff / 16) sts128(sbase + kOffRing + 4 * kSlot + (i * 512 + threadIdx.x) * 16, make_uint4(0, 0, 0, 0));
    if (warp == 0) TRACE(5);
    if (warp == 12) TRACE(8);
    if (warp < 12) {
      const uint32_t dst = sbase + (wu >> 1) * kWAtom + wk * 32 + (((wu ^ (wk >> 2)) & 1) << 4);
#pragma unroll
      for (int i = 0; i < 9; i++) sts128(dst + (i / 3) * 64 * 32 + (i % 3) * 3 * kWAtom, v[i]);
      if (warp == 0) TRACE(6);
      fence_proxy_async();
    }
  } else if (lane == 0 && warp < kb::kStages) {
    const uint32_t bar = sbase + kb::kOffBar;
    mbar_init(bar + 8 * warp, 1);
    mbar_init(bar + 64 + 8 * warp, 4);
    fence_mbar_init();
  }
  __syncthreads();
  if (warp == 0) TRACE(7);

  if (strip_cta) {
    using namespace ka;
    const uint32_t bar = sbase + kOffBar, ring = sbase + kOffRing;
    if (wg < 2) {
      reg_inc<192>();
      AttnState s;
      const int qc0 = 16 * strip + 2 * warp;
      const int kc0 = clampi(qc0 - 3, 0, kS - 8);
      const uint32_t colb = ring + (kc0 - (16 * strip - 3) + (lane & 7)) * kCol;
      s.kaddr = colb + ((lane >> 3) & 1) * 192 + (lane >> 4) * 16;
      s.vaddr = colb + 96 + (lane >> 4) * 192 + ((lane >> 3) & 1) * 16;
      {
        const int qr = (lane & 7) >> 1;
        const uint32_t qa = ring + kQOff + (2 * warp + (lane & 1)) * kQCol + (lane >> 3) * 16;
        s.qaddr = qa + (qr == 3 ? kSlot : (qr + 1) * 96);
      }
      s.bar = bar;
      s.optr = reinterpret_cast<uint32_t*>(g_o + (size_t)(ps * 4 + head) * 6144 + warp * 768) + lane - 3 * 28 * kOTileBytes / 4;
      {
        const int kc = kc0 + (lane >> 2);
        const unsigned short* r = reinterpret_cast<const unsigned short*>(rpb) + head * 169 + (3 - (lane & 3)) * 13 + kc - qc0 + 6;
        const int sw0 = clampi(qc0 - 3, 0, kS - 7), sw1 = clampi(qc0 - 2, 0, kS - 7);
        const bool ok0 = kc >= sw0 && kc < sw0 + 7, ok1 = kc >= sw1 && kc < sw1 + 7;
#pragma unroll
        for (int i = 0; i < 10; i++) {
          const uint32_t v0 = ok0 ? (uint32_t)__ldg(r + i * 13) : 0xFF80u;
          const uint32_t v1 = ok1 ? (uint32_t)__ldg(r + i * 13 - 1) : 0xFF80u;
          s.bias[i >> 1][2 * (i & 1)] = __uint_as_float(v0 << 16) * 6.928203230275509f;
          s.bias[i >> 1][2 * (i & 1) + 1] = __uint_as_float(v1 << 16) * 6.928203230275509f;
        }
      }
#pragma unroll
      for (int i = 0; i < 5; i++) {
        s.p[i][0] = s.p[i][1] = 0u;
#pragma unroll
        for (int k = 0; k < 3; k++)
#pragma unroll
          for (int c = 0; c < 4; c++) s.kf[i][k][c] = s.vf[i][k][c] = 0u;
      }
      s.sum0 = s.sum1 = 1.f;
      s.junk = s.fence = 0;
      s.pm = (7u << (lane & 3) & 7u) | ((7u << (lane >> 3) & 7u) << 3) | (lane == 0 ? 64u : 0u) | ((lane & 6) == 6 ? 128u : 0u);
      s.pm = __shfl_sync(0xffffffffu, s.pm, lane);
#pragma unroll 1
      for (int g = -2; g < kSteps; g += 5) {
        attn_step<3>(s, g, warp);
        attn_step<4>(s, g + 1, warp);
        attn_step<0>(s, g + 2, warp);
        attn_step<1>(s, g + 3, warp);
        attn_step<2>(s, g + 4, warp);
      }
      {
        float o[3][4], z[4];
        const uint32_t ones[4] = {0x3F803F80u, s.kaddr, 0x3F803F80u, s.vaddr};
#pragma unroll
        for (int mt = 0; mt < 3; mt++) mma16816_z(o[mt], s.vf[4][mt], s.p[0][0], s.p[0][1]);
        mma16816_z(z, ones, s.p[0][0], s.p[0][1]);
#pragma unroll
        for (int i = 1; i < 5; i++) {
#pragma unroll
          for (int mt = 0; mt < 3; mt++) mma16816(o[mt], s.vf[i - 1][mt], s.p[i][0], s.p[i][1]);
          mma16816(z, ones, s.p[i][0], s.p[i][1]);
        }
        store_o(s, o, rcp_approx(z[0]), rcp_approx(z[1]), kSteps - 1);
      }
      s.junk ^= s.fence;
      if (s.junk == 0x9e3779b9u) sts32(bar + kBarW, 0);
      if (warp == 0) TRACE(1);
    } else if (wg == 2) {
      reg_dec<104>();
      const int col = ((lane >> 3) & 1) * 8 + (lane & 7);
      uint32_t kva = ring + (3 + col) * kCol + wl * 192 + (lane >> 4) * 16;
      uint32_t qa = ring + kQOff + col * kQCol + wl * 96 + (lane >> 4) * 16;
      const uint64_t dA0 = make_desc(sbase + kOffX, 16, 1024, 1), dB0 = make_desc(sbase, kWAtom, 256, 3);
      if (wl == 0) TRACE(2);
      int slot = 0, bph = 0;
      named_bar_arrive(2 + 3, DEV_STAG ? 256 : 384);
      named_bar_arrive(2 + 4, DEV_STAG ? 256 : 384);
      mbar_wait(bar + kBarX, 0);
      if (wl == 0) TRACE(16 + 0);
#pragma unroll 1
      for (int a = 0; a < kArr; a++) {
        float acc[72];
        if (a >= kD) named_bar_sync(2 + bph, DEV_STAG ? 256 : 384);
        if (a >= kD) bph = bph == 4 ? 0 : bph + 1;
        if (wl == 0) TRACE(16 + a * 4 + 1);
        const uint64_t dA = dA0 + (uint64_t)((a & 1) * (kXBytes >> 4));
        wg_fence();
#pragma unroll
        for (int k = 0; k < 12; k++)
          wgmma_m64n144k16_ss<0, 1>(acc, dA + (uint64_t)(((k >> 2) * 8192 + (k & 3) * 32) >> 4), dB0 + (uint64_t)((k * 512) >> 4), k != 0);
        wg_commit();
        if (a + 1 < kArr) mbar_wait(bar + kBarX + 8 * (a + 1), 0);
        if (wl == 0) TRACE(16 + (a + 1) * 4 + 0);
        wg_wait<0>();
        fence_regs(acc);
        if (lane == 0) mbar_arrive(bar + kBarXe + 8 * a);
        if (wl == 0) TRACE(16 + a * 4 + 2);
        const uint32_t so = slot * kSlot;
#pragma unroll
        for (int jp = 0; jp < 9; jp++)
          stmatrix_x4(jp < 3 ? qa + so + jp * 32 : kva + so + (jp - 3) * 32, pack_bf16(acc[8 * jp + 0], acc[8 * jp + 1]),
                      pack_bf16(acc[8 * jp + 2], acc[8 * jp + 3]), pack_bf16(acc[8 * jp + 4], acc[8 * jp + 5]),
                      pack_bf16(acc[8 * jp + 6], acc[8 * jp + 7]));
        __syncwarp();
        if (lane == 0) mbar_arrive(bar + kBarWr + 8 * a);
        if (wl == 0) TRACE(16 + a * 4 + 3);
        slot = slot == 4 ? 0 : slot + 1;
      }
#pragma unroll 1
      for (int g = kArr - kD; g < kSteps; g++) {
        named_bar_arrive(2 + bph, DEV_STAG ? 256 : 384);
        bph = bph == 4 ? 0 : bph + 1;
      }
      {
        const uint64_t dW = make_desc(sbase + kOffWo, kWAtom, 256, 3);
        const int n = lane & 7, j = 2 * wl + ((lane >> 3) & 1);
        const uint32_t sta = sbase + kOffStage + ((2 * j + (n & 1)) * 4 + (n >> 1)) * 96 + (lane >> 4) * 16;
        mbar_wait(bar + kBarX + 8 * kArr, 0);
        int buf = 0;
#pragma unroll 1
        for (int i = 0; i < kTailBands; i++) {
          float acc[24];
          mbar_wait(bar + kBarT + 8 * i, 0);
          if (wl == 0) TRACE(200 + i * 4);
          const uint64_t dA = make_desc(sbase + tail_buf(buf), 128, 768, 0);
          wg_fence();
#pragma unroll
          for (int k = 0; k < 12; k++)
            wgmma_m64n48k16_ss<1, 1>(acc, dA + (uint64_t)(((k / 3) * 6144 + (k % 3) * 256) >> 4), dW + (uint64_t)((k * 512) >> 4), k != 0);
          wg_commit();
          if (threadIdx.x == 256) bulk_wait_read();
          wg_wait<0>();
          fence_regs(acc);
          if (lane == 0) mbar_arrive(bar + kBarTe + 8 * i);
          named_bar_sync(1, 128);
#pragma unroll
          for (int jp = 0; jp < 3; jp++)
            stmatrix_x4(sta + jp * 32, pack_bf16(acc[8 * jp + 0], acc[8 * jp + 1]), pack_bf16(acc[8 * jp + 2], acc[8 * jp + 3]),
                        pack_bf16(acc[8 * jp + 4], acc[8 * jp + 5]), pack_bf16(acc[8 * jp + 6], acc[8 * jp + 7]));
          fence_proxy_async();
          named_bar_sync(1, 128);
          if (threadIdx.x == 256) {
            tma_store_5d(&tm_out, sbase + kOffStage, head * 48, 4 * (kSteps - kTailBands + i), 16 * strip, par & 1, par >> 1);
            bulk_commit();
          }
          if (wl == 0) TRACE(200 + i * 4 + 1);
          buf = buf == 2 ? 0 : buf + 1;
        }
        if (threadIdx.x == 256) {
          bulk_wait<0>();
          GT(2);
        }
      }
    } else {
      reg_dec<24>();
      if (wl == 0) {
        if (lane == 0) {
#pragma unroll 1
          for (int ap = kXStages + ((head - kXStages) & 3); ap < kXStages + kPrefetch; ap += 4)
            tma_prefetch_5d(&tm_x, 0, 16 * strip, 4 * ap - 1, 3 * (par & 1), par >> 1);
#pragma unroll 1
          for (int a = kXStages; a < kArr; a++) {
            mbar_wait_sleep(bar + kBarXe + 8 * (a - kXStages), 0);
            mbar_expect_tx(bar + kBarX + 8 * a, kXBytes);
            tma_load_5d(sbase + kOffX + (a % kXStages) * kXBytes, &tm_x, bar + kBarX + 8 * a, 0, 16 * strip, 4 * a - 1,
                        3 * (par & 1), par >> 1);
            const int ap = a + kPrefetch;
            if (ap < kArr && (ap & 3) == head) tma_prefetch_5d(&tm_x, 0, 16 * strip, 4 * ap - 1, 3 * (par & 1), par >> 1);
          }
          mbar_wait_sleep(bar + kBarXe + 8 * (kArr - 2), 0);
          mbar_expect_tx(bar + kBarX + 8 * kArr, 3 * kWAtom);
#pragma unroll 1
          for (int i = 0; i < 3; i++) tma_load_2d(sbase + kOffWo + i * kWAtom, &tm_wo, bar + kBarX + 8 * kArr, head * 48 + i * 16, 0);
          mbar_wait_sleep(bar + kBarXe + 8 * (kArr - 1), 0);
        }
        __syncwarp();
        if (lane < 4) {
          const uint32_t ep = ld_relaxed(&g_epoch[cta * 32 + 1]);
          int buf = 0;
#pragma unroll 1
          for (int i = 0; i < kTailBands; i++) {
            const int g = kSteps - kTailBands + i;
            if (i >= 3) mbar_wait_sleep(bar + kBarTe + 8 * (i - 3), 0);
            uint32_t it = 0;
            while (true) {
              const bool ok = (int)(POLL(&g_oflag[ps * 32 + lane]) - (ep * 32u + g + 1)) >= 0;
              if (__all_sync(15u, ok)) break;
              if (++it > LIMIT) { BAIL(0x3000000 + g); break; }
            }
            if (lane == 0) {
              fence_proxy_async_global();
              mbar_expect_tx(bar + kBarT + 8 * i, kOTileBytes);
              bulk_load(sbase + tail_buf(buf), g_o + (size_t)(g * 28 + ps) * kOTileBytes, kOTileBytes, bar + kBarT + 8 * i);
            }
            __syncwarp(15u);
            buf = buf == 2 ? 0 : buf + 1;
          }
          if (lane == 0) st_relaxed(&g_epoch[cta * 32 + 1], ep + 1);
        }
      } else if (wl == 2) {
        if (lane < 2) {
          const uint32_t ep = ld_relaxed(&g_epoch[cta * 32 + 3]) * 32u;
          const bool on = lane == 0 ? strip > 0 : strip < 6;
          const int nb = on ? cta + (lane == 0 ? -4 : 4) : cta;
          const uint8_t* src = g_halo + (size_t)(nb * 2 + (lane == 0 ? 1 : 0)) * kArr * kHaloPitch;
          const uint32_t bytes = (strip > 0 && strip < 6) ? 2 * kHaloBytes : kHaloBytes;
          int slot = 0;
#pragma unroll 1
          for (int a = 0; a < kArr; a++) {
            mbar_wait_sleep(bar + kBarWr + 8 * a, 0);
            if (lane == 0) mbar_expect_tx(bar + kBarFull + 8 * a, bytes);
            TRACE(256 + a * 8 + 4);
            uint32_t it = 0;
            while (true) {
              const bool ok = !on || (int)(POLL(&g_hflag[nb * 32 + (a & 1)]) - (ep + a + 1)) >= 0;
              if (__all_sync(3u, ok)) break;
              if (++it > LIMIT) { BAIL(0x1000000 + a); break; }
            }
            TRACE(256 + a * 8 + 1);
            fence_proxy_async_global();
            TRACE(256 + a * 8 + 5);
            if (on) bulk_load(ring + slot * kSlot + lane * 19 * kCol, src, kHaloBytes, bar + kBarFull + 8 * a);
            TRACE(256 + a * 8 + 6);
            src += kHaloPitch;
            slot = slot == 4 ? 0 : slot + 1;
          }
          if (lane == 0) st_relaxed(&g_epoch[cta * 32 + 3], (ep >> 5) + 1);
        }
      } else {
        if (lane == 0) {
          const int p = wl >> 1;
          const uint32_t ep = ld_relaxed(&g_epoch[cta * 32 + 2 * p]) * 32u;
          uint8_t* dst = g_halo + ((size_t)cta * 2 * kArr + p) * kHaloPitch;
          int slot = p, g = 0;
#pragma unroll 1
          for (int a = p; a < kArr; a += 2) {
            mbar_wait_sleep(bar + kBarWr + 8 * a, 0);
            const uint32_t src = ring + slot * kSlot;
            fence_proxy_async();
            if (strip > 0) bulk_store(dst, src + 3 * kCol, kHaloBytes);
            if (strip < 6) bulk_store(dst + kArr * kHaloPitch, src + 16 * kCol, kHaloBytes);
            bulk_commit();
            bulk_wait_read();
            mbar_arrive(bar + kBarFull + 8 * a);
            bulk_wait<0>();
            TRACE(256 + a * 8 + 0);
            while (mbar_test_wait(bar + kBarO + 8 * g, 0)) g++;
            fence_gpu();
            st_relaxed(&g_hflag[cta * 32 + p], ep + a + 1);
            if (g) red_max(&g_oflag[ps * 32 + head], ep + g);
            TRACE(256 + a * 8 + 7);
            dst += 2 * kHaloPitch;
            slot = slot >= 3 ? slot - 3 : slot + 2;
          }
#pragma unroll 1
          for (g = kSteps - 4 - p; g < kSteps; g += 2) {
            mbar_wait(bar + kBarO + 8 * g, 0);
            TRACE(256 + g * 8 + 2);
            fence_gpu();
            red_max(&g_oflag[ps * 32 + head], ep + g + 1);
            TRACE(256 + g * 8 + 3);
          }
          st_relaxed(&g_epoch[cta * 32 + 2 * p], (ep >> 5) + 1);
          if (p == 1) GT(1);
        }
      }
    }
  } else {
    using namespace kb;
    const uint32_t bar = sbase + kOffBar, sA = sbase + kOffA;
    const int k = cta - kStripCtas;
    if (wg < 3) {
      reg_inc<160>();
#pragma unroll
      for (int it = 0; it < 12; it++) {
        const int c = it * 384 + (int)threadIdx.x;
        const int kr = c / 24, u = c - kr * 24;
        const uint4 v = ldg128(wo + kr * 192 + u * 8);
        const uint32_t row = sbase + (u >> 3) * kWoBlk + kr * 128 + (u & 3) * 4;
        const uint32_t h = u & 4;
        sts32(row + (((h + 0) ^ (kr & 7)) << 4), v.x);
        sts32(row + (((h + 1) ^ (kr & 7)) << 4), v.y);
        sts32(row + (((h + 2) ^ (kr & 7)) << 4), v.z);
        sts32(row + (((h + 3) ^ (kr & 7)) << 4), v.w);
      }
      fence_proxy_async();
      named_bar_sync(1, 384);
      const uint64_t dB0 = make_desc(sbase, kWoBlk, 1024, 1);
#pragma unroll 1
      for (int it = wg;; it += 3) {
        const int t = k + it * kProjCtas;
        if (t >= kProjTiles) break;
        const int st = it % kStages;
        mbar_wait(bar + 8 * st, (it / kStages) & 1);
        if (wl == 0) TRACEB(16 + it * 4 + 1);
        float acc[96];
        const uint64_t dA = make_desc(sA + st * kOTileBytes, 128, 768, 0);
        wg_fence();
#pragma unroll
        for (int kk = 0; kk < 12; kk++)
          wgmma_m64n192k16_ss<1, 1>(acc, dA + (uint64_t)(((kk / 3) * 6144 + (kk % 3) * 256) >> 4), dB0 + (uint64_t)((kk * 16 * 128) >> 4), kk != 0);
        wg_commit();
        const int g = t / 28, tp = t - 28 * g, tpar = tp / 7, tstrip = tp - 7 * tpar;
        const int n = lane >> 2;
        const int prow = 2 * (4 * g + (n >> 1)) + (tpar >> 1), pcol = 2 * (16 * tstrip + 4 * wl + (n & 1)) + (tpar & 1);
        uint8_t* oa = reinterpret_cast<uint8_t*>(out) + ((size_t)prow * 224 + pcol) * 384 + (lane & 3) * 16;
        wg_wait<0>();
        fence_regs(acc);
        if (lane == 0) mbar_arrive(bar + 64 + 8 * st);
        if (wl == 0) TRACEB(16 + it * 4 + 2);
#pragma unroll
        for (int u = 0; u < 6; u++) {
          *reinterpret_cast<uint4*>(oa + u * 64) =
              make_uint4(pack_bf16(acc[16 * u + 0], acc[16 * u + 1]), pack_bf16(acc[16 * u + 4], acc[16 * u + 5]),
                         pack_bf16(acc[16 * u + 8], acc[16 * u + 9]), pack_bf16(acc[16 * u + 12], acc[16 * u + 13]));
          *reinterpret_cast<uint4*>(oa + 4 * 384 + u * 64) =
              make_uint4(pack_bf16(acc[16 * u + 2], acc[16 * u + 3]), pack_bf16(acc[16 * u + 6], acc[16 * u + 7]),
                         pack_bf16(acc[16 * u + 10], acc[16 * u + 11]), pack_bf16(acc[16 * u + 14], acc[16 * u + 15]));
        }
        if (wl == 0) TRACEB(16 + it * 4 + 3);
      }
      if (threadIdx.x == 0) GT(1);
    } else {
      reg_dec<24>();
      if (wl < 3 && lane < 4) {
        const uint32_t e0 = ld_relaxed(&g_epoch[cta * 32 + wl]);
#pragma unroll 1
        for (int it = wl;; it += 3) {
          const int t = k + it * kProjCtas;
          if (t >= kProjTiles) break;
          const int st = it % kStages;
          const int g = t / 28, tp = t - 28 * g;
          if (it >= kStages) mbar_wait(bar + 64 + 8 * st, ((it / kStages) & 1) ^ 1);
          uint32_t sp = 0;
          while (true) {
            const bool ok = (int)(POLL(&g_oflag[tp * 32 + lane]) - (e0 * 32u + g + 1)) >= 0;
            if (__all_sync(15u, ok)) break;
            if (++sp > LIMIT) { BAIL(0x2000000 + t); break; }
          }
          TRACEB(16 + it * 4 + 0);
          if (lane == 0) {
            fence_proxy_async_global();
            mbar_expect_tx(bar + 8 * st, kOTileBytes);
            bulk_load(sA + st * kOTileBytes, g_o + (size_t)t * kOTileBytes, kOTileBytes, bar + 8 * st);
          }
          __syncwarp(15u);
        }
        if (lane == 0) st_relaxed(&g_epoch[cta * 32 + wl], e0 + 1);
      }
    }
  }
}

}

namespace {

typedef CUresult (*EncodeTiledFn)(CUtensorMap*, CUtensorMapDataType, cuuint32_t, void*, const cuuint64_t*,
                                  const cuuint64_t*, const cuuint32_t*, const cuuint32_t*, CUtensorMapInterleave,
                                  CUtensorMapSwizzle, CUtensorMapL2promotion, CUtensorMapFloatOOBfill);

EncodeTiledFn get_encode_fn() {
  static EncodeTiledFn fn = nullptr;
  if (!fn) {
    void* p = nullptr;
    cudaDriverEntryPointQueryResult qres;
    if (cudaGetDriverEntryPoint("cuTensorMapEncodeTiled", &p, cudaEnableDefault, &qres) == cudaSuccess)
      fn = reinterpret_cast<EncodeTiledFn>(p);
  }
  return fn;
}

CUtensorMap make_map(void* base, int rank, const cuuint64_t* dims, const cuuint64_t* strides, const cuuint32_t* box,
                     CUtensorMapSwizzle swz) {
  CUtensorMap m;
  cuuint32_t es[5] = {1, 1, 1, 1, 1};
  get_encode_fn()(&m, CU_TENSOR_MAP_DATA_TYPE_BFLOAT16, (cuuint32_t)rank, base, dims, strides, box, es,
                  CU_TENSOR_MAP_INTERLEAVE_NONE, swz, CU_TENSOR_MAP_L2_PROMOTION_L2_128B,
                  CU_TENSOR_MAP_FLOAT_OOB_FILL_NONE);
  return m;
}

}

extern "C" void kernel_launch(void* const* d_in, const int* in_sizes, int n_in, void* d_out, int out_size) {
  using namespace nat;
  (void)in_sizes; (void)n_in; (void)out_size;
  const __nv_bfloat16* x = (const __nv_bfloat16*)d_in[0];
  const __nv_bfloat16* wqkv = (const __nv_bfloat16*)d_in[1];
  const __nv_bfloat16* wo = (const __nv_bfloat16*)d_in[2];
  const __nv_bfloat16* rpb = (const __nv_bfloat16*)d_in[3];
  __nv_bfloat16* out = (__nv_bfloat16*)d_out;

  CUtensorMap tm_x, tm_wo, tm_out;
  {
    cuuint64_t dims[5] = {64, 112, 112, 6, 2};
    cuuint64_t str[4] = {768, 2ull * 224 * 384, 128, 224ull * 384};
    cuuint32_t box[5] = {64, 16, 4, 3, 1};
    tm_x = make_map((void*)x, 5, dims, str, box, CU_TENSOR_MAP_SWIZZLE_128B);
  }
  {
    cuuint64_t dims[2] = {192, 192};
    cuuint64_t str[1] = {384};
    cuuint32_t box[2] = {16, 192};
    tm_wo = make_map((void*)wo, 2, dims, str, box, CU_TENSOR_MAP_SWIZZLE_32B);
  }
  {
    cuuint64_t dims[5] = {192, 112, 112, 2, 2};
    cuuint64_t str[4] = {2ull * 224 * 384, 768, 384, 224ull * 384};
    cuuint32_t box[5] = {48, 4, 16, 1, 1};
    tm_out = make_map((void*)out, 5, dims, str, box, CU_TENSOR_MAP_SWIZZLE_NONE);
  }
  cudaFuncSetAttribute(nat_kernel, cudaFuncAttributeMaxDynamicSharedMemorySize, kSmemBytes);
  nat_kernel<<<kStripCtas + kProjCtas, kThreads, kSmemBytes>>>(tm_x, tm_wo, tm_out, wqkv, wo, rpb, out);
}
```

```cpp
#include <cuda_runtime.h>
#include <cuda_bf16.h>
#include <cuda.h>
#include <stdint.h>

#define DEVI __device__ __forceinline__

namespace nat {

DEVI uint32_t smem_u32(const void* p) { return (uint32_t)__cvta_generic_to_shared(p); }

DEVI void mbar_init(uint32_t bar, uint32_t count) {
  asm volatile("mbarrier.init.shared::cta.b64 [%0], %1;" ::"r"(bar), "r"(count) : "memory");
}
DEVI void mbar_expect_tx(uint32_t bar, uint32_t bytes) {
  asm volatile("mbarrier.arrive.expect_tx.shared::cta.b64 _, [%0], %1;" ::"r"(bar), "r"(bytes) : "memory");
}
DEVI void mbar_arrive(uint32_t bar) {
  asm volatile("mbarrier.arrive.shared::cta.b64 _, [%0];" ::"r"(bar) : "memory");
}
DEVI bool mbar_try_wait(uint32_t bar, uint32_t parity) {
  uint32_t ok;
  asm volatile(
      "{\n.reg .pred p;\nmbarrier.try_wait.parity.shared::cta.b64 p, [%1], %2;\nselp.u32 %0, 1, 0, p;\n}\n"
      : "=r"(ok)
      : "r"(bar), "r"(parity)
      : "memory");
  return ok != 0;
}
DEVI bool mbar_test_wait(uint32_t bar, uint32_t parity) {
  uint32_t ok;
  asm volatile(
      "{\n.reg .pred p;\nmbarrier.test_wait.parity.shared::cta.b64 p, [%1], %2;\nselp.u32 %0, 1, 0, p;\n}\n"
      : "=r"(ok)
      : "r"(bar), "r"(parity)
      : "memory");
  return ok != 0;
}
#define BAIL(code) __trap()
#define LIMIT (1u << 20)
DEVI void mbar_wait(uint32_t bar, uint32_t parity) {
  uint32_t it = 0;
  while (!mbar_try_wait(bar, parity)) {
    if (++it > LIMIT) { BAIL(bar & 0xfffff); break; }
  }
}
DEVI void fence_mbar_init() { asm volatile("fence.mbarrier_init.release.cluster;" ::: "memory"); }

DEVI void tma_load_2d(uint32_t dst, const CUtensorMap* tm, uint32_t bar, int c0, int c1) {
  asm volatile(
      "cp.async.bulk.tensor.2d.shared::cluster.global.mbarrier::complete_tx::bytes [%0], [%1, {%3, %4}], [%2];"
      ::"r"(dst), "l"(tm), "r"(bar), "r"(c0), "r"(c1)
      : "memory");
}
DEVI void tma_store_5d(const CUtensorMap* tm, uint32_t src, int c0, int c1, int c2, int c3, int c4) {
  asm volatile("cp.async.bulk.tensor.5d.global.shared::cta.bulk_group [%0, {%2, %3, %4, %5, %6}], [%1];"
               ::"l"(tm), "r"(src), "r"(c0), "r"(c1), "r"(c2), "r"(c3), "r"(c4)
               : "memory");
}
DEVI void bulk_wait_read() { asm volatile("cp.async.bulk.wait_group.read 0;" ::: "memory"); }
DEVI void tma_load_4d(uint32_t dst, const CUtensorMap* tm, uint32_t bar, int c0, int c1, int c2, int c3) {
  asm volatile(
      "cp.async.bulk.tensor.4d.shared::cluster.global.mbarrier::complete_tx::bytes [%0], [%1, {%3, %4, %5, %6}], [%2];"
      ::"r"(dst), "l"(tm), "r"(bar), "r"(c0), "r"(c1), "r"(c2), "r"(c3)
      : "memory");
}
DEVI void tma_load_5d(uint32_t dst, const CUtensorMap* tm, uint32_t bar, int c0, int c1, int c2, int c3, int c4) {
  asm volatile(
      "cp.async.bulk.tensor.5d.shared::cluster.global.mbarrier::complete_tx::bytes [%0], [%1, {%3, %4, %5, %6, %7}], [%2];"
      ::"r"(dst), "l"(tm), "r"(bar), "r"(c0), "r"(c1), "r"(c2), "r"(c3), "r"(c4)
      : "memory");
}
DEVI void tma_load_5d_mc(uint32_t dst, const CUtensorMap* tm, uint32_t bar, int c0, int c1, int c2, int c3, int c4, uint16_t mask) {
  asm volatile(
      "cp.async.bulk.tensor.5d.shared::cluster.global.mbarrier::complete_tx::bytes.multicast::cluster [%0], [%1, {%3, %4, %5, %6, %7}], [%2], %8;"
      ::"r"(dst), "l"(tm), "r"(bar), "r"(c0), "r"(c1), "r"(c2), "r"(c3), "r"(c4), "h"(mask)
      : "memory");
}
DEVI uint32_t mapa(uint32_t addr, uint32_t rank) {
  uint32_t r;
  asm("mapa.shared::cluster.u32 %0, %1, %2;" : "=r"(r) : "r"(addr), "r"(rank));
  return r;
}
DEVI void mbar_arrive_cluster(uint32_t cluster_bar) {
  asm volatile("mbarrier.arrive.shared::cluster.b64 _, [%0];" ::"r"(cluster_bar) : "memory");
}
DEVI void cluster_arrive_relaxed() { asm volatile("barrier.cluster.arrive.relaxed.aligned;" ::: "memory"); }
DEVI void cluster_wait() { asm volatile("barrier.cluster.wait.aligned;" ::: "memory"); }
DEVI void tma_prefetch_5d(const CUtensorMap* tm, int c0, int c1, int c2, int c3, int c4) {
  asm volatile("cp.async.bulk.prefetch.tensor.5d.L2.global [%0, {%1, %2, %3, %4, %5}];"
               ::"l"(tm), "r"(c0), "r"(c1), "r"(c2), "r"(c3), "r"(c4)
               : "memory");
}
DEVI void bulk_load(uint32_t dst, const void* src, uint32_t bytes, uint32_t bar) {
  asm volatile("cp.async.bulk.shared::cluster.global.mbarrier::complete_tx::bytes [%0], [%1], %2, [%3];"
               ::"r"(dst), "l"(src), "r"(bytes), "r"(bar) : "memory");
}
DEVI void bulk_store(void* dst, uint32_t src, uint32_t bytes) {
  asm volatile("cp.async.bulk.global.shared::cta.bulk_group [%0], [%1], %2;" ::"l"(dst), "r"(src), "r"(bytes) : "memory");
}
DEVI void bulk_commit() { asm volatile("cp.async.bulk.commit_group;" ::: "memory"); }
template <int N>
DEVI void bulk_wait() { asm volatile("cp.async.bulk.wait_group %0;" ::"n"(N) : "memory"); }

template <int N>
DEVI void reg_dec() { asm volatile("setmaxnreg.dec.sync.aligned.u32 %0;" ::"n"(N)); }
template <int N>
DEVI void reg_inc() { asm volatile("setmaxnreg.inc.sync.aligned.u32 %0;" ::"n"(N)); }

DEVI void wg_fence() { asm volatile("wgmma.fence.sync.aligned;" ::: "memory"); }
DEVI void wg_commit() { asm volatile("wgmma.commit_group.sync.aligned;" ::: "memory"); }
template <int N>
DEVI void wg_wait() { asm volatile("wgmma.wait_group.sync.aligned %0;" ::"n"(N) : "memory"); }
template <int N>
DEVI void fence_regs(float (&d)[N]) {
#pragma unroll
  for (int i = 0; i < N; i++) asm volatile("" : "+f"(d[i])::"memory");
}

DEVI uint64_t make_desc(uint32_t addr, uint32_t lbo, uint32_t sbo, uint32_t swz) {
  return (uint64_t)((addr & 0x3FFFFu) >> 4) | ((uint64_t)((lbo & 0x3FFFFu) >> 4) << 16) |
         ((uint64_t)((sbo & 0x3FFFFu) >> 4) << 32) | ((uint64_t)swz << 62);
}

DEVI uint64_t desc64(uint32_t lo, uint32_t hi) {
  uint64_t d;
  asm("mov.b64 %0, {%1, %2};" : "=l"(d) : "r"(lo), "r"(hi));
  return d;
}
DEVI uint32_t pack_bf16(float lo, float hi) {
  uint32_t r;
  asm("cvt.rn.bf16x2.f32 %0, %1, %2;" : "=r"(r) : "f"(hi), "f"(lo));
  return r;
}
DEVI float ex2(float x) {
  float r;
  asm("ex2.approx.ftz.f32 %0, %1;" : "=f"(r) : "f"(x));
  return r;
}
DEVI float rcp_approx(float x) {
  float r;
  asm("rcp.approx.ftz.f32 %0, %1;" : "=f"(r) : "f"(x));
  return r;
}
DEVI uint32_t movmatrix_t(uint32_t a) {
  uint32_t r;
  asm("movmatrix.sync.aligned.m8n8.trans.b16 %0, %1;" : "=r"(r) : "r"(a));
  return r;
}
DEVI void ldmatrix_x4(uint32_t (&r)[4], uint32_t addr) {
  asm volatile("ldmatrix.sync.aligned.m8n8.x4.shared.b16 {%0, %1, %2, %3}, [%4];"
               : "=r"(r[0]), "=r"(r[1]), "=r"(r[2]), "=r"(r[3]) : "r"(addr) : "memory");
}
DEVI void ldmatrix_x4(uint32_t& r0, uint32_t& r1, uint32_t& r2, uint32_t& r3, uint32_t addr) {
  asm volatile("ldmatrix.sync.aligned.m8n8.x4.shared.b16 {%0, %1, %2, %3}, [%4];"
               : "=r"(r0), "=r"(r1), "=r"(r2), "=r"(r3) : "r"(addr) : "memory");
}
DEVI void ldmatrix_x2(uint32_t& r0, uint32_t& r1, uint32_t addr) {
  asm volatile("ldmatrix.sync.aligned.m8n8.x2.shared.b16 {%0, %1}, [%2];"
               : "=r"(r0), "=r"(r1) : "r"(addr) : "memory");
}
DEVI void ldmatrix_x4_t(uint32_t (&r)[4], uint32_t addr) {
  asm volatile("ldmatrix.sync.aligned.m8n8.x4.trans.shared.b16 {%0, %1, %2, %3}, [%4];"
               : "=r"(r[0]), "=r"(r[1]), "=r"(r[2]), "=r"(r[3]) : "r"(addr) : "memory");
}
DEVI void stmatrix_x4(uint32_t addr, uint32_t r0, uint32_t r1, uint32_t r2, uint32_t r3) {
  asm volatile("stmatrix.sync.aligned.m8n8.x4.shared.b16 [%0], {%1, %2, %3, %4};"
               ::"r"(addr), "r"(r0), "r"(r1), "r"(r2), "r"(r3) : "memory");
}
DEVI void mma16816(float (&d)[4], const uint32_t (&a)[4], uint32_t b0, uint32_t b1) {
  asm volatile("mma.sync.aligned.m16n8k16.row.col.f32.bf16.bf16.f32 {%0, %1, %2, %3}, {%4, %5, %6, %7}, {%8, %9}, {%0, %1, %2, %3};"
               : "+f"(d[0]), "+f"(d[1]), "+f"(d[2]), "+f"(d[3])
               : "r"(a[0]), "r"(a[1]), "r"(a[2]), "r"(a[3]), "r"(b0), "r"(b1));
}
DEVI void mma16816_z(float (&d)[4], const uint32_t (&a)[4], uint32_t b0, uint32_t b1) {
  asm volatile("mma.sync.aligned.m16n8k16.row.col.f32.bf16.bf16.f32 {%0, %1, %2, %3}, {%4, %5, %6, %7}, {%8, %9}, {%10, %10, %10, %10};"
               : "=f"(d[0]), "=f"(d[1]), "=f"(d[2]), "=f"(d[3])
               : "r"(a[0]), "r"(a[1]), "r"(a[2]), "r"(a[3]), "r"(b0), "r"(b1), "f"(0.f));
}
DEVI void mma16816_c(float (&d)[4], const uint32_t (&a)[4], uint32_t b0, uint32_t b1, const float (&c)[4]) {
  asm volatile("mma.sync.aligned.m16n8k16.row.col.f32.bf16.bf16.f32 {%0, %1, %2, %3}, {%4, %5, %6, %7}, {%8, %9}, {%10, %11, %12, %13};"
               : "=f"(d[0]), "=f"(d[1]), "=f"(d[2]), "=f"(d[3])
               : "r"(a[0]), "r"(a[1]), "r"(a[2]), "r"(a[3]), "r"(b0), "r"(b1), "f"(c[0]), "f"(c[1]), "f"(c[2]), "f"(c[3]));
}
template <int BIT>
DEVI void sel2(uint32_t mask, float& r0, float& r1, float a0, float a1, float b0, float b1) {
  asm("{\n.reg .pred p;\n.reg .b32 t;\nand.b32 t, %2, %7;\nsetp.ne.b32 p, t, 0;\nselp.f32 %0, %3, %5, p;\nselp.f32 %1, %4, %6, p;\n}"
      : "=f"(r0), "=f"(r1) : "r"(mask), "f"(a0), "f"(a1), "f"(b0), "f"(b1), "n"(BIT));
}
template <int BIT>
DEVI void split2(uint32_t mask, uint32_t& r0, uint32_t& r1, uint32_t v) {
  asm("{\n.reg .pred p;\n.reg .b32 t;\nand.b32 t, %2, %4;\nsetp.ne.b32 p, t, 0;\nselp.b32 %0, %3, 0, p;\nselp.b32 %1, 0, %3, p;\n}"
      : "=r"(r0), "=r"(r1) : "r"(mask), "r"(v), "n"(BIT));
}
DEVI void red_max(uint32_t* p, uint32_t v) {
  asm volatile("red.relaxed.gpu.global.max.u32 [%0], %1;" ::"l"(p), "r"(v) : "memory");
}
DEVI uint4 ldg128(const void* p) {
  uint4 v;
  asm volatile("ld.global.nc.v4.u32 {%0, %1, %2, %3}, [%4];" : "=r"(v.x), "=r"(v.y), "=r"(v.z), "=r"(v.w) : "l"(p));
  return v;
}
DEVI uint32_t ld_acquire(const uint32_t* p) {
  uint32_t v;
  asm volatile("ld.acquire.gpu.global.u32 %0, [%1];" : "=r"(v) : "l"(p) : "memory");
  return v;
}
DEVI uint32_t ld_relaxed(const uint32_t* p) {
  uint32_t v;
  asm volatile("ld.relaxed.gpu.global.u32 %0, [%1];" : "=r"(v) : "l"(p) : "memory");
  return v;
}
DEVI void st_relaxed(uint32_t* p, uint32_t v) {
  asm volatile("st.relaxed.gpu.global.u32 [%0], %1;" ::"l"(p), "r"(v) : "memory");
}
DEVI void st_release(uint32_t* p, uint32_t v) {
  asm volatile("st.release.gpu.global.u32 [%0], %1;" ::"l"(p), "r"(v) : "memory");
}
DEVI void fence_gpu() { asm volatile("fence.acq_rel.gpu;" ::: "memory"); }
DEVI uint32_t lds32(uint32_t addr) {
  uint32_t v;
  asm volatile("ld.shared.u32 %0, [%1];" : "=r"(v) : "r"(addr) : "memory");
  return v;
}
DEVI int lds32v(uint32_t addr) {
  int v;
  asm volatile("ld.volatile.shared.s32 %0, [%1];" : "=r"(v) : "r"(addr) : "memory");
  return v;
}
DEVI void sts32(uint32_t addr, uint32_t v) {
  asm volatile("st.shared.u32 [%0], %1;" ::"r"(addr), "r"(v) : "memory");
}
DEVI void sts128(uint32_t addr, uint4 v) {
  asm volatile("st.shared.v4.u32 [%0], {%1, %2, %3, %4};" ::"r"(addr), "r"(v.x), "r"(v.y), "r"(v.z), "r"(v.w) : "memory");
}
DEVI void named_bar_arrive(int id, int n) { asm volatile("bar.arrive %0, %1;" ::"r"(id), "r"(n) : "memory"); }
DEVI void named_bar_sync(int id, int n) { asm volatile("bar.sync %0, %1;" ::"r"(id), "r"(n) : "memory"); }
DEVI void fence_proxy_async() { asm volatile("fence.proxy.async.shared::cta;" ::: "memory"); }
DEVI void fence_proxy_async_global() { asm volatile("fence.proxy.async.global;" ::: "memory"); }
DEVI int clampi(int v, int lo, int hi) { return v < lo ? lo : (v > hi ? hi : v); }

template <int TA, int TB> DEVI void wgmma_m64n144k16_ss(float (&d)[72], uint64_t descA, uint64_t descB, int scaleD) {
  asm volatile("{\n.reg .pred p;\nsetp.ne.b32 p, %74, 0;\nwgmma.mma_async.sync.aligned.m64n144k16.f32.bf16.bf16 {%0, %1, %2, %3, %4, %5, %6, %7, %8, %9, %10, %11, %12, %13, %14, %15, %16, %17, %18, %19, %20, %21, %22, %23, %24, %25, %26, %27, %28, %29, %30, %31, %32, %33, %34, %35, %36, %37, %38, %39, %40, %41, %42, %43, %44, %45, %46, %47, %48, %49, %50, %51, %52, %53, %54, %55, %56, %57, %58, %59, %60, %61, %62, %63, %64, %65, %66, %67, %68, %69, %70, %71}, %72, %73, p, 1, 1, %75, %76;\n}\n"
    : "+f"(d[0]), "+f"(d[1]), "+f"(d[2]), "+f"(d[3]), "+f"(d[4]), "+f"(d[5]), "+f"(d[6]), "+f"(d[7]), "+f"(d[8]), "+f"(d[9]), "+f"(d[10]), "+f"(d[11]), "+f"(d[12]), "+f"(d[13]), "+f"(d[14]), "+f"(d[15]), "+f"(d[16]), "+f"(d[17]), "+f"(d[18]), "+f"(d[19]), "+f"(d[20]), "+f"(d[21]), "+f"(d[22]), "+f"(d[23]), "+f"(d[24]), "+f"(d[25]), "+f"(d[26]), "+f"(d[27]), "+f"(d[28]), "+f"(d[29]), "+f"(d[30]), "+f"(d[31]), "+f"(d[32]), "+f"(d[33]), "+f"(d[34]), "+f"(d[35]), "+f"(d[36]), "+f"(d[37]), "+f"(d[38]), "+f"(d[39]), "+f"(d[40]), "+f"(d[41]), "+f"(d[42]), "+f"(d[43]), "+f"(d[44]), "+f"(d[45]), "+f"(d[46]), "+f"(d[47]), "+f"(d[48]), "+f"(d[49]), "+f"(d[50]), "+f"(d[51]), "+f"(d[52]), "+f"(d[53]), "+f"(d[54]), "+f"(d[55]), "+f"(d[56]), "+f"(d[57]), "+f"(d[58]), "+f"(d[59]), "+f"(d[60]), "+f"(d[61]), "+f"(d[62]), "+f"(d[63]), "+f"(d[64]), "+f"(d[65]), "+f"(d[66]), "+f"(d[67]), "+f"(d[68]), "+f"(d[69]), "+f"(d[70]), "+f"(d[71])
    : "l"(descA), "l"(descB), "r"(scaleD), "n"(TA), "n"(TB));
}

template <int TA, int TB> DEVI void wgmma_m64n192k16_ss(float (&d)[96], uint64_t descA, uint64_t descB, int scaleD) {
  asm volatile("{\n.reg .pred p;\nsetp.ne.b32 p, %98, 0;\nwgmma.mma_async.sync.aligned.m64n192k16.f32.bf16.bf16 {%0, %1, %2, %3, %4, %5, %6, %7, %8, %9, %10, %11, %12, %13, %14, %15, %16, %17, %18, %19, %20, %21, %22, %23, %24, %25, %26, %27, %28, %29, %30, %31, %32, %33, %34, %35, %36, %37, %38, %39, %40, %41, %42, %43, %44, %45, %46, %47, %48, %49, %50, %51, %52, %53, %54, %55, %56, %57, %58, %59, %60, %61, %62, %63, %64, %65, %66, %67, %68, %69, %70, %71, %72, %73, %74, %75, %76, %77, %78, %79, %80, %81, %82, %83, %84, %85, %86, %87, %88, %89, %90, %91, %92, %93, %94, %95}, %96, %97, p, 1, 1, %99, %100;\n}\n"
    : "+f"(d[0]), "+f"(d[1]), "+f"(d[2]), "+f"(d[3]), "+f"(d[4]), "+f"(d[5]), "+f"(d[6]), "+f"(d[7]), "+f"(d[8]), "+f"(d[9]), "+f"(d[10]), "+f"(d[11]), "+f"(d[12]), "+f"(d[13]), "+f"(d[14]), "+f"(d[15]), "+f"(d[16]), "+f"(d[17]), "+f"(d[18]), "+f"(d[19]), "+f"(d[20]), "+f"(d[21]), "+f"(d[22]), "+f"(d[23]), "+f"(d[24]), "+f"(d[25]), "+f"(d[26]), "+f"(d[27]), "+f"(d[28]), "+f"(d[29]), "+f"(d[30]), "+f"(d[31]), "+f"(d[32]), "+f"(d[33]), "+f"(d[34]), "+f"(d[35]), "+f"(d[36]), "+f"(d[37]), "+f"(d[38]), "+f"(d[39]), "+f"(d[40]), "+f"(d[41]), "+f"(d[42]), "+f"(d[43]), "+f"(d[44]), "+f"(d[45]), "+f"(d[46]), "+f"(d[47]), "+f"(d[48]), "+f"(d[49]), "+f"(d[50]), "+f"(d[51]), "+f"(d[52]), "+f"(d[53]), "+f"(d[54]), "+f"(d[55]), "+f"(d[56]), "+f"(d[57]), "+f"(d[58]), "+f"(d[59]), "+f"(d[60]), "+f"(d[61]), "+f"(d[62]), "+f"(d[63]), "+f"(d[64]), "+f"(d[65]), "+f"(d[66]), "+f"(d[67]), "+f"(d[68]), "+f"(d[69]), "+f"(d[70]), "+f"(d[71]), "+f"(d[72]), "+f"(d[73]), "+f"(d[74]), "+f"(d[75]), "+f"(d[76]), "+f"(d[77]), "+f"(d[78]), "+f"(d[79]), "+f"(d[80]), "+f"(d[81]), "+f"(d[82]), "+f"(d[83]), "+f"(d[84]), "+f"(d[85]), "+f"(d[86]), "+f"(d[87]), "+f"(d[88]), "+f"(d[89]), "+f"(d[90]), "+f"(d[91]), "+f"(d[92]), "+f"(d[93]), "+f"(d[94]), "+f"(d[95])
    : "l"(descA), "l"(descB), "r"(scaleD), "n"(TA), "n"(TB));
}

template <int TA, int TB> DEVI void wgmma_m64n48k16_ss(float (&d)[24], uint64_t descA, uint64_t descB, int scaleD) {
  asm volatile("{\n.reg .pred p;\nsetp.ne.b32 p, %26, 0;\nwgmma.mma_async.sync.aligned.m64n48k16.f32.bf16.bf16 {%0, %1, %2, %3, %4, %5, %6, %7, %8, %9, %10, %11, %12, %13, %14, %15, %16, %17, %18, %19, %20, %21, %22, %23}, %24, %25, p, 1, 1, %27, %28;\n}\n"
    : "+f"(d[0]), "+f"(d[1]), "+f"(d[2]), "+f"(d[3]), "+f"(d[4]), "+f"(d[5]), "+f"(d[6]), "+f"(d[7]), "+f"(d[8]), "+f"(d[9]), "+f"(d[10]), "+f"(d[11]), "+f"(d[12]), "+f"(d[13]), "+f"(d[14]), "+f"(d[15]), "+f"(d[16]), "+f"(d[17]), "+f"(d[18]), "+f"(d[19]), "+f"(d[20]), "+f"(d[21]), "+f"(d[22]), "+f"(d[23])
    : "l"(descA), "l"(descB), "r"(scaleD), "n"(TA), "n"(TB));
}

constexpr int kS = 112;
constexpr int kStripCtas = 112;
constexpr int kProjCtas = 20;
constexpr int kThreads = 512;
constexpr int kArr = 29;
constexpr int kExch = 26;
constexpr int kSteps = 28;
constexpr int kTiles = kSteps * 28;
constexpr int kOTileBytes = 64 * 192 * 2;
#define DEV_NB 7
constexpr int kTailBands = DEV_NB;
constexpr int kProjTiles = (kSteps - kTailBands) * 28;
constexpr int kHaloBytes = 3 * 784 - 16, kHaloPitch = 2432;

__device__ __align__(1024) uint8_t g_o[(size_t)kTiles * kOTileBytes];
__device__ __align__(1024) uint8_t g_halo[(size_t)kStripCtas * 2 * kArr * kHaloPitch];
__device__ uint32_t g_hflag[kStripCtas * 32];
__device__ uint32_t g_oflag[28 * 32];
__device__ uint32_t g_wflag[4 * 32];
__device__ __align__(1024) uint8_t g_wop[4 * 3 * 192 * 32];
__device__ uint32_t g_epoch[132 * 32];

namespace ka {
constexpr int kWAtom = 192 * 32;
constexpr int kWBytes = 9 * kWAtom;
constexpr int kXBytes = 64 * 384;
constexpr int kXStages = 2;
constexpr int kCol = 784;
constexpr int kQCol = 400;
constexpr int kSlot = 22 * kCol;
constexpr int kQSlot = 16 * kQCol;
constexpr int kQOff = 5 * kSlot + 32;
constexpr int kOffX = kWBytes;
constexpr int kOffRing = kOffX + kXStages * kXBytes;
constexpr int kOffWo = kOffX;
constexpr int kOffStage = kOffWo + 3 * kWAtom, kOffStage2 = 2 * kOTileBytes;
#define DEV_EARLY 0
constexpr int kEarly = DEV_EARLY;
DEVI uint32_t tail_buf(int i) { return i == 2 ? kOffX + kXBytes : i * kOTileBytes; }
constexpr int kHaloBox = 27 * 128;
constexpr int kOffBar = kOffRing + kQOff + 6 * kQSlot;
constexpr int kBarX = 0, kBarXe = 256, kBarWr = 512, kBarFull = 768, kBarT = 1024, kBarTe = 1152, kBarO = 1280, kBarW = 1536;
constexpr int kSmemBytes = kOffBar + 1536 + 16;
#define DEV_D 6
#define DEV_DI 6
constexpr int kDi = DEV_DI;
constexpr int kD = DEV_D;
#define DEV_PFA 4
constexpr int kPrefetch = DEV_PFA;
#define DEV_BARPOS 1
#define DEV_VPOS 2
#define DEV_LOCK 1
#define DEV_VWAIT 0
#define DEV_STAG 0
#define DEV_NS 100
#define POLL ld_acquire
#define DEV_HSUM 1
#define SUM(x) x
#define DEV_ORD 0
#define DEV_NV 0
#define DEV_X0 1
#define DEV_WOD 2000
#define AWAIT mbar_wait
#define DEV_WTMA 2
#define DEV_X1 0
#define DEV_HGATE 1
#define DEV_XDEF 0
#define DEV_WF 0
#define DEV_FB 0
#define FENCE_A sched_fence(s.junk)
#define FENCE_B
static_assert(kPrefetch == 4, "prefetch schedule");
static_assert(kDi + kSteps - 1 >= kArr && kDi >= 3 && kD - kDi < 5, "burst barriers");
static_assert(kD <= 6 && kD >= 2, "ring");
}

namespace kb {
constexpr int kWoBlk = 192 * 128;
constexpr int kStages = 6;
constexpr int kOffA = 3 * kWoBlk;
constexpr int kOffBar = kOffA + kStages * kOTileBytes;
constexpr int kSmemBytes = kOffBar + 128;
}

constexpr int kSmemBytes = ka::kSmemBytes > kb::kSmemBytes ? ka::kSmemBytes : kb::kSmemBytes;
static_assert(kSmemBytes <= 232448, "smem");

#define TRACE(idx)
#define GT(i)
#define TRACEB TRACE

DEVI void mbar_wait_sleep(uint32_t bar, uint32_t parity) {
  uint32_t it = 0;
  while (!mbar_test_wait(bar, parity)) {
    if (DEV_NS) __nanosleep(DEV_NS);
    if (++it > LIMIT) { BAIL(bar & 0xfffff); break; }
  }
}

DEVI void publish_fence() {
  fence_proxy_async_global();
  fence_gpu();
}

struct AttnState {
  uint32_t kf[5][3][4];
  uint32_t vf[5][3][4];
  float bias[5][4];
  uint32_t p[5][2];
  uint32_t q[6];
  float sum0, sum1;
  uint32_t kaddr, vaddr, qaddr, bar, rdy, junk, fence;
  uint32_t pm;
  uint32_t* optr;
};

#define ATRACE(k)
#define TRBASE (sbase + kTraceOff)

DEVI uint32_t sched_fence() {
  uint32_t t;
  asm volatile("mov.u32 %0, %clock;" : "=r"(t)::"memory");
  return t;
}

DEVI void store_o(AttnState& s, float (&o)[3][4], float i0, float i1, int g) {
  if (g >= 0) {
#pragma unroll
    for (int mt = 0; mt < 3; mt++) {
      s.optr[(2 * mt) * 32] = pack_bf16(o[mt][0] * i0, o[mt][1] * i1);
      s.optr[(2 * mt + 1) * 32] = pack_bf16(o[mt][2] * i0, o[mt][3] * i1);
    }
    __syncwarp();
    if (s.pm & 64) mbar_arrive(s.bar + ka::kBarO + 8 * g);
  }
  s.optr += 28 * kOTileBytes / 4;
}

DEVI void load_q(AttnState& s) {
  ldmatrix_x4(s.q[0], s.q[1], s.q[2], s.q[3], s.qaddr);
  ldmatrix_x2(s.q[4], s.q[5], s.qaddr + 64);
}

template <int PH>
DEVI void load_k(AttnState& s) {
  constexpr int R = (2 * PH) % 5, SL = ((PH + 1) % 5) * ka::kSlot;
#pragma unroll
  for (int ks = 0; ks < 3; ks++) ldmatrix_x4(s.kf[(R + 3) % 5][ks], s.kaddr + SL + ks * 32);
#pragma unroll
  for (int ks = 0; ks < 3; ks++) ldmatrix_x4(s.kf[(R + 4) % 5][ks], s.kaddr + SL + 384 + ks * 32);
}

template <int PH>
DEVI void attn_step(AttnState& s, int g, int warp) {
  using namespace ka;
  constexpr int R = (2 * PH) % 5, N0 = (R + 3) % 5, N1 = (R + 4) % 5;
  constexpr int SL = ((PH + 1) % 5) * kSlot;
  if (PH == 0 && g == 0) {
    mbar_wait(s.rdy, 0);
#pragma unroll
    for (int k = 0; k < 3; k++) {
      ldmatrix_x4(s.kf[1][k], s.kaddr + k * 32);
      ldmatrix_x4(s.kf[2][k], s.kaddr + 384 + k * 32);
      ldmatrix_x4_t(s.vf[1][k], s.vaddr + k * 32);
      ldmatrix_x4_t(s.vf[2][k], s.vaddr + 384 + k * 32);
      s.vf[0][k][0] = s.vf[0][k][1] = s.vf[0][k][2] = s.vf[0][k][3] = 0u;
    }
    named_bar_arrive(13, 384);
  }
  {
    uint32_t rb = s.rdy + 8 * (g + 1);
    if (PH >= 3 && g < 0) rb = s.bar + kBarFull - 8;
    if (PH <= 2 && g + 1 >= kExch && warp < 4) rb = s.bar + kBarWr + 8 * kArr;
    mbar_wait(rb, 0);
  }
  const int ta = g + (warp < 4 ? kD : kDi);
  const bool arr = g >= 0 && ta <= kArr;
  const int bid = 2 + (warp < 4 ? (PH + kD) % 5 : (PH + kDi) % 5);
  ATRACE(0);
  float t[5][4], o[3][4], z[4];
  const uint32_t ones[4] = {0x3F803F80u, s.kaddr, 0x3F803F80u, s.vaddr};
#define PV(i) _Pragma("unroll") for (int mt = 0; mt < 3; mt++) mma16816(o[mt], s.vf[(R + 3 + (i)) % 5][mt], s.p[i][0], s.p[i][1]); \
              SUM(mma16816(z, ones, s.p[i][0], s.p[i][1]);)
#define QK0(i) mma16816_c(t[i], s.kf[(R + (i)) % 5][0], s.q[0], s.q[1], s.bias[i]);
#define QK(i, ks) mma16816(t[i], s.kf[(R + (i)) % 5][ks], s.q[2 * (ks)], s.q[2 * (ks) + 1]);
#define LDV(n) ldmatrix_x4_t(s.vf[(n) < 3 ? N0 : N1][(n) % 3], s.vaddr + SL + ((n) / 3) * 384 + ((n) % 3) * 32);
#define LDK(n) ldmatrix_x4(s.kf[(n) & 1 ? N1 : N0][(n) >> 1], s.kaddr + SL + ((n) & 1) * 384 + ((n) >> 1) * 32);
  load_q(s);
  LDK(0) LDK(1) LDK(2) LDK(3) LDK(4) LDK(5)
#pragma unroll
  for (int mt = 0; mt < 3; mt++) mma16816_z(o[mt], s.vf[N0][mt], s.p[0][0], s.p[0][1]);
  SUM(mma16816_z(z, ones, s.p[0][0], s.p[0][1]);)
  PV(1) PV(2) PV(3) PV(4)
  const uint32_t f1 = sched_fence();
  s.junk ^= s.fence;
  if (DEV_NV < 6) LDV(5)
  if (DEV_NV < 5) LDV(4)
  if (DEV_NV < 4) LDV(3)
  if (DEV_NV < 3) LDV(2)
  if (DEV_NV < 2) LDV(1)
  if (DEV_NV < 1) LDV(0)
  QK0(0) QK0(1) QK0(2) QK0(3) QK0(4)
  QK(0, 1) QK(1, 1) QK(2, 1) QK(3, 1) QK(4, 1)
  QK(0, 2) QK(1, 2) QK(2, 2) QK(3, 2) QK(4, 2)
  const uint32_t f2 = sched_fence();
  if (arr) named_bar_arrive(bid, 384);
  s.fence = sched_fence();
  ATRACE(1);
  uint32_t pm = s.pm;
  if (PH == 0 && g == 0) pm &= ~0x3Fu;
  if (PH == 2 && g == kSteps - 1) pm |= 0x3Fu;
  float x[7][2];
  sel2<1>(pm, x[0][0], x[0][1], t[0][0], t[0][1], t[3][2], t[3][3]);
  sel2<2>(pm, x[1][0], x[1][1], t[0][2], t[0][3], t[4][0], t[4][1]);
  sel2<4>(pm, x[2][0], x[2][1], t[1][0], t[1][1], t[4][2], t[4][3]);
#pragma unroll
  for (int e = 0; e < 2; e++) {
    x[3][e] = t[1][2 + e]; x[4][e] = t[2][e]; x[5][e] = t[2][2 + e]; x[6][e] = t[3][e];
  }
  float m0 = fmaxf(fmaxf(fmaxf(x[0][0], x[1][0]), fmaxf(x[2][0], x[3][0])), fmaxf(fmaxf(x[4][0], x[5][0]), x[6][0]));
  float m1 = fmaxf(fmaxf(fmaxf(x[0][1], x[1][1]), fmaxf(x[2][1], x[3][1])), fmaxf(fmaxf(x[4][1], x[5][1]), x[6][1]));
#pragma unroll
  for (int d = 4; d <= 16; d <<= 1) {
    m0 = fmaxf(m0, __shfl_xor_sync(0xffffffffu, m0, d));
    m1 = fmaxf(m1, __shfl_xor_sync(0xffffffffu, m1, d));
  }
  uint32_t f4 = 0;
  if (DEV_NV > 0) {
    f4 = sched_fence();
    LDV(0)
    if (DEV_NV > 1) LDV(1)
    if (DEV_NV > 2) LDV(2)
    if (DEV_NV > 3) LDV(3)
    if (DEV_NV > 4) LDV(4)
    if (DEV_NV > 5) LDV(5)
  }
  const float c = 0.14433756729740643f * 1.4426950408889634f;
  const float n0 = -m0 * c, n1 = -m1 * c;
  uint32_t pt[7];
#pragma unroll
  for (int i = 0; i < 7; i++) {
    const float e0 = ex2(fmaf(x[i][0], c, n0)), e1 = ex2(fmaf(x[i][1], c, n1));
    pt[i] = movmatrix_t(pack_bf16(e0, e1));
  }
  split2<8>(pm, s.p[0][0], s.p[3][1], pt[0]);
  split2<16>(pm, s.p[0][1], s.p[4][0], pt[1]);
  split2<32>(pm, s.p[1][0], s.p[4][1], pt[2]);
  s.p[1][1] = pt[3]; s.p[2][0] = pt[4]; s.p[2][1] = pt[5]; s.p[3][0] = pt[6];
#pragma unroll
  for (int i = 0; i < 5; i++) asm volatile("" : "+r"(s.p[i][0]), "+r"(s.p[i][1])::"memory");
  store_o(s, o, rcp_approx(z[0]), rcp_approx(z[1]), g - 1);
  s.junk ^= f1 ^ f2;
  s.qaddr += kQSlot;
  if (s.qaddr >= s.bar) s.qaddr -= 6 * kQSlot;
  s.fence ^= f4;
  asm volatile("" : "+r"(s.junk)::"memory");
  ATRACE(2);
}

__global__ void __launch_bounds__(kThreads, 1)
nat_kernel(const __nv_bfloat16* __restrict__ wqkv, const __nv_bfloat16* __restrict__ wo,
           const __nv_bfloat16* __restrict__ rpb, __nv_bfloat16* __restrict__ out,
           const __grid_constant__ CUtensorMap tm_x, const __grid_constant__ CUtensorMap tm_w,
           const __grid_constant__ CUtensorMap tm_h,
           const __grid_constant__ CUtensorMap tm_wo, const __grid_constant__ CUtensorMap tm_out) {
  extern __shared__ __align__(1024) uint8_t smem_raw[];
  const uint32_t sbase = smem_u32(smem_raw);
  if (sbase & 1023u) __trap();
  const int warp = __shfl_sync(0xffffffffu, (int)(threadIdx.x >> 5), 0), lane = threadIdx.x & 31;
  const int wg = warp >> 2, wl = warp & 3;
  const int cta = blockIdx.x;
  const bool strip_cta = cta < kStripCtas;
  const int head = cta & 3, ps = cta >> 2, par = ps / 7, strip = ps - 7 * par;
  if (threadIdx.x == 0) TRACE(0);

  if (strip_cta && threadIdx.x == 384) {
    using namespace ka;
    const uint32_t bar = sbase + kOffBar;
    mbar_init(bar + kBarX, 1);
    mbar_expect_tx(bar + kBarX, kXBytes + DEV_WTMA * 3 * kWAtom);
    tma_load_5d(sbase + kOffX, &tm_x, bar + kBarX, 0, 16 * strip, -1, 3 * (par & 1), par >> 1);
#pragma unroll
    for (int i = 9 - 3 * DEV_WTMA; i < 9; i++)
      tma_load_2d(sbase + i * kWAtom, &tm_w, bar + kBarX, (i / 3) * 192 + head * 48 + (i % 3) * 16, 0);
    TRACE(10);
  }
  __syncwarp();
  if (strip_cta && threadIdx.x < 384) {
    using namespace ka;
    constexpr int kSec = 3 - DEV_WTMA;
    uint4 v[3 * kSec];
    const int wk = (int)threadIdx.x / 6, wu = (int)threadIdx.x - 6 * wk;
    const uint8_t* src = reinterpret_cast<const uint8_t*>(wqkv) + wk * 1152 + head * 96 + wu * 16;
    if (warp == 0) TRACE(9);
#pragma unroll
    for (int i = 0; i < 3 * kSec; i++) v[i] = ldg128(src + (i / kSec) * 64 * 1152 + (i % kSec) * 384);
    if (warp == 0) TRACE(4);
    const uint32_t dst = sbase + (wu >> 1) * kWAtom + wk * 32 + (((wu ^ (wk >> 2)) & 1) << 4);
#pragma unroll
    for (int i = 0; i < 3 * kSec; i++) sts128(dst + (i / kSec) * 64 * 32 + (i % kSec) * 3 * kWAtom, v[i]);
    if (warp == 0) TRACE(6);
    fence_proxy_async();
  }
  if (threadIdx.x == 480) GT(0);

  if (strip_cta) {
    using namespace ka;
    const uint32_t bar = sbase + kOffBar, ring = sbase + kOffRing;
    if (wg < 2) {
      named_bar_arrive(14, 416);
      reg_inc<184>();
      named_bar_sync(0, 512);
      AttnState s;
      const int j = warp < 2 ? warp : (warp < 4 ? warp + 4 : warp - 2);
      const int qc0 = 16 * strip + 2 * j;
      s.rdy = bar + (warp < 4 ? kBarFull : kBarWr);
      if (warp < 4) {
#pragma unroll
        for (int a = kDi; a < kD; a++) named_bar_arrive(2 + a % 5, 384);
      }
      const int kc0 = clampi(qc0 - 3, 0, kS - 8);
      const uint32_t colb = ring + (kc0 - (16 * strip - 3) + (lane & 7)) * kCol;
      s.kaddr = colb + ((lane >> 3) & 1) * 192 + (lane >> 4) * 16;
      s.vaddr = colb + 96 + (lane >> 4) * 192 + ((lane >> 3) & 1) * 16;
      {
        const int qr = (lane & 7) >> 1;
        const uint32_t qa = ring + kQOff + (2 * j + (lane & 1)) * kQCol + (lane >> 3) * 16;
        s.qaddr = qa + (qr == 3 ? 5 * kQSlot : 4 * kQSlot + (qr + 1) * 96);
      }
      s.bar = bar;
      s.optr = reinterpret_cast<uint32_t*>(g_o + (size_t)(ps * 4 + head) * 6144 + j * 768) + lane - 3 * 28 * kOTileBytes / 4;
      {
        const int kc = kc0 + (lane >> 2);
        const unsigned short* r = reinterpret_cast<const unsigned short*>(rpb) + head * 169 + (3 - (lane & 3)) * 13 + kc - qc0 + 6;
        const int sw0 = clampi(qc0 - 3, 0, kS - 7), sw1 = clampi(qc0 - 2, 0, kS - 7);
        const bool ok0 = kc >= sw0 && kc < sw0 + 7, ok1 = kc >= sw1 && kc < sw1 + 7;
#pragma unroll
        for (int i = 0; i < 10; i++) {
          const uint32_t v0 = ok0 ? (uint32_t)__ldg(r + i * 13) : 0xFF80u;
          const uint32_t v1 = ok1 ? (uint32_t)__ldg(r + i * 13 - 1) : 0xFF80u;
          s.bias[i >> 1][2 * (i & 1)] = __uint_as_float(v0 << 16) * 6.928203230275509f;
          s.bias[i >> 1][2 * (i & 1) + 1] = __uint_as_float(v1 << 16) * 6.928203230275509f;
        }
      }
#pragma unroll
      for (int i = 0; i < 5; i++) {
        s.p[i][0] = s.p[i][1] = 0u;
#pragma unroll
        for (int k = 0; k < 3; k++)
#pragma unroll
          for (int c = 0; c < 4; c++) s.kf[i][k][c] = s.vf[i][k][c] = 0u;
      }
      s.sum0 = s.sum1 = 1.f;
      s.junk = s.fence = 0;
      s.pm = (7u << (lane & 3) & 7u) | ((7u << (lane >> 3) & 7u) << 3) | (lane == 0 ? 64u : 0u);
      s.pm = __shfl_sync(0xffffffffu, s.pm, lane);
#pragma unroll 1
      for (int g = -2; g < kSteps; g += 5) {
        attn_step<3>(s, g, warp);
        attn_step<4>(s, g + 1, warp);
        attn_step<0>(s, g + 2, warp);
        attn_step<1>(s, g + 3, warp);
        attn_step<2>(s, g + 4, warp);
      }
      {
        float o[3][4], z[4];
        const uint32_t ones[4] = {0x3F803F80u, s.kaddr, 0x3F803F80u, s.vaddr};
#pragma unroll
        for (int mt = 0; mt < 3; mt++) mma16816_z(o[mt], s.vf[4][mt], s.p[0][0], s.p[0][1]);
        mma16816_z(z, ones, s.p[0][0], s.p[0][1]);
#pragma unroll
        for (int i = 1; i < 5; i++) {
#pragma unroll
          for (int mt = 0; mt < 3; mt++) mma16816(o[mt], s.vf[i - 1][mt], s.p[i][0], s.p[i][1]);
          mma16816(z, ones, s.p[i][0], s.p[i][1]);
        }
        store_o(s, o, rcp_approx(z[0]), rcp_approx(z[1]), kSteps - 1);
      }
      s.junk ^= s.fence;
      if (s.junk == 0x9e3779b9u) sts32(bar + kBarW, 0);
      if (warp == 0) TRACE(1);
    } else if (wg == 2) {
      reg_dec<104>();
      const int col = ((lane >> 3) & 1) * 8 + (lane & 7);
      uint32_t kva = ring + (3 + col) * kCol + wl * 192 + (lane >> 4) * 16;
      uint32_t qa = ring + kQOff + col * kQCol + wl * 96 + (lane >> 4) * 16;
      const uint32_t alo = (uint32_t)make_desc(sbase + kOffX, 16, 1024, 1), blo = (uint32_t)make_desc(sbase, kWAtom, 256, 3);
      constexpr uint32_t ahi = (1u << 30) | (1024 >> 4), bhi = (3u << 30) | (256 >> 4);
      if (wl == 0) TRACE(2);
      int bid = 2;
      named_bar_sync(14, 416);
      if (wl == 0) TRACE(7);
      mbar_wait(bar + kBarX, 0);
      if (wl == 0) TRACE(16 + 0);
#pragma unroll 1
      for (int a = 0; a <= kArr; a++) {
        float acc[72];
        const uint32_t al = alo + (a & 1) * (kXBytes >> 4);
        if (a >= kDi) named_bar_sync(bid, 384);
        if (wl == 0) TRACE(16 + a * 4 + 1);
        wg_fence();
#pragma unroll
        for (int k = 0; k < 12; k++)
          wgmma_m64n144k16_ss<0, 1>(acc, desc64(al + (((k >> 2) * 8192 + (k & 3) * 32) >> 4), ahi), desc64(blo + k * 32, bhi), k != 0);
        wg_commit();
        bid = bid == 6 ? 2 : bid + 1;
        if (a == 0) named_bar_sync(0, 512);
        const bool xok = mbar_test_wait(bar + kBarX + 8 * (a + 1), 0);
        if (a == kArr) {
          const int i = (16 * wl + col) & 31, r = i / 3, c = i - 3 * r;
          qa = sbase + kOffStage + lane * 16;
          kva = i < 27 ? ring + ((kExch + (r >> 2)) % 5) * kSlot + ((wl >> 1) * 19 + c) * kCol + (r & 3) * 192 + (lane >> 4) * 16 : qa;
        }
        wg_wait<0>();
        fence_regs(acc);
        if (lane == 0) mbar_arrive(bar + kBarXe + 8 * a);
        if (a == 5) named_bar_sync(13, 384);
        if (wl == 0) TRACE(16 + a * 4 + 2);
#pragma unroll
        for (int jp = 0; jp < 9; jp++) {
          const int j = jp < 6 ? jp + 3 : jp - 6;
          stmatrix_x4(j < 3 ? qa + j * 32 : kva + (j - 3) * 32, pack_bf16(acc[8 * j + 0], acc[8 * j + 1]),
                      pack_bf16(acc[8 * j + 2], acc[8 * j + 3]), pack_bf16(acc[8 * j + 4], acc[8 * j + 5]),
                      pack_bf16(acc[8 * j + 6], acc[8 * j + 7]));
        }
        __syncwarp();
        if (lane == 0) mbar_arrive(bar + kBarWr + 8 * a);
        if (wl == 0) TRACE(16 + a * 4 + 3);
        if (!xok) mbar_wait(bar + kBarX + 8 * (a + 1), 0);
        if (wl == 0) TRACE(16 + (a + 1) * 4 + 0);
        kva += kSlot;
        if (kva >= ring + 5 * kSlot) kva -= 5 * kSlot;
        qa += kQSlot;
        if (qa >= bar) qa -= 6 * kQSlot;
      }
      {
        const uint32_t wlo = (uint32_t)make_desc(sbase + kOffWo, kWAtom, 256, 3);
        const int n = lane & 7, j = 2 * wl + ((lane >> 3) & 1);
        const uint32_t sta = sbase + ((2 * j + (n & 1)) * 4 + (n >> 1)) * 96 + (lane >> 4) * 16;
        auto issue = [&](float (&acc)[24], int i) {
          mbar_wait(bar + kBarT + 64 + 8 * i, 0);
          if (wl == 0) TRACE(144 + i * 2);
          const uint32_t tlo = (uint32_t)make_desc(sbase + tail_buf(i % 3), 128, 768, 0);
          wg_fence();
#pragma unroll
          for (int k = 0; k < 12; k++)
            wgmma_m64n48k16_ss<1, 1>(acc, desc64(tlo + (((k / 3) * 6144 + (k % 3) * 256) >> 4), 768 >> 4), desc64(wlo + k * 32, bhi), k != 0);
          wg_commit();
        };
        auto finish = [&](float (&acc)[24], int i) {
          const uint32_t stg = (i & 1) ? kOffStage : kOffStage2;
          fence_regs(acc);
          if (lane == 0) mbar_arrive(bar + kBarTe + 8 * i);
#pragma unroll
          for (int jp = 0; jp < 3; jp++)
            stmatrix_x4(sta + stg + jp * 32, pack_bf16(acc[8 * jp + 0], acc[8 * jp + 1]), pack_bf16(acc[8 * jp + 2], acc[8 * jp + 3]),
                        pack_bf16(acc[8 * jp + 4], acc[8 * jp + 5]), pack_bf16(acc[8 * jp + 6], acc[8 * jp + 7]));
          fence_proxy_async();
          if (threadIdx.x == 256) bulk_wait_read();
          named_bar_sync(1, 128);
          if (threadIdx.x == 256) {
            tma_store_5d(&tm_out, sbase + stg, head * 48, 4 * (kSteps - kTailBands + i), 16 * strip, par & 1, par >> 1);
            bulk_commit();
          }
          if (wl == 0) TRACE(145 + i * 2);
        };
        float acc0[24], acc1[24];
        named_bar_sync(1, 128);
        issue(acc0, 0);
#pragma unroll 1
        for (int i = 0; i < kEarly; i += 2) {
          issue(acc1, i + 1);
          wg_wait<1>();
          finish(acc0, i);
          issue(acc0, i + 2);
          wg_wait<1>();
          finish(acc1, i + 1);
        }
        wg_wait<0>();
        finish(acc0, kEarly);
#pragma unroll 1
        for (int i = kEarly + 1; i < kTailBands; i++) {
          issue(acc0, i);
          wg_wait<0>();
          finish(acc0, i);
        }
        if (threadIdx.x == 256) {
          bulk_wait<0>();
          GT(2);
        }
      }
    } else {
      if (wl == 0) named_bar_arrive(14, 416);
      if (lane == 0) {
        const uint32_t b0 = bar + 64 * wl;
        if (wl == 1 && head == 1) tma_prefetch_5d(&tm_x, 0, 16 * strip, 3, 3 * (par & 1), par >> 1);
#pragma unroll
        for (int i = 0; i < 64; i += 8) {
          if (i || wl) mbar_init(b0 + kBarX + i, 1);
          mbar_init(b0 + kBarXe + i, 4);
          mbar_init(b0 + kBarWr + i, i == 56 && wl == 3 ? 1 : 4);
          mbar_init(b0 + kBarFull + i, 2);
          mbar_init(b0 + kBarO + i, 8);
          mbar_init(b0 + kBarT + i, wl < 2 ? 1 : 4);
        }
#pragma unroll
        for (int i = 0; i < 64; i += 8)
          if (i || wl)
            mbar_expect_tx(b0 + kBarX + i, wl < 3 || i < 40 ? kXBytes : (i == 40 ? 6 * kHaloBox : 3 * kWAtom));
        if (wl == 1) {
#pragma unroll
          for (int i = 0; i < kTailBands; i++) mbar_expect_tx(bar + kBarT + 64 + 8 * i, kOTileBytes);
        }
        if (wl == 2) sts32(bar + kBarW + 8, 0);
        if (wl == 3) mbar_arrive(bar + kBarFull - 8);
        fence_mbar_init();
        if (wl == 0) {
          tma_load_5d(sbase + kOffX + kXBytes, &tm_x, bar + kBarX + 8, 0, 16 * strip, 3, 3 * (par & 1), par >> 1);
          tma_prefetch_5d(&tm_x, 0, 16 * strip, 4 * (2 + ((head - 2) & 3)) - 1, 3 * (par & 1), par >> 1);
          TRACE(5);
        }
      }
      __syncwarp();
      reg_dec<40>();
      const uint32_t ep = ld_relaxed(&g_epoch[cta * 32 + wl]) * 32u;
      named_bar_sync(0, 512);
      if (wl == 0) {
        if (lane == 0) {
#pragma unroll 1
          for (int a = 2; a < kArr; a++) {
            mbar_wait_sleep(bar + kBarXe + 8 * (a - 2), 0);
            if (DEV_XDEF && a >= 4 && a - 2 < kExch) {
#pragma unroll 1
              for (int it = 0; it < DEV_XDEF && lds32v(bar + kBarW + 8) < a - 1; it++) __nanosleep(50);
            }
            tma_load_5d(sbase + kOffX + (a & 1) * kXBytes, &tm_x, bar + kBarX + 8 * a, 0, 16 * strip, 4 * a - 1,
                        3 * (par & 1), par >> 1);
            const int ap = a + kPrefetch;
            if (ap < kArr && (ap & 3) == head) tma_prefetch_5d(&tm_x, 0, 16 * strip, 4 * ap - 1, 3 * (par & 1), par >> 1);
          }
          uint32_t it = 0;
          while ((int)(ld_acquire(&g_wflag[head * 32]) - (ep + 1)) < 0)
            if (++it > LIMIT) { BAIL(0x5000000); break; }
                    mbar_wait(bar + kBarXe + 8 * (kArr - 2), 0);
#pragma unroll 1
          for (int i = 0; i < 6; i++)
            tma_load_5d(sbase + kOffX + kXBytes + (i >> 1) * 8192 + (i & 1) * 4096, &tm_h, bar + kBarX + 8 * kArr, 0,
                        16 * strip - 3 + 19 * (i & 1), 4 * kExch - 1, 3 * (par & 1) + (i >> 1), par >> 1);
          mbar_wait(bar + kBarXe + 8 * (kArr - 1), 0);
          bulk_load(sbase + kOffWo, g_wop + head * 3 * kWAtom, 3 * kWAtom, bar + kBarX + 8 * (kArr + 1));
        }
        __syncwarp();
        if (lane < 4) {
          int buf = 0;
          uint32_t seen = ep;
#pragma unroll 1
          for (int i = 0; i < kTailBands; i++) {
            const int g = kSteps - kTailBands + i;
            if (i >= 3) mbar_wait(bar + kBarTe + 8 * (i - 3), 0);
            uint32_t it = 0;
            while (!__all_sync(15u, (int)(seen - (ep + g + 1)) >= 0)) {
              seen = ld_acquire(&g_oflag[ps * 32 + lane]);
              if (++it > LIMIT) { BAIL(0x3000000 + g); break; }
            }
            if (i == 0) {
              mbar_wait(bar + kBarXe + 8 * kArr, 0);
            }
            if (lane == 0) {
              bulk_load(sbase + tail_buf(buf), g_o + (size_t)(g * 28 + ps) * kOTileBytes, kOTileBytes, bar + kBarT + 64 + 8 * i);
            }
            __syncwarp(15u);
            buf = buf == 2 ? 0 : buf + 1;
          }
        }
      } else {
        const int p = wl - 1;
        if (lane < 2) {
          const bool on = lane == 0 ? strip > 0 : strip < 6;
          const int nb = on ? cta + (lane == 0 ? -4 : 4) : cta;
          const uint32_t bytes = (strip > 0 && strip < 6) ? 2 * kHaloBytes : kHaloBytes;
          int slot = p, g = 0;
#pragma unroll 1
          for (int a = p; a < kExch; a += 3) {
            AWAIT(bar + kBarWr + 8 * a, 0);
            const uint32_t sl = ring + slot * kSlot;
            fence_proxy_async();
            if (on) bulk_store(g_halo + (size_t)((cta * 2 + lane) * kArr + a) * kHaloPitch, sl + (3 + 13 * lane) * kCol, kHaloBytes);
            bulk_commit();
            if (DEV_XDEF && lane == 1) sts32(bar + kBarW + 8, a + 1);
            while (mbar_test_wait(bar + kBarO + 8 * g, 0)) g++;
            bulk_wait<0>();
            TRACE(160 + a * 4 + 0);
            publish_fence();
            st_relaxed(&g_hflag[cta * 32 + 4 * lane + p], ep + a + 1);
            if (lane == 0) {
              if (g) red_max(&g_oflag[ps * 32 + head], ep + g);
              mbar_expect_tx(bar + kBarFull + 8 * a, bytes);
            } else {
              mbar_arrive(bar + kBarFull + 8 * a);
            }
            TRACE(160 + a * 4 + 1);
            uint32_t it = 0;
            while (true) {
              const bool ok = !on || (int)(ld_acquire(&g_hflag[nb * 32 + 4 * (lane ^ 1) + p]) - (ep + a + 1)) >= 0;
              if (__all_sync(3u, ok)) break;
              if (++it > LIMIT) { BAIL(0x1000000 + a); break; }
            }
            TRACE(160 + a * 4 + 2);
            if (on) bulk_load(sl + lane * 19 * kCol, g_halo + (size_t)((nb * 2 + (lane ^ 1)) * kArr + a) * kHaloPitch, kHaloBytes,
                              bar + kBarFull + 8 * a);
            TRACE(160 + a * 4 + 3);
            slot = slot >= 2 ? slot - 2 : slot + 3;
          }
        }
        if (lane == 0) {
#pragma unroll 1
          for (int g = kSteps - 9 + (p + 1) % 3; g < kSteps; g += 3) {
            mbar_wait(bar + kBarO + 8 * g, 0);
            TRACE(370 + g * 2);
            publish_fence();
            red_max(&g_oflag[ps * 32 + head], ep + g + 1);
            TRACE(371 + g * 2);
          }
          if (p == 1) GT(1);
        }
      }
      __syncwarp();
      if (lane == 0) st_relaxed(&g_epoch[cta * 32 + wl], (ep >> 5) + 1);
    }
  } else {
    using namespace kb;
    const uint32_t bar = sbase + kOffBar, sA = sbase + kOffA;
    const int k = cta - kStripCtas;
    if (lane == 0 && warp <= kStages) {
      mbar_init(bar + 8 * warp, 1);
      mbar_init(bar + 64 + 8 * warp, 4);
      fence_mbar_init();
    }
    __syncwarp();
    named_bar_sync(0, 512);
    if (wg < 3) {
      reg_inc<160>();
      if (DEV_WOD) __nanosleep(DEV_WOD);
#pragma unroll
      for (int it = 0; it < 12; it++) {
        const int c = it * 384 + (int)threadIdx.x;
        const int kr = c / 24, u = c - kr * 24;
        const uint4 v = ldg128(wo + kr * 192 + u * 8);
        const uint32_t row = sbase + (u >> 3) * kWoBlk + kr * 128 + (u & 3) * 4;
        const uint32_t h = u & 4;
        sts32(row + (((h + 0) ^ (kr & 7)) << 4), v.x);
        sts32(row + (((h + 1) ^ (kr & 7)) << 4), v.y);
        sts32(row + (((h + 2) ^ (kr & 7)) << 4), v.z);
        sts32(row + (((h + 3) ^ (kr & 7)) << 4), v.w);
      }
      fence_proxy_async();
      named_bar_sync(1, 384);
      const uint64_t dB0 = make_desc(sbase, kWoBlk, 1024, 1);
#pragma unroll 1
      for (int it = wg;; it += 3) {
        const int t = k + it * kProjCtas;
        if (t >= kProjTiles) break;
        const int st = it % kStages;
        mbar_wait(bar + 8 * st, (it / kStages) & 1);
        if (wl == 0) TRACEB(16 + it * 4 + 1);
        float acc[96];
        const uint64_t dA = make_desc(sA + st * kOTileBytes, 128, 768, 0);
        wg_fence();
#pragma unroll
        for (int kk = 0; kk < 12; kk++)
          wgmma_m64n192k16_ss<1, 1>(acc, dA + (uint64_t)(((kk / 3) * 6144 + (kk % 3) * 256) >> 4), dB0 + (uint64_t)((kk * 16 * 128) >> 4), kk != 0);
        wg_commit();
        const int g = t / 28, tp = t - 28 * g, tpar = tp / 7, tstrip = tp - 7 * tpar;
        const int n = lane >> 2;
        const int prow = 2 * (4 * g + (n >> 1)) + (tpar >> 1), pcol = 2 * (16 * tstrip + 4 * wl + (n & 1)) + (tpar & 1);
        uint8_t* oa = reinterpret_cast<uint8_t*>(out) + ((size_t)prow * 224 + pcol) * 384 + (lane & 3) * 16;
        wg_wait<0>();
        fence_regs(acc);
        if (lane == 0) mbar_arrive(bar + 64 + 8 * st);
        if (wl == 0) TRACEB(16 + it * 4 + 2);
#pragma unroll
        for (int u = 0; u < 6; u++) {
          *reinterpret_cast<uint4*>(oa + u * 64) =
              make_uint4(pack_bf16(acc[16 * u + 0], acc[16 * u + 1]), pack_bf16(acc[16 * u + 4], acc[16 * u + 5]),
                         pack_bf16(acc[16 * u + 8], acc[16 * u + 9]), pack_bf16(acc[16 * u + 12], acc[16 * u + 13]));
          *reinterpret_cast<uint4*>(oa + 4 * 384 + u * 64) =
              make_uint4(pack_bf16(acc[16 * u + 2], acc[16 * u + 3]), pack_bf16(acc[16 * u + 6], acc[16 * u + 7]),
                         pack_bf16(acc[16 * u + 10], acc[16 * u + 11]), pack_bf16(acc[16 * u + 14], acc[16 * u + 15]));
        }
        if (wl == 0) TRACEB(16 + it * 4 + 3);
      }
      if (threadIdx.x == 0) GT(1);
    } else {
      reg_dec<32>();
      if (wl == 3 && k < 4) {
        if (lane == 0) {
          const uint32_t e0 = ld_relaxed(&g_epoch[cta * 32 + 3]);
          const uint32_t stg = sA + (kStages - 1) * kOTileBytes;
          if (DEV_WOD) __nanosleep(DEV_WOD);
          mbar_expect_tx(bar + 48, 3 * ka::kWAtom);
#pragma unroll 1
          for (int i = 0; i < 3; i++) tma_load_2d(stg + i * ka::kWAtom, &tm_wo, bar + 48, k * 48 + i * 16, 0);
          mbar_wait(bar + 48, 0);
          bulk_store(g_wop + k * 3 * ka::kWAtom, stg, 3 * ka::kWAtom);
          bulk_commit();
          bulk_wait<0>();
          publish_fence();
          st_relaxed(&g_wflag[k * 32], e0 * 32u + 1);
          st_relaxed(&g_epoch[cta * 32 + 3], e0 + 1);
        }
        __syncwarp();
        named_bar_arrive(2, 64);
      }
      if (wl == 2 && k < 4) named_bar_sync(2, 64);
      if (wl < 3 && lane < 4) {
        const uint32_t e0 = ld_relaxed(&g_epoch[cta * 32 + wl]);
#pragma unroll 1
        for (int it = wl;; it += 3) {
          const int t = k + it * kProjCtas;
          if (t >= kProjTiles) break;
          const int st = it % kStages;
          const int g = t / 28, tp = t - 28 * g;
          if (it >= kStages) mbar_wait(bar + 64 + 8 * st, ((it / kStages) & 1) ^ 1);
          uint32_t sp = 0;
          while (true) {
            const bool ok = (int)(POLL(&g_oflag[tp * 32 + lane]) - (e0 * 32u + g + 1)) >= 0;
            if (__all_sync(15u, ok)) break;
            if (++sp > LIMIT) { BAIL(0x2000000 + t); break; }
          }
          TRACEB(16 + it * 4 + 0);
          if (lane == 0) {
                        mbar_expect_tx(bar + 8 * st, kOTileBytes);
            bulk_load(sA + st * kOTileBytes, g_o + (size_t)t * kOTileBytes, kOTileBytes, bar + 8 * st);
          }
          __syncwarp(15u);
        }
        if (lane == 0) st_relaxed(&g_epoch[cta * 32 + wl], e0 + 1);
      }
    }
  }
}

}

namespace {

typedef CUresult (*EncodeTiledFn)(CUtensorMap*, CUtensorMapDataType, cuuint32_t, void*, const cuuint64_t*,
                                  const cuuint64_t*, const cuuint32_t*, const cuuint32_t*, CUtensorMapInterleave,
                                  CUtensorMapSwizzle, CUtensorMapL2promotion, CUtensorMapFloatOOBfill);

EncodeTiledFn get_encode_fn() {
  static EncodeTiledFn fn = nullptr;
  if (!fn) {
    void* p = nullptr;
    cudaDriverEntryPointQueryResult qres;
    if (cudaGetDriverEntryPoint("cuTensorMapEncodeTiled", &p, cudaEnableDefault, &qres) == cudaSuccess)
      fn = reinterpret_cast<EncodeTiledFn>(p);
  }
  return fn;
}

CUtensorMap make_map(void* base, int rank, const cuuint64_t* dims, const cuuint64_t* strides, const cuuint32_t* box,
                     CUtensorMapSwizzle swz) {
  CUtensorMap m;
  cuuint32_t es[5] = {1, 1, 1, 1, 1};
  get_encode_fn()(&m, CU_TENSOR_MAP_DATA_TYPE_BFLOAT16, (cuuint32_t)rank, base, dims, strides, box, es,
                  CU_TENSOR_MAP_INTERLEAVE_NONE, swz, CU_TENSOR_MAP_L2_PROMOTION_L2_128B,
                  CU_TENSOR_MAP_FLOAT_OOB_FILL_NONE);
  return m;
}

}

extern "C" void kernel_launch(void* const* d_in, const int* in_sizes, int n_in, void* d_out, int out_size) {
  using namespace nat;
  (void)in_sizes; (void)n_in; (void)out_size;
  const __nv_bfloat16* x = (const __nv_bfloat16*)d_in[0];
  const __nv_bfloat16* wqkv = (const __nv_bfloat16*)d_in[1];
  const __nv_bfloat16* wo = (const __nv_bfloat16*)d_in[2];
  const __nv_bfloat16* rpb = (const __nv_bfloat16*)d_in[3];
  __nv_bfloat16* out = (__nv_bfloat16*)d_out;

  CUtensorMap tm_x, tm_h, tm_w, tm_wo, tm_out;
  {
    cuuint64_t dims[5] = {64, 112, 112, 6, 2};
    cuuint64_t str[4] = {768, 2ull * 224 * 384, 128, 224ull * 384};
    cuuint32_t box[5] = {64, 16, 4, 3, 1};
    tm_x = make_map((void*)x, 5, dims, str, box, CU_TENSOR_MAP_SWIZZLE_128B);
    cuuint32_t boxh[5] = {64, 3, 9, 1, 1};
    tm_h = make_map((void*)x, 5, dims, str, boxh, CU_TENSOR_MAP_SWIZZLE_128B);
  }
  {
    cuuint64_t dims[2] = {576, 192};
    cuuint64_t str[1] = {1152};
    cuuint32_t box[2] = {16, 192};
    tm_w = make_map((void*)wqkv, 2, dims, str, box, CU_TENSOR_MAP_SWIZZLE_32B);
  }
  {
    cuuint64_t dims[2] = {192, 192};
    cuuint64_t str[1] = {384};
    cuuint32_t box[2] = {16, 192};
    tm_wo = make_map((void*)wo, 2, dims, str, box, CU_TENSOR_MAP_SWIZZLE_32B);
  }
  {
    cuuint64_t dims[5] = {192, 112, 112, 2, 2};
    cuuint64_t str[4] = {2ull * 224 * 384, 768, 384, 224ull * 384};
    cuuint32_t box[5] = {48, 4, 16, 1, 1};
    tm_out = make_map((void*)out, 5, dims, str, box, CU_TENSOR_MAP_SWIZZLE_NONE);
  }
  cudaFuncSetAttribute(nat_kernel, cudaFuncAttributeMaxDynamicSharedMemorySize, kSmemBytes);
  nat_kernel<<<kStripCtas + kProjCtas, kThreads, kSmemBytes>>>(wqkv, wo, rpb, out, tm_x, tm_w, tm_h, tm_wo, tm_out);
}
```

```cpp
#include <cuda_runtime.h>
#include <cuda_bf16.h>
#include <cuda.h>
#include <stdint.h>

#define DEVI __device__ __forceinline__

namespace nat {

DEVI uint32_t smem_u32(const void* p) { return (uint32_t)__cvta_generic_to_shared(p); }

DEVI void mbar_init(uint32_t bar, uint32_t count) {
  asm volatile("mbarrier.init.shared::cta.b64 [%0], %1;" ::"r"(bar), "r"(count) : "memory");
}
DEVI void mbar_expect_tx(uint32_t bar, uint32_t bytes) {
  asm volatile("mbarrier.arrive.expect_tx.shared::cta.b64 _, [%0], %1;" ::"r"(bar), "r"(bytes) : "memory");
}
DEVI void mbar_arrive(uint32_t bar) {
  asm volatile("mbarrier.arrive.shared::cta.b64 _, [%0];" ::"r"(bar) : "memory");
}
DEVI bool mbar_try_wait(uint32_t bar, uint32_t parity) {
  uint32_t ok;
  asm volatile(
      "{\n.reg .pred p;\nmbarrier.try_wait.parity.shared::cta.b64 p, [%1], %2;\nselp.u32 %0, 1, 0, p;\n}\n"
      : "=r"(ok)
      : "r"(bar), "r"(parity)
      : "memory");
  return ok != 0;
}
DEVI bool mbar_test_wait(uint32_t bar, uint32_t parity) {
  uint32_t ok;
  asm volatile(
      "{\n.reg .pred p;\nmbarrier.test_wait.parity.shared::cta.b64 p, [%1], %2;\nselp.u32 %0, 1, 0, p;\n}\n"
      : "=r"(ok)
      : "r"(bar), "r"(parity)
      : "memory");
  return ok != 0;
}
#define BAIL(code) __trap()
#define LIMIT (1u << 20)
DEVI void mbar_wait(uint32_t bar, uint32_t parity) {
  uint32_t it = 0;
  while (!mbar_try_wait(bar, parity)) {
    if (++it > LIMIT) { BAIL(bar & 0xfffff); break; }
  }
}
DEVI void fence_mbar_init() { asm volatile("fence.mbarrier_init.release.cluster;" ::: "memory"); }

DEVI void tma_load_2d(uint32_t dst, const CUtensorMap* tm, uint32_t bar, int c0, int c1) {
  asm volatile(
      "cp.async.bulk.tensor.2d.shared::cluster.global.mbarrier::complete_tx::bytes [%0], [%1, {%3, %4}], [%2];"
      ::"r"(dst), "l"(tm), "r"(bar), "r"(c0), "r"(c1)
      : "memory");
}
DEVI void tma_store_5d(const CUtensorMap* tm, uint32_t src, int c0, int c1, int c2, int c3, int c4) {
  asm volatile("cp.async.bulk.tensor.5d.global.shared::cta.bulk_group [%0, {%2, %3, %4, %5, %6}], [%1];"
               ::"l"(tm), "r"(src), "r"(c0), "r"(c1), "r"(c2), "r"(c3), "r"(c4)
               : "memory");
}
DEVI void bulk_wait_read1() { asm volatile("cp.async.bulk.wait_group.read 1;" ::: "memory"); }
DEVI void bulk_wait_read() { asm volatile("cp.async.bulk.wait_group.read 0;" ::: "memory"); }
DEVI void tma_load_4d(uint32_t dst, const CUtensorMap* tm, uint32_t bar, int c0, int c1, int c2, int c3) {
  asm volatile(
      "cp.async.bulk.tensor.4d.shared::cluster.global.mbarrier::complete_tx::bytes [%0], [%1, {%3, %4, %5, %6}], [%2];"
      ::"r"(dst), "l"(tm), "r"(bar), "r"(c0), "r"(c1), "r"(c2), "r"(c3)
      : "memory");
}
DEVI void tma_load_5d(uint32_t dst, const CUtensorMap* tm, uint32_t bar, int c0, int c1, int c2, int c3, int c4) {
  asm volatile(
      "cp.async.bulk.tensor.5d.shared::cluster.global.mbarrier::complete_tx::bytes [%0], [%1, {%3, %4, %5, %6, %7}], [%2];"
      ::"r"(dst), "l"(tm), "r"(bar), "r"(c0), "r"(c1), "r"(c2), "r"(c3), "r"(c4)
      : "memory");
}
DEVI void tma_load_5d_mc(uint32_t dst, const CUtensorMap* tm, uint32_t bar, int c0, int c1, int c2, int c3, int c4, uint16_t mask) {
  asm volatile(
      "cp.async.bulk.tensor.5d.shared::cluster.global.mbarrier::complete_tx::bytes.multicast::cluster [%0], [%1, {%3, %4, %5, %6, %7}], [%2], %8;"
      ::"r"(dst), "l"(tm), "r"(bar), "r"(c0), "r"(c1), "r"(c2), "r"(c3), "r"(c4), "h"(mask)
      : "memory");
}
DEVI uint32_t mapa(uint32_t addr, uint32_t rank) {
  uint32_t r;
  asm("mapa.shared::cluster.u32 %0, %1, %2;" : "=r"(r) : "r"(addr), "r"(rank));
  return r;
}
DEVI void mbar_arrive_cluster(uint32_t cluster_bar) {
  asm volatile("mbarrier.arrive.shared::cluster.b64 _, [%0];" ::"r"(cluster_bar) : "memory");
}
DEVI void cluster_arrive_relaxed() { asm volatile("barrier.cluster.arrive.relaxed.aligned;" ::: "memory"); }
DEVI void cluster_wait() { asm volatile("barrier.cluster.wait.aligned;" ::: "memory"); }
DEVI void tma_prefetch_5d(const CUtensorMap* tm, int c0, int c1, int c2, int c3, int c4) {
  asm volatile("cp.async.bulk.prefetch.tensor.5d.L2.global [%0, {%1, %2, %3, %4, %5}];"
               ::"l"(tm), "r"(c0), "r"(c1), "r"(c2), "r"(c3), "r"(c4)
               : "memory");
}
DEVI void bulk_load(uint32_t dst, const void* src, uint32_t bytes, uint32_t bar) {
  asm volatile("cp.async.bulk.shared::cluster.global.mbarrier::complete_tx::bytes [%0], [%1], %2, [%3];"
               ::"r"(dst), "l"(src), "r"(bytes), "r"(bar) : "memory");
}
DEVI void bulk_store(void* dst, uint32_t src, uint32_t bytes) {
  asm volatile("cp.async.bulk.global.shared::cta.bulk_group [%0], [%1], %2;" ::"l"(dst), "r"(src), "r"(bytes) : "memory");
}
DEVI void bulk_commit() { asm volatile("cp.async.bulk.commit_group;" ::: "memory"); }
template <int N>
DEVI void bulk_wait() { asm volatile("cp.async.bulk.wait_group %0;" ::"n"(N) : "memory"); }

template <int N>
DEVI void reg_dec() { asm volatile("setmaxnreg.dec.sync.aligned.u32 %0;" ::"n"(N)); }
template <int N>
DEVI void reg_inc() { asm volatile("setmaxnreg.inc.sync.aligned.u32 %0;" ::"n"(N)); }

DEVI void wg_fence() { asm volatile("wgmma.fence.sync.aligned;" ::: "memory"); }
DEVI void wg_commit() { asm volatile("wgmma.commit_group.sync.aligned;" ::: "memory"); }
template <int N>
DEVI void wg_wait() { asm volatile("wgmma.wait_group.sync.aligned %0;" ::"n"(N) : "memory"); }
template <int N>
DEVI void fence_regs(float (&d)[N]) {
#pragma unroll
  for (int i = 0; i < N; i++) asm volatile("" : "+f"(d[i])::"memory");
}

DEVI uint64_t make_desc(uint32_t addr, uint32_t lbo, uint32_t sbo, uint32_t swz) {
  return (uint64_t)((addr & 0x3FFFFu) >> 4) | ((uint64_t)((lbo & 0x3FFFFu) >> 4) << 16) |
         ((uint64_t)((sbo & 0x3FFFFu) >> 4) << 32) | ((uint64_t)swz << 62);
}

DEVI uint64_t desc64(uint32_t lo, uint32_t hi) {
  uint64_t d;
  asm("mov.b64 %0, {%1, %2};" : "=l"(d) : "r"(lo), "r"(hi));
  return d;
}
DEVI uint32_t pack_bf16(float lo, float hi) {
  uint32_t r;
  asm("cvt.rn.bf16x2.f32 %0, %1, %2;" : "=r"(r) : "f"(hi), "f"(lo));
  return r;
}
DEVI float ex2(float x) {
  float r;
  asm("ex2.approx.ftz.f32 %0, %1;" : "=f"(r) : "f"(x));
  return r;
}
DEVI float rcp_approx(float x) {
  float r;
  asm("rcp.approx.ftz.f32 %0, %1;" : "=f"(r) : "f"(x));
  return r;
}
DEVI uint32_t movmatrix_t(uint32_t a) {
  uint32_t r;
  asm("movmatrix.sync.aligned.m8n8.trans.b16 %0, %1;" : "=r"(r) : "r"(a));
  return r;
}
DEVI void ldmatrix_x4(uint32_t (&r)[4], uint32_t addr) {
  asm volatile("ldmatrix.sync.aligned.m8n8.x4.shared.b16 {%0, %1, %2, %3}, [%4];"
               : "=r"(r[0]), "=r"(r[1]), "=r"(r[2]), "=r"(r[3]) : "r"(addr) : "memory");
}
DEVI void ldmatrix_x4(uint32_t& r0, uint32_t& r1, uint32_t& r2, uint32_t& r3, uint32_t addr) {
  asm volatile("ldmatrix.sync.aligned.m8n8.x4.shared.b16 {%0, %1, %2, %3}, [%4];"
               : "=r"(r0), "=r"(r1), "=r"(r2), "=r"(r3) : "r"(addr) : "memory");
}
DEVI void ldmatrix_x2(uint32_t& r0, uint32_t& r1, uint32_t addr) {
  asm volatile("ldmatrix.sync.aligned.m8n8.x2.shared.b16 {%0, %1}, [%2];"
               : "=r"(r0), "=r"(r1) : "r"(addr) : "memory");
}
DEVI void ldmatrix_x4_t(uint32_t (&r)[4], uint32_t addr) {
  asm volatile("ldmatrix.sync.aligned.m8n8.x4.trans.shared.b16 {%0, %1, %2, %3}, [%4];"
               : "=r"(r[0]), "=r"(r[1]), "=r"(r[2]), "=r"(r[3]) : "r"(addr) : "memory");
}
DEVI void stmatrix_x4(uint32_t addr, uint32_t r0, uint32_t r1, uint32_t r2, uint32_t r3) {
  asm volatile("stmatrix.sync.aligned.m8n8.x4.shared.b16 [%0], {%1, %2, %3, %4};"
               ::"r"(addr), "r"(r0), "r"(r1), "r"(r2), "r"(r3) : "memory");
}
DEVI void stmatrix_x4_t(uint32_t addr, uint32_t r0, uint32_t r1, uint32_t r2, uint32_t r3) {
  asm volatile("stmatrix.sync.aligned.m8n8.x4.trans.shared.b16 [%0], {%1, %2, %3, %4};"
               ::"r"(addr), "r"(r0), "r"(r1), "r"(r2), "r"(r3) : "memory");
}
DEVI void mma16816(float (&d)[4], const uint32_t (&a)[4], uint32_t b0, uint32_t b1) {
  asm volatile("mma.sync.aligned.m16n8k16.row.col.f32.bf16.bf16.f32 {%0, %1, %2, %3}, {%4, %5, %6, %7}, {%8, %9}, {%0, %1, %2, %3};"
               : "+f"(d[0]), "+f"(d[1]), "+f"(d[2]), "+f"(d[3])
               : "r"(a[0]), "r"(a[1]), "r"(a[2]), "r"(a[3]), "r"(b0), "r"(b1));
}
DEVI void mma16816_z(float (&d)[4], const uint32_t (&a)[4], uint32_t b0, uint32_t b1) {
  asm volatile("mma.sync.aligned.m16n8k16.row.col.f32.bf16.bf16.f32 {%0, %1, %2, %3}, {%4, %5, %6, %7}, {%8, %9}, {%10, %10, %10, %10};"
               : "=f"(d[0]), "=f"(d[1]), "=f"(d[2]), "=f"(d[3])
               : "r"(a[0]), "r"(a[1]), "r"(a[2]), "r"(a[3]), "r"(b0), "r"(b1), "f"(0.f));
}
DEVI void mma16816_c(float (&d)[4], const uint32_t (&a)[4], uint32_t b0, uint32_t b1, const float (&c)[4]) {
  asm volatile("mma.sync.aligned.m16n8k16.row.col.f32.bf16.bf16.f32 {%0, %1, %2, %3}, {%4, %5, %6, %7}, {%8, %9}, {%10, %11, %12, %13};"
               : "=f"(d[0]), "=f"(d[1]), "=f"(d[2]), "=f"(d[3])
               : "r"(a[0]), "r"(a[1]), "r"(a[2]), "r"(a[3]), "r"(b0), "r"(b1), "f"(c[0]), "f"(c[1]), "f"(c[2]), "f"(c[3]));
}
template <int BIT>
DEVI void sel2(uint32_t mask, float& r0, float& r1, float a0, float a1, float b0, float b1) {
  asm("{\n.reg .pred p;\n.reg .b32 t;\nand.b32 t, %2, %7;\nsetp.ne.b32 p, t, 0;\nselp.f32 %0, %3, %5, p;\nselp.f32 %1, %4, %6, p;\n}"
      : "=f"(r0), "=f"(r1) : "r"(mask), "f"(a0), "f"(a1), "f"(b0), "f"(b1), "n"(BIT));
}
template <int BIT>
DEVI void split2(uint32_t mask, uint32_t& r0, uint32_t& r1, uint32_t v) {
  asm("{\n.reg .pred p;\n.reg .b32 t;\nand.b32 t, %2, %4;\nsetp.ne.b32 p, t, 0;\nselp.b32 %0, %3, 0, p;\nselp.b32 %1, 0, %3, p;\n}"
      : "=r"(r0), "=r"(r1) : "r"(mask), "r"(v), "n"(BIT));
}
DEVI void red_add1(uint32_t* p) {
  asm volatile("red.relaxed.gpu.global.add.u32 [%0], 1;" ::"l"(p) : "memory");
}
DEVI bool named_bar_or(int id, int n, bool v) {
  uint32_t r;
  asm volatile("{\n.reg .pred p, q;\nsetp.ne.u32 p, %1, 0;\nbar.red.or.pred q, %2, %3, p;\nselp.u32 %0, 1, 0, q;\n}"
               : "=r"(r) : "r"((uint32_t)v), "r"(id), "r"(n) : "memory");
  return r != 0;
}
DEVI void red_max(uint32_t* p, uint32_t v) {
  asm volatile("red.relaxed.gpu.global.max.u32 [%0], %1;" ::"l"(p), "r"(v) : "memory");
}
DEVI uint4 ldg128(const void* p) {
  uint4 v;
  asm volatile("ld.global.nc.v4.u32 {%0, %1, %2, %3}, [%4];" : "=r"(v.x), "=r"(v.y), "=r"(v.z), "=r"(v.w) : "l"(p));
  return v;
}
DEVI uint32_t ld_acquire(const uint32_t* p) {
  uint32_t v;
  asm volatile("ld.acquire.gpu.global.u32 %0, [%1];" : "=r"(v) : "l"(p) : "memory");
  return v;
}
DEVI uint32_t ld_relaxed(const uint32_t* p) {
  uint32_t v;
  asm volatile("ld.relaxed.gpu.global.u32 %0, [%1];" : "=r"(v) : "l"(p) : "memory");
  return v;
}
DEVI void st_relaxed(uint32_t* p, uint32_t v) {
  asm volatile("st.relaxed.gpu.global.u32 [%0], %1;" ::"l"(p), "r"(v) : "memory");
}
DEVI void st_release(uint32_t* p, uint32_t v) {
  asm volatile("st.release.gpu.global.u32 [%0], %1;" ::"l"(p), "r"(v) : "memory");
}
DEVI void fence_gpu() { asm volatile("fence.acq_rel.gpu;" ::: "memory"); }
DEVI uint32_t lds32(uint32_t addr) {
  uint32_t v;
  asm volatile("ld.shared.u32 %0, [%1];" : "=r"(v) : "r"(addr) : "memory");
  return v;
}
DEVI uint4 lds128(uint32_t addr) {
  uint4 v;
  asm volatile("ld.shared.v4.u32 {%0, %1, %2, %3}, [%4];" : "=r"(v.x), "=r"(v.y), "=r"(v.z), "=r"(v.w) : "r"(addr) : "memory");
  return v;
}
DEVI int lds32v(uint32_t addr) {
  int v;
  asm volatile("ld.volatile.shared.s32 %0, [%1];" : "=r"(v) : "r"(addr) : "memory");
  return v;
}
DEVI void sts32(uint32_t addr, uint32_t v) {
  asm volatile("st.shared.u32 [%0], %1;" ::"r"(addr), "r"(v) : "memory");
}
DEVI void sts128(uint32_t addr, uint4 v) {
  asm volatile("st.shared.v4.u32 [%0], {%1, %2, %3, %4};" ::"r"(addr), "r"(v.x), "r"(v.y), "r"(v.z), "r"(v.w) : "memory");
}
DEVI void named_bar_arrive(int id, int n) { asm volatile("bar.arrive %0, %1;" ::"r"(id), "r"(n) : "memory"); }
DEVI void named_bar_sync(int id, int n) { asm volatile("bar.sync %0, %1;" ::"r"(id), "r"(n) : "memory"); }
DEVI void fence_proxy_async() { asm volatile("fence.proxy.async.shared::cta;" ::: "memory"); }
DEVI void fence_proxy_async_global() { asm volatile("fence.proxy.async.global;" ::: "memory"); }
DEVI int clampi(int v, int lo, int hi) { return v < lo ? lo : (v > hi ? hi : v); }

template <int TA, int TB> DEVI void wgmma_m64n144k16_ss(float (&d)[72], uint64_t descA, uint64_t descB, int scaleD) {
  asm volatile("{\n.reg .pred p;\nsetp.ne.b32 p, %74, 0;\nwgmma.mma_async.sync.aligned.m64n144k16.f32.bf16.bf16 {%0, %1, %2, %3, %4, %5, %6, %7, %8, %9, %10, %11, %12, %13, %14, %15, %16, %17, %18, %19, %20, %21, %22, %23, %24, %25, %26, %27, %28, %29, %30, %31, %32, %33, %34, %35, %36, %37, %38, %39, %40, %41, %42, %43, %44, %45, %46, %47, %48, %49, %50, %51, %52, %53, %54, %55, %56, %57, %58, %59, %60, %61, %62, %63, %64, %65, %66, %67, %68, %69, %70, %71}, %72, %73, p, 1, 1, %75, %76;\n}\n"
    : "+f"(d[0]), "+f"(d[1]), "+f"(d[2]), "+f"(d[3]), "+f"(d[4]), "+f"(d[5]), "+f"(d[6]), "+f"(d[7]), "+f"(d[8]), "+f"(d[9]), "+f"(d[10]), "+f"(d[11]), "+f"(d[12]), "+f"(d[13]), "+f"(d[14]), "+f"(d[15]), "+f"(d[16]), "+f"(d[17]), "+f"(d[18]), "+f"(d[19]), "+f"(d[20]), "+f"(d[21]), "+f"(d[22]), "+f"(d[23]), "+f"(d[24]), "+f"(d[25]), "+f"(d[26]), "+f"(d[27]), "+f"(d[28]), "+f"(d[29]), "+f"(d[30]), "+f"(d[31]), "+f"(d[32]), "+f"(d[33]), "+f"(d[34]), "+f"(d[35]), "+f"(d[36]), "+f"(d[37]), "+f"(d[38]), "+f"(d[39]), "+f"(d[40]), "+f"(d[41]), "+f"(d[42]), "+f"(d[43]), "+f"(d[44]), "+f"(d[45]), "+f"(d[46]), "+f"(d[47]), "+f"(d[48]), "+f"(d[49]), "+f"(d[50]), "+f"(d[51]), "+f"(d[52]), "+f"(d[53]), "+f"(d[54]), "+f"(d[55]), "+f"(d[56]), "+f"(d[57]), "+f"(d[58]), "+f"(d[59]), "+f"(d[60]), "+f"(d[61]), "+f"(d[62]), "+f"(d[63]), "+f"(d[64]), "+f"(d[65]), "+f"(d[66]), "+f"(d[67]), "+f"(d[68]), "+f"(d[69]), "+f"(d[70]), "+f"(d[71])
    : "l"(descA), "l"(descB), "r"(scaleD), "n"(TA), "n"(TB));
}

template <int TB> DEVI void wgmma_m64n64k16_rs(float (&d)[32], uint32_t a0, uint32_t a1, uint32_t a2, uint32_t a3, uint64_t descB, int scaleD) {
  asm volatile("{\n.reg .pred p;\nsetp.ne.b32 p, %37, 0;\nwgmma.mma_async.sync.aligned.m64n64k16.f32.bf16.bf16 {%0, %1, %2, %3, %4, %5, %6, %7, %8, %9, %10, %11, %12, %13, %14, %15, %16, %17, %18, %19, %20, %21, %22, %23, %24, %25, %26, %27, %28, %29, %30, %31}, {%32, %33, %34, %35}, %36, p, 1, 1, %38;\n}\n"
    : "+f"(d[0]), "+f"(d[1]), "+f"(d[2]), "+f"(d[3]), "+f"(d[4]), "+f"(d[5]), "+f"(d[6]), "+f"(d[7]), "+f"(d[8]), "+f"(d[9]), "+f"(d[10]), "+f"(d[11]), "+f"(d[12]), "+f"(d[13]), "+f"(d[14]), "+f"(d[15]), "+f"(d[16]), "+f"(d[17]), "+f"(d[18]), "+f"(d[19]), "+f"(d[20]), "+f"(d[21]), "+f"(d[22]), "+f"(d[23]), "+f"(d[24]), "+f"(d[25]), "+f"(d[26]), "+f"(d[27]), "+f"(d[28]), "+f"(d[29]), "+f"(d[30]), "+f"(d[31])
    : "r"(a0), "r"(a1), "r"(a2), "r"(a3), "l"(descB), "r"(scaleD), "n"(TB));
}

template <int TA, int TB> DEVI void wgmma_m64n48k16_ss(float (&d)[24], uint64_t descA, uint64_t descB, int scaleD) {
  asm volatile("{\n.reg .pred p;\nsetp.ne.b32 p, %26, 0;\nwgmma.mma_async.sync.aligned.m64n48k16.f32.bf16.bf16 {%0, %1, %2, %3, %4, %5, %6, %7, %8, %9, %10, %11, %12, %13, %14, %15, %16, %17, %18, %19, %20, %21, %22, %23}, %24, %25, p, 1, 1, %27, %28;\n}\n"
    : "+f"(d[0]), "+f"(d[1]), "+f"(d[2]), "+f"(d[3]), "+f"(d[4]), "+f"(d[5]), "+f"(d[6]), "+f"(d[7]), "+f"(d[8]), "+f"(d[9]), "+f"(d[10]), "+f"(d[11]), "+f"(d[12]), "+f"(d[13]), "+f"(d[14]), "+f"(d[15]), "+f"(d[16]), "+f"(d[17]), "+f"(d[18]), "+f"(d[19]), "+f"(d[20]), "+f"(d[21]), "+f"(d[22]), "+f"(d[23])
    : "l"(descA), "l"(descB), "r"(scaleD), "n"(TA), "n"(TB));
}

#define DEV_NB 7
#define DEV_D 6
#define DEV_WTMA 2
#define DEV_WOD 2000
#define DEV_PB 7
#define DEV_SEND 0
#define DEV_NV 2
#define DEV_BE 0
#define DEV_ONORM 0
#define DEV_GF 1
#define X_NOV 0
#define X_NOK 0
#define X_NOSH 0
#define X_NOMV 0
#define X_NOST 0
#define X_NOH 0
#define X_NOSTSM 0
#define DEV_ORD 0
#define DEV_HSUM 1
#define DEV_DEPH 24
#define DEV_PS 200
#define PWAIT mbar_wait_sleep
#define DEV_TURN 0
#define DEV_WG 1
#define DEV_GATE 0
#define DEV_NS 200

constexpr int kS = 112;
constexpr int kStripCtas = 112;
constexpr int kProjCtas = 20;
constexpr int kThreads = 512;
constexpr int kArr = 29;
constexpr int kExch = 27;
constexpr int kSteps = 28;
constexpr int kTiles = kSteps * 28;
constexpr int kOTileBytes = 64 * 192 * 2;
constexpr int kTailBands = DEV_NB;
constexpr int kProjTiles = (kSteps - kTailBands) * 28;
constexpr int kHaloBytes = 3 * 784 - 16, kHaloPitch = 2432;

__device__ __align__(1024) uint8_t g_o[(size_t)kTiles * kOTileBytes];
__device__ __align__(1024) uint8_t g_halo[(size_t)kStripCtas * 2 * kExch * kHaloPitch];
__device__ __align__(1024) uint8_t g_wop[4 * 3 * 192 * 32];
__device__ uint32_t g_hflag[kStripCtas * 32];
__device__ uint32_t g_oflag[28 * 32];
__device__ uint32_t g_wflag[4 * 32];
__device__ uint32_t g_epoch[132 * 32];

namespace ka {
constexpr int kWAtom = 192 * 32;
constexpr int kWBytes = 9 * kWAtom;
constexpr int kXBytes = 64 * 384;
constexpr int kCol = 784;
constexpr int kQCol = 400;
constexpr int kSlot = 22 * kCol;
constexpr int kQSlot = 16 * kQCol;
constexpr int kQOff = 5 * kSlot + 32;
constexpr int kOffX = kWBytes;
constexpr int kOffRing = kOffX + 2 * kXBytes;
constexpr int kOffBar = kOffRing + kQOff + 6 * kQSlot;
constexpr int kOffWo = kOffX + kXBytes;
constexpr int kOffStage = kOffWo + 3 * kWAtom, kOffStage2 = 2 * kOTileBytes;
DEVI uint32_t tail_buf(int i) { return i == 2 ? kOffX : i * kOTileBytes; }
constexpr int kLastBytes = 3 * (16 + 2 * 15) * 128;
constexpr int kBarX = 0, kBarFull = 256, kBarO = 512, kBarT = 768, kBarTe = 832, kBarJunk = 896;
constexpr int kSmemBytes = kOffBar + 912;
constexpr int kD = DEV_D;
static_assert(kD == 5 || kD == 6, "ring");
static_assert(kTailBands <= 8, "barriers");
constexpr int kNbInit = 0, kNbMisc = 1, kNbBurst = 2, kNbTile = 7, kNbFirst = 13, kNbX = 14;
}

namespace kb {
constexpr int kWoBlk = 192 * 128;
constexpr int kStages = 6;
constexpr int kOffA = 3 * kWoBlk;
constexpr int kOffBar = kOffA + kStages * kOTileBytes;
constexpr int kSmemBytes = kOffBar + 128;
}

constexpr int kSmemBytes = ka::kSmemBytes > kb::kSmemBytes ? ka::kSmemBytes : kb::kSmemBytes;
static_assert(kSmemBytes <= 232448, "smem");

#define TRACE(idx)
#define GT(i)
#define ATRACE(k)
#define TRBASE (sbase + kTraceOff)

DEVI void mbar_wait_sleep(uint32_t bar, uint32_t parity) {
  uint32_t it = 0;
  while (!mbar_test_wait(bar, parity)) {
    __nanosleep(DEV_NS);
    if (++it > LIMIT) { BAIL(bar & 0xfffff); break; }
  }
}

DEVI void publish_fence() {
  fence_proxy_async_global();
  fence_gpu();
}

DEVI uint32_t sched_fence() {
  uint32_t t;
  asm volatile("mov.u32 %0, %clock;" : "=r"(t)::"memory");
  return t;
}

struct AttnState {
  uint32_t kf[5][3][4];
  uint32_t vf[5][3][4];
  float bias[5][4];
  uint32_t p[5][2];
  uint32_t kaddr, vaddr, qaddr, bar, junk, fence;
  float sum0, sum1;
  uint32_t pm;
  uint32_t* optr;
};

DEVI void store_o(AttnState& s, float (&o)[3][4], float i0, float i1, int g) {
  if (g >= 0) {
#pragma unroll
    for (int mt = 0; mt < 3; mt++) {
      if (!X_NOST || o[mt][0] == 123.f) s.optr[(2 * mt) * 32] = pack_bf16(o[mt][0] * i0, o[mt][1] * i1);
      if (!X_NOST || o[mt][0] == 123.f) s.optr[(2 * mt + 1) * 32] = pack_bf16(o[mt][2] * i0, o[mt][3] * i1);
    }
  }
  __syncwarp();
  if ((s.pm & 64) && g >= (DEV_NV ? -1 : 0)) mbar_arrive(s.bar + ka::kBarO + 8 * g);
  s.optr += 28 * kOTileBytes / 4;
}

template <int PH>
DEVI void attn_step(AttnState& s, int g, int warp, const __nv_bfloat16* __restrict__ rpb) {
  using namespace ka;
  constexpr int R = (2 * PH) % 5, N0 = (R + 3) % 5, N1 = (R + 4) % 5;
  constexpr int SL = ((PH + 1) % 5) * kSlot;
  if (PH == 0 && g == 0) {
    {
      const int lane = threadIdx.x & 31, qc0 = 16 * ((blockIdx.x >> 2) % 7) + 2 * warp;
      const int kc = clampi(qc0 - 3, 0, kS - 8) + (lane >> 2);
      const unsigned short* r = reinterpret_cast<const unsigned short*>(rpb) + (blockIdx.x & 3) * 169 + (3 - (lane & 3)) * 13 + kc - qc0 + 6;
      const int sw0 = clampi(qc0 - 3, 0, kS - 7), sw1 = clampi(qc0 - 2, 0, kS - 7);
      const bool ok0 = kc >= sw0 && kc < sw0 + 7, ok1 = kc >= sw1 && kc < sw1 + 7;
#pragma unroll
      for (int i = 0; i < 10; i++) {
        const uint32_t v0 = ok0 ? (uint32_t)__ldg(r + i * 13) : 0xFF80u;
        const uint32_t v1 = ok1 ? (uint32_t)__ldg(r + i * 13 - 1) : 0xFF80u;
        s.bias[i >> 1][2 * (i & 1)] = __uint_as_float(v0 << 16) * 6.928203230275509f;
        s.bias[i >> 1][2 * (i & 1) + 1] = __uint_as_float(v1 << 16) * 6.928203230275509f;
      }
    }
    named_bar_sync(kNbMisc, 384);
    mbar_wait(s.bar + kBarFull, 0);
#pragma unroll
    for (int k = 0; k < 3; k++) {
      ldmatrix_x4(s.kf[1][k], s.kaddr + k * 32);
      ldmatrix_x4(s.kf[2][k], s.kaddr + 384 + k * 32);
      ldmatrix_x4_t(s.vf[1][k], s.vaddr + k * 32);
      ldmatrix_x4_t(s.vf[2][k], s.vaddr + 384 + k * 32);
      s.vf[0][k][0] = s.vf[0][k][1] = s.vf[0][k][2] = s.vf[0][k][3] = 0u;
    }
    named_bar_arrive(kNbFirst, 384);
  }
  if (PH < 3 || g >= 0) mbar_wait(s.bar + kBarFull + 8 * (g + 1), 0);
  if (DEV_DEPH && PH == DEV_DEPH % 5 && g == DEV_DEPH && warp >= 4) named_bar_sync(kNbInit, 256);
  ATRACE(0);
  float t[5][4], o[3][4], z[4];
  uint32_t q[6];
  const uint32_t ones[4] = {0x3F803F80u, s.kaddr, 0x3F803F80u, s.vaddr};
#define LDV(n) if (!X_NOV) ldmatrix_x4_t(s.vf[(n) < 3 ? N0 : N1][(n) % 3], s.vaddr + SL + ((n) / 3) * 384 + ((n) % 3) * 32);
#define LDK(n) if (!X_NOK) ldmatrix_x4(s.kf[(n) & 1 ? N1 : N0][(n) >> 1], s.kaddr + SL + ((n) & 1) * 384 + ((n) >> 1) * 32);
#define PV(i) { _Pragma("unroll") for (int mt = 0; mt < 3; mt++) { \
                  if ((i) == 0) mma16816_z(o[mt], s.vf[N0][mt], s.p[0][0], s.p[0][1]); \
                  else mma16816(o[mt], s.vf[(R + 3 + (i)) % 5][mt], s.p[i][0], s.p[i][1]); } \
                if (DEV_HSUM) { if ((i) == 0) mma16816_z(z, ones, s.p[0][0], s.p[0][1]); else mma16816(z, ones, s.p[i][0], s.p[i][1]); } }
#define QK(i, ks) { if ((ks) == 0) mma16816_c(t[i], s.kf[(R + (i)) % 5][0], q[0], q[1], s.bias[i]); \
                    else mma16816(t[i], s.kf[(R + (i)) % 5][ks], q[2 * (ks)], q[2 * (ks) + 1]); }
#define REL named_bar_arrive(kNbBurst + (PH + kD) % 5, 384);
  ldmatrix_x4(q[0], q[1], q[2], q[3], s.qaddr);
  ldmatrix_x2(q[4], q[5], s.qaddr + 64);
  uint32_t f0 = 0, f1, f2, f3 = 0;
  LDK(0) LDK(1) LDK(2) LDK(3) LDK(4) LDK(5)
  PV(0) PV(1) PV(2) PV(3) PV(4)
  f1 = sched_fence();
  s.junk ^= s.fence;
#pragma unroll
  for (int n = 5; n >= DEV_NV; n--) LDV(n)
#pragma unroll
  for (int n = 0; n < 15 - DEV_BE; n++) QK(n % 5, n / 5)
  f2 = sched_fence();
  REL
#pragma unroll
  for (int n = 15 - DEV_BE; n < 15; n++) QK(n % 5, n / 5)
  s.fence = sched_fence();
  if (DEV_DEPH && PH == DEV_DEPH % 5 && g == DEV_DEPH && warp < 4) named_bar_arrive(kNbInit, 256);
  ATRACE(1);
  uint32_t pm = s.pm;
  if (PH == 0 && g == 0) pm &= ~0x3Fu;
  if (PH == 2 && g == kSteps - 1) pm |= 0x3Fu;
  float x[7][2];
  sel2<1>(pm, x[0][0], x[0][1], t[0][0], t[0][1], t[3][2], t[3][3]);
  sel2<2>(pm, x[1][0], x[1][1], t[0][2], t[0][3], t[4][0], t[4][1]);
  sel2<4>(pm, x[2][0], x[2][1], t[1][0], t[1][1], t[4][2], t[4][3]);
#pragma unroll
  for (int e = 0; e < 2; e++) {
    x[3][e] = t[1][2 + e]; x[4][e] = t[2][e]; x[5][e] = t[2][2 + e]; x[6][e] = t[3][e];
  }
  float m0 = fmaxf(fmaxf(fmaxf(x[0][0], x[1][0]), fmaxf(x[2][0], x[3][0])), fmaxf(fmaxf(x[4][0], x[5][0]), x[6][0]));
  float m1 = fmaxf(fmaxf(fmaxf(x[0][1], x[1][1]), fmaxf(x[2][1], x[3][1])), fmaxf(fmaxf(x[4][1], x[5][1]), x[6][1]));
#pragma unroll
  for (int d = 4; d <= (X_NOSH ? 0 : 16); d <<= 1) {
    m0 = fmaxf(m0, __shfl_xor_sync(0xffffffffu, m0, d));
    m1 = fmaxf(m1, __shfl_xor_sync(0xffffffffu, m1, d));
    if (!DEV_HSUM) {
      s.sum0 += __shfl_xor_sync(0xffffffffu, s.sum0, d);
      s.sum1 += __shfl_xor_sync(0xffffffffu, s.sum1, d);
    }
  }
  if (!DEV_HSUM) { z[0] = s.sum0; z[1] = s.sum1; }
  uint32_t f4 = 0;
  if (DEV_NV > 0) {
    f4 = sched_fence();
#pragma unroll
    for (int n = 0; n < DEV_NV; n++) LDV(n)
  }
  const float c = 0.14433756729740643f * 1.4426950408889634f;
  const float n0 = -m0 * c, n1 = -m1 * c;
  uint32_t pt[7];
#pragma unroll
  for (int i = 0; i < 7; i++) {
    const float e0 = ex2(fmaf(x[i][0], c, n0)), e1 = ex2(fmaf(x[i][1], c, n1));
    if (!DEV_HSUM) {
      s.sum0 = i ? s.sum0 + e0 : e0;
      s.sum1 = i ? s.sum1 + e1 : e1;
    }
    pt[i] = X_NOMV ? pack_bf16(e0, e1) : movmatrix_t(pack_bf16(e0, e1));
  }
  split2<8>(pm, s.p[0][0], s.p[3][1], pt[0]);
  split2<16>(pm, s.p[0][1], s.p[4][0], pt[1]);
  split2<32>(pm, s.p[1][0], s.p[4][1], pt[2]);
  s.p[1][1] = pt[3]; s.p[2][0] = pt[4]; s.p[2][1] = pt[5]; s.p[3][0] = pt[6];
#pragma unroll
  for (int i = 0; i < 5; i++) asm volatile("" : "+r"(s.p[i][0]), "+r"(s.p[i][1])::"memory");
  if (!DEV_HSUM) asm volatile("" : "+f"(s.sum0), "+f"(s.sum1)::"memory");
  store_o(s, o, rcp_approx(z[0]), rcp_approx(z[1]), g - 1);
  s.junk ^= f0 ^ f1 ^ f2 ^ f3;
  s.fence ^= f4;
  s.qaddr += kQSlot;
  if (s.qaddr >= s.bar) s.qaddr -= 6 * kQSlot;
  asm volatile("" : "+r"(s.junk)::"memory");
  ATRACE(2);
}

__global__ void __launch_bounds__(kThreads, 1)
nat_kernel(const __nv_bfloat16* __restrict__ wqkv, const __nv_bfloat16* __restrict__ rpb,
           const __grid_constant__ CUtensorMap tm_x, const __grid_constant__ CUtensorMap tm_w,
           const __grid_constant__ CUtensorMap tm_h, const __grid_constant__ CUtensorMap tm_r,
           const __grid_constant__ CUtensorMap tm_wo, const __grid_constant__ CUtensorMap tm_out,
           const __grid_constant__ CUtensorMap tm_wo2, const __grid_constant__ CUtensorMap tm_o2) {
  extern __shared__ __align__(1024) uint8_t smem_raw[];
  const uint32_t sbase = smem_u32(smem_raw);
  if (sbase & 1023u) __trap();
  const int warp = __shfl_sync(0xffffffffu, (int)(threadIdx.x >> 5), 0), lane = threadIdx.x & 31;
  const int wg = warp >> 2, wl = warp & 3;
  const int cta = blockIdx.x;
  const bool strip_cta = cta < kStripCtas;
  const int head = cta & 3, ps = cta >> 2, par = ps / 7, strip = ps - 7 * par;
  if (threadIdx.x == 0) TRACE(0);

  if (strip_cta && threadIdx.x == 384) {
    using namespace ka;
    const uint32_t bar = sbase + kOffBar;
    mbar_init(bar + kBarX, 1);
    mbar_expect_tx(bar + kBarX, kXBytes + DEV_WTMA * 3 * kWAtom);
    tma_load_5d(sbase + kOffX, &tm_x, bar + kBarX, 0, 16 * strip, -1, 3 * (par & 1), par >> 1);
#pragma unroll
    for (int i = 9 - 3 * DEV_WTMA; i < 9; i++)
      tma_load_2d(sbase + i * kWAtom, &tm_w, bar + kBarX, (i / 3) * 192 + head * 48 + (i % 3) * 16, 0);
    TRACE(10);
  }
  __syncwarp();
  if (DEV_WTMA < 3 && strip_cta && wg == 2 && threadIdx.x < 256 + 96) {
    using namespace ka;
    constexpr int kSec = DEV_WTMA < 3 ? 3 - DEV_WTMA : 1;
    uint4 v[12 * kSec];
    const int wk = ((int)threadIdx.x - 256) / 6, wu = (int)threadIdx.x - 256 - 6 * wk;
    const uint8_t* src = reinterpret_cast<const uint8_t*>(wqkv) + wk * 1152 + head * 96 + wu * 16;
#pragma unroll
    for (int i = 0; i < 12 * kSec; i++) v[i] = ldg128(src + (i / kSec) * 16 * 1152 + (i % kSec) * 384);
    const uint32_t dst = sbase + (wu >> 1) * kWAtom + wk * 32 + (((wu ^ (wk >> 2)) & 1) << 4);
#pragma unroll
    for (int i = 0; i < 12 * kSec; i++) sts128(dst + (i / kSec) * 16 * 32 + (i % kSec) * 3 * kWAtom, v[i]);
    if (warp == 8) TRACE(6);
    fence_proxy_async();
  }
  if (threadIdx.x == 480) GT(0);

  if (strip_cta) {
    using namespace ka;
    const uint32_t bar = sbase + kOffBar, ring = sbase + kOffRing;
    if (wg < 2) {
      if (DEV_WG == 0) named_bar_arrive(kNbX, 416);
      reg_inc<184>();
      AttnState s;
      const int qc0 = 16 * strip + 2 * warp;
      const int kc0 = clampi(qc0 - 3, 0, kS - 8);
      const uint32_t colb = ring + (kc0 - (16 * strip - 3) + (lane & 7)) * kCol;
      s.kaddr = colb + ((lane >> 3) & 1) * 192 + (lane >> 4) * 16;
      s.vaddr = colb + 96 + (lane >> 4) * 192 + ((lane >> 3) & 1) * 16;
      {
        const int qr = (lane & 7) >> 1;
        const uint32_t qa = ring + kQOff + (2 * warp + (lane & 1)) * kQCol + (lane >> 3) * 16;
        s.qaddr = qa + (qr == 3 ? 5 * kQSlot : 4 * kQSlot + (qr + 1) * 96);
      }
      s.bar = bar;
      s.optr = reinterpret_cast<uint32_t*>(g_o + (size_t)(ps * 4 + head) * 6144 + warp * 768) + lane - 3 * 28 * kOTileBytes / 4;
#pragma unroll
      for (int i = 0; i < 5; i++) {
        s.p[i][0] = s.p[i][1] = 0u;
        s.bias[i][0] = s.bias[i][1] = s.bias[i][2] = s.bias[i][3] = 0.f;
#pragma unroll
        for (int k = 0; k < 3; k++)
#pragma unroll
          for (int c = 0; c < 4; c++) s.kf[i][k][c] = s.vf[i][k][c] = 0u;
      }
      s.junk = s.fence = 0;
      s.sum0 = s.sum1 = 1.f;
      s.pm = (7u << (lane & 3) & 7u) | ((7u << (lane >> 3) & 7u) << 3) | (lane == 0 ? 64u : 0u);
      s.pm = __shfl_sync(0xffffffffu, s.pm, lane);
#pragma unroll 1
      for (int g = -2; g < kSteps; g += 5) {
        attn_step<3>(s, g, warp, rpb);
        attn_step<4>(s, g + 1, warp, rpb);
        attn_step<0>(s, g + 2, warp, rpb);
        attn_step<1>(s, g + 3, warp, rpb);
        attn_step<2>(s, g + 4, warp, rpb);
      }
      {
        float o[3][4], z[4];
        const uint32_t ones[4] = {0x3F803F80u, s.kaddr, 0x3F803F80u, s.vaddr};
#pragma unroll
        for (int mt = 0; mt < 3; mt++) mma16816_z(o[mt], s.vf[4][mt], s.p[0][0], s.p[0][1]);
        mma16816_z(z, ones, s.p[0][0], s.p[0][1]);
#pragma unroll
        for (int i = 1; i < 5; i++) {
#pragma unroll
          for (int mt = 0; mt < 3; mt++) mma16816(o[mt], s.vf[i - 1][mt], s.p[i][0], s.p[i][1]);
          mma16816(z, ones, s.p[i][0], s.p[i][1]);
        }
        store_o(s, o, rcp_approx(z[0]), rcp_approx(z[1]), kSteps - 1);
      }
      s.junk ^= s.fence;
      if (s.junk == 0x9e3779b9u) sts32(bar + kBarJunk, 0);
      if (warp == 0) TRACE(1);
      if (threadIdx.x == 128) GT(3);
    } else if (wg == 2) {
      reg_dec<104>();
      const int col = ((lane >> 3) & 1) * 8 + (lane & 7);
      uint32_t kva = ring + (3 + col) * kCol + wl * 192 + (lane >> 4) * 16;
      uint32_t qa = ring + kQOff + col * kQCol + wl * 96 + (lane >> 4) * 16;
      const uint32_t alo = (uint32_t)make_desc(sbase + kOffX, 16, 1024, 1), blo = (uint32_t)make_desc(sbase, kWAtom, 256, 3);
      constexpr uint32_t ahi = (1u << 30) | (1024 >> 4), bhi = (3u << 30) | (256 >> 4);
      if (wl == 0) TRACE(2);
      uint32_t gj = 0;
      int bid = kNbBurst, tid = kNbTile;
      named_bar_arrive(kNbBurst + (kD - 2) % 5, 384);
      named_bar_arrive(kNbBurst + (kD - 1) % 5, 384);
      named_bar_sync(kNbX, DEV_WG ? 160 : 416);
      if (wl == 0) TRACE(7);
      mbar_wait(bar + kBarX, 0);
      if (wl == 0) TRACE(16 + 0);
#pragma unroll 1
      for (int a = 0; a < kArr; a++) {
        float acc[72];
        const uint32_t al = alo + (a & 1) * (kXBytes >> 4);
        if (a >= kD) named_bar_sync(bid, 384);
        if (wl == 0) TRACE(16 + a * 4 + 1);
        wg_fence();
#pragma unroll
        for (int k = 0; k < 12; k++)
          wgmma_m64n144k16_ss<0, 1>(acc, desc64(al + (((k >> 2) * 8192 + (k & 3) * 32) >> 4), ahi), desc64(blo + k * 32, bhi), k != 0);
        wg_commit();
        if (DEV_GF) gj ^= sched_fence();
        bid = bid == kNbBurst + 4 ? kNbBurst : bid + 1;
        if (a == 0) named_bar_sync(kNbInit, 256);
        const bool xok = mbar_test_wait(bar + kBarX + 8 * (a + 1), 0);
        if (a == kArr - 1 && wl != 0) {
          const int r = col / 3, c = col - 3 * r;
          qa = sbase + kOffStage + lane * 16;
          kva = col < 15 && wl < 3 ? ring + ((kExch + (r >> 2)) % 5) * kSlot + ((wl - 1) * 19 + c) * kCol + (r & 3) * 192 + (lane >> 4) * 16
                                   : qa;
        }
        wg_wait<0>();
        fence_regs(acc);
        named_bar_arrive(kNbX + (a & 1), 160);
        if (kD == 6 && a == 5) named_bar_sync(kNbFirst, 384);
        if (DEV_NV && a >= 6) mbar_wait(bar + kBarO + 8 * (a - 7), 0);
        if (wl == 0) TRACE(16 + a * 4 + 2);
#pragma unroll
        for (int jp = 0; jp < 9; jp++) {
          const int j = jp < 6 ? jp + 3 : jp - 6;
          if (!X_NOSTSM || acc[8 * j] == 123.f) stmatrix_x4(j < 3 ? qa + j * 32 : kva + (j - 3) * 32, pack_bf16(acc[8 * j + 0], acc[8 * j + 1]),
                      pack_bf16(acc[8 * j + 2], acc[8 * j + 3]), pack_bf16(acc[8 * j + 4], acc[8 * j + 5]),
                      pack_bf16(acc[8 * j + 6], acc[8 * j + 7]));
        }
        if (a < kExch) named_bar_arrive(tid, 160);
        tid = tid == kNbTile + 5 ? kNbTile : tid + 1;
        if (wl == 0) TRACE(16 + a * 4 + 3);
        if (!xok && a + 1 < kArr) mbar_wait(bar + kBarX + 8 * (a + 1), 0);
        if (wl == 0) TRACE(16 + (a + 1) * 4 + 0);
        kva += kSlot;
        if (kva >= ring + 5 * kSlot) kva -= 5 * kSlot;
        qa += kQSlot;
        if (qa >= bar) qa -= 6 * kQSlot;
      }
      __syncwarp();
      if (lane < kArr - kExch) mbar_arrive(bar + kBarFull + 8 * (kExch + lane));
      if (gj == 0x9e3779b9u) sts32(bar + kBarJunk, 0);
      if (kD == 5) named_bar_arrive(kNbFirst, 384);
#pragma unroll 1
      for (int g = kArr - kD; g < kSteps - DEV_GATE; g++) {
        named_bar_arrive(bid, 384);
        bid = bid == kNbBurst + 4 ? kNbBurst : bid + 1;
      }
      {
        const uint32_t wlo = (uint32_t)make_desc(sbase + kOffWo, kWAtom, 256, 3);
        const int n = lane & 7, j = 2 * wl + ((lane >> 3) & 1);
        const uint32_t sta = sbase + ((2 * j + (n & 1)) * 4 + (n >> 1)) * 96 + (lane >> 4) * 16;
        mbar_wait(bar + kBarX + 8 * kArr, 0);
        named_bar_sync(kNbMisc, 128);
        int buf = 0;
#pragma unroll 1
        for (int i = 0; i < kTailBands; i++) {
          float acc[24];
          mbar_wait(bar + kBarT + 8 * i, 0);
          if (i < DEV_GATE) {
            named_bar_sync(bid, 384);
            bid = bid == kNbBurst + 4 ? kNbBurst : bid + 1;
          }
          if (wl == 0) TRACE(144 + i * 2);
          const uint32_t tlo = (uint32_t)make_desc(sbase + tail_buf(buf), 128, 768, 0);
          wg_fence();
#pragma unroll
          for (int k = 0; k < 12; k++)
            wgmma_m64n48k16_ss<1, 1>(acc, desc64(tlo + (((k / 3) * 6144 + (k % 3) * 256) >> 4), 768 >> 4), desc64(wlo + k * 32, bhi), k != 0);
          wg_commit();
          const uint32_t stg = (i & 1) ? kOffStage : kOffStage2;
          wg_wait<0>();
          fence_regs(acc);
          if (lane == 0) mbar_arrive(bar + kBarTe + 8 * i);
#pragma unroll
          for (int jp = 0; jp < 3; jp++)
            stmatrix_x4(sta + stg + jp * 32, pack_bf16(acc[8 * jp + 0], acc[8 * jp + 1]), pack_bf16(acc[8 * jp + 2], acc[8 * jp + 3]),
                        pack_bf16(acc[8 * jp + 4], acc[8 * jp + 5]), pack_bf16(acc[8 * jp + 6], acc[8 * jp + 7]));
          fence_proxy_async();
          if (threadIdx.x == 256) bulk_wait_read();
          named_bar_sync(kNbMisc, 128);
          if (threadIdx.x == 256) {
            tma_store_5d(&tm_out, sbase + stg, head * 48, 4 * (kSteps - kTailBands + i), 16 * strip, par & 1, par >> 1);
            bulk_commit();
          }
          if (wl == 0) TRACE(145 + i * 2);
          buf = buf == 2 ? 0 : buf + 1;
        }
        if (threadIdx.x == 256) {
          bulk_wait<0>();
          GT(2);
        }
      }
    } else {
      reg_dec<40>();
      if (wl == 0) named_bar_arrive(kNbX, DEV_WG ? 160 : 416);
      if (lane == 0) {
        const uint32_t b0 = bar + 64 * wl;
        if (wl == 1 && head == 1) tma_prefetch_5d(&tm_x, 0, 16 * strip, 3, 3 * (par & 1), par >> 1);
#pragma unroll
        for (int i = 0; i < 64; i += 8) {
          if (i || wl) mbar_init(b0 + kBarX + i, 1);
          mbar_init(b0 + kBarFull + i, wl < 3 || i < 8 * (kExch - 24) ? 2 : (i == 56 ? 8 : 4));
          mbar_init(b0 + kBarO + i, 8);
          if (wl < 2) mbar_init(b0 + kBarT + i, wl == 0 ? 1 : 4);
        }
#pragma unroll
        for (int i = 0; i < 64; i += 8) {
          if (i || wl)
            mbar_expect_tx(b0 + kBarX + i, wl < 3 || i < 32 ? kXBytes : (i == 32 ? kLastBytes : 3 * kWAtom));
          if (wl == 0) mbar_expect_tx(bar + kBarT + i, kOTileBytes);
        }
        fence_mbar_init();
        if (wl == 0) {
          tma_load_5d(sbase + kOffX + kXBytes, &tm_x, bar + kBarX + 8, 0, 16 * strip, 3, 3 * (par & 1), par >> 1);
          tma_prefetch_5d(&tm_x, 0, 16 * strip, 4 * (2 + ((head - 2) & 3)) - 1, 3 * (par & 1), par >> 1);
          TRACE(5);
        }
      }
      __syncwarp();
      const uint32_t ep = ld_relaxed(&g_epoch[cta * 32 + wl]) * 32u;
      named_bar_arrive(kNbMisc, 384);
      named_bar_sync(kNbInit, 256);
      if (wl == 0) {
#pragma unroll 1
        for (int a = 2; a < kArr - 1; a++) {
          named_bar_sync(kNbX + (a & 1), 160);
          if (lane == 0) {
            tma_load_5d(sbase + kOffX + (a & 1) * kXBytes, &tm_x, bar + kBarX + 8 * a, 0, 16 * strip, 4 * a - 1,
                        3 * (par & 1), par >> 1);
            const int ap = a + 4;
            if (ap < kArr && (ap & 3) == head) tma_prefetch_5d(&tm_x, 0, 16 * strip, 4 * ap - 1, 3 * (par & 1), par >> 1);
          }
          __syncwarp();
        }
        named_bar_sync(kNbX, 160);
        if (lane < 9) {
          const int kb = lane / 3, w = lane - 3 * kb;
          tma_load_5d(sbase + kOffX + kb * 8192 + w * 2048, w == 0 ? &tm_r : &tm_h, bar + kBarX + 8 * (kArr - 1), 0,
                      16 * strip + (w == 0 ? 0 : (w == 1 ? -3 : 16)), w == 0 ? kS - 1 : 4 * kExch - 1, 3 * (par & 1) + kb, par >> 1);
        }
        if (lane == 0) {
          uint32_t it = 0;
          while ((int)(ld_acquire(&g_wflag[head * 32]) - (ep + 1)) < 0)
            if (++it > LIMIT) { BAIL(0x5000000); break; }
        }
        __syncwarp();
        named_bar_sync(kNbX + 1, 160);
        if (lane == 0) bulk_load(sbase + kOffWo, g_wop + head * 3 * kWAtom, 3 * kWAtom, bar + kBarX + 8 * kArr);
        uint32_t seen = ld_acquire(&g_oflag[ps * 32 + (lane & 3)]);
        named_bar_sync(kNbX, 160);
        int buf = 0;
#pragma unroll 1
        for (int i = 0; i < kTailBands; i++) {
          const int g = kSteps - kTailBands + i;
          if (i >= 3) mbar_wait(bar + kBarTe + 8 * (i - 3), 0);
          uint32_t it = 0;
          while (!__all_sync(0xffffffffu, (int)(seen - (ep + g + 1)) >= 0)) {
            seen = ld_acquire(&g_oflag[ps * 32 + (lane & 3)]);
            if (++it > LIMIT) { BAIL(0x3000000 + g); break; }
          }
          if (lane == 0)
            bulk_load(sbase + tail_buf(buf), g_o + (size_t)(g * 28 + ps) * kOTileBytes, kOTileBytes, bar + kBarT + 8 * i);
          __syncwarp();
          buf = buf == 2 ? 0 : buf + 1;
        }
      } else {
        const int p = wl - 1;
        const bool on = !X_NOH && (lane == 0 ? strip > 0 : strip < 6);
        const int nb = on ? cta + (lane == 0 ? -4 : 4) : cta;
        const uint32_t bytes = X_NOH ? 0 : ((strip > 0 && strip < 6) ? 2 * kHaloBytes : kHaloBytes);
        int slot = p, g = 0;
#pragma unroll 1
        for (int a = p; a < kExch; a += 3) {
          named_bar_sync(kNbTile + a % 6, 160);
          const uint32_t sl = ring + slot * kSlot;
          if (lane < 2) {
            fence_proxy_async();
            if (on) bulk_store(g_halo + (size_t)((cta * 2 + lane) * kExch + a) * kHaloPitch, sl + (3 + 13 * lane) * kCol, kHaloBytes);
            bulk_commit();
            bulk_wait<0>();
          }
          __syncwarp();
          g += __ffs(~__ballot_sync(0xffffffffu, lane < 4 && mbar_test_wait(bar + kBarO + 8 * (g + lane), 0))) - 1;
          __syncwarp();
          if (lane < 2) {
            TRACE(160 + a * 4 + 0);
            publish_fence();
            st_relaxed(&g_hflag[cta * 32 + 4 * lane + p], ep + a + 1);
            if (lane == 0) {
              if (g) red_max(&g_oflag[ps * 32 + head], ep + g);
              mbar_expect_tx(bar + kBarFull + 8 * a, bytes);
            } else {
              mbar_arrive(bar + kBarFull + 8 * a);
            }
            TRACE(160 + a * 4 + 1);
            uint32_t it = 0;
            while (true) {
              const bool ok = !on || (int)(ld_acquire(&g_hflag[nb * 32 + 4 * (lane ^ 1) + p]) - (ep + a + 1)) >= 0;
              if (__all_sync(3u, ok)) break;
              if (++it > LIMIT) { BAIL(0x1000000 + a); break; }
            }
            TRACE(160 + a * 4 + 2);
            if (on) bulk_load(sl + lane * 19 * kCol, g_halo + (size_t)((nb * 2 + (lane ^ 1)) * kExch + a) * kHaloPitch, kHaloBytes,
                              bar + kBarFull + 8 * a);
            TRACE(160 + a * 4 + 3);
          }
          __syncwarp();
          slot = slot >= 2 ? slot - 2 : slot + 3;
        }
        if (lane == 0) {
#pragma unroll 1
          for (g = kSteps - DEV_PB + p; g < kSteps; g += 3) {
            if (g < kSteps - 3) mbar_wait_sleep(bar + kBarO + 8 * g, 0);
            else mbar_wait(bar + kBarO + 8 * g, 0);
            TRACE(370 + g * 2);
            publish_fence();
            red_max(&g_oflag[ps * 32 + head], ep + g + 1);
            TRACE(371 + g * 2);
          }
          if (p == (DEV_PB - 1) % 3) GT(1);
        }
      }
      __syncwarp();
      if (lane == 0) st_relaxed(&g_epoch[cta * 32 + wl], (ep >> 5) + 1);
    }
  } else {
    using namespace kb;
    const uint32_t bar = sbase + kOffBar, sA = sbase + kOffA;
    const int k = cta - kStripCtas;
    if (wg < 3) {
      reg_inc<160>();
      named_bar_sync(0, 512);
      uint32_t wf[12][4];
      mbar_wait(bar + 56, 0);
      {
        const int kr = (lane & 7) + ((lane >> 4) << 3);
        const uint32_t wa = sbase + wg * kWoBlk + kr * 128 + (((2 * wl + ((lane >> 3) & 1)) ^ (lane & 7)) << 4);
#pragma unroll
        for (int kk = 0; kk < 12; kk++) ldmatrix_x4_t(wf[kk], wa + kk * 2048);
      }
      named_bar_sync(3 + wg, 128);
      const int px = (2 * (lane >> 4) + (lane & 1)) * 4 + ((lane & 7) >> 1);
      const uint32_t sto = sbase + wg * kWoBlk + px * 128 + (((2 * wl + ((lane >> 3) & 1)) ^ (px & 7)) << 4);
      int st = 0, sb = 0;
      uint32_t ph = 0;
      uint32_t pk[16];
#pragma unroll
      for (int i = 0; i < 16; i++) pk[i] = 0u;
#pragma unroll 1
      for (int t = k; t < kProjTiles + kProjCtas; t += kProjCtas) {
        float acc[32];
        if (t < kProjTiles) PWAIT(bar + 8 * st, ph);
        if (warp == 0) TRACE(16 + (t / kProjCtas) * 4 + 1);
        const uint32_t blo = (uint32_t)make_desc(sA + st * kOTileBytes, 128, 768, 0);
        if (DEV_TURN && (t > k || wg)) named_bar_sync(6 + wg, 256);
        wg_fence();
#pragma unroll
        for (int kk = 0; kk < 12; kk++)
          wgmma_m64n64k16_rs<1>(acc, wf[kk][0], wf[kk][1], wf[kk][2], wf[kk][3],
                                desc64(blo + (((kk / 3) * 6144 + (kk % 3) * 256) >> 4), 768 >> 4), kk != 0);
        wg_commit();
        if (DEV_TURN && (wg < 2 || t < kProjTiles)) named_bar_arrive(6 + (wg == 2 ? 0 : wg + 1), 256);
        {
          const int tq = t - kProjCtas, g = tq / 28, tp = tq - 28 * g, tpar = tp / 7, tstrip = tp - 7 * tpar;
#pragma unroll
          for (int jp = 0; jp < 4; jp++)
            stmatrix_x4_t(sto + sb * 8192 + jp * 2048, pk[4 * jp], pk[4 * jp + 1], pk[4 * jp + 2], pk[4 * jp + 3]);
          fence_proxy_async();
          if (wl == 0 && lane == 0) bulk_wait_read1();
          named_bar_sync(3 + wg, 128);
          if (wl == 0 && lane == 0 && tq >= 0) {
            tma_store_5d(&tm_o2, sbase + wg * kWoBlk + sb * 8192, 0, 4 * g, 16 * tstrip, 3 * (tpar & 1) + wg, tpar >> 1);
            bulk_commit();
          }
          __syncwarp();
          if (warp == 0) TRACE(12 + (t / kProjCtas) * 4 + 3);
          sb = sb == 2 ? 0 : sb + 1;
        }
        wg_wait<0>();
        fence_regs(acc);
        if (lane == 0) mbar_arrive(bar + 64 + 8 * st);
        if (warp == 0) TRACE(16 + (t / kProjCtas) * 4 + 2);
#pragma unroll
        for (int i = 0; i < 16; i++) pk[i] = pack_bf16(acc[2 * i], acc[2 * i + 1]);
        if (++st == kStages) { st = 0; ph ^= 1; }
      }
      if (wl == 0 && lane == 0) bulk_wait<0>();
      if (threadIdx.x == 0) GT(1);
    } else {
      reg_dec<32>();
      if (lane == 0) {
        mbar_init(bar + 16 * wl, 1);
        mbar_init(bar + 16 * wl + 8, 1);
        mbar_init(bar + 64 + 16 * wl, 12);
        mbar_init(bar + 64 + 16 * wl + 8, 12);
        fence_mbar_init();
      }
      __syncwarp();
      named_bar_sync(0, 512);
      if (wl == 3 && lane == 0) {
        if (DEV_WOD) __nanosleep(DEV_WOD);
        mbar_expect_tx(bar + 56, 3 * kWoBlk);
#pragma unroll 1
        for (int i = 0; i < 3; i++) tma_load_2d(sbase + i * kWoBlk, &tm_wo2, bar + 56, i * 64, 0);
      }
      __syncwarp();
      if (wl == 3 && k < 4) {
        if (lane == 0) {
          const uint32_t e0 = ld_relaxed(&g_epoch[cta * 32 + 3]);
          const uint32_t stg = sA + (kStages - 1) * kOTileBytes;
          mbar_expect_tx(bar + 48, 3 * ka::kWAtom);
#pragma unroll 1
          for (int i = 0; i < 3; i++) tma_load_2d(stg + i * ka::kWAtom, &tm_wo, bar + 48, k * 48 + i * 16, 0);
          mbar_wait(bar + 48, 0);
          bulk_store(g_wop + k * 3 * ka::kWAtom, stg, 3 * ka::kWAtom);
          bulk_commit();
          bulk_wait<0>();
          publish_fence();
          st_relaxed(&g_wflag[k * 32], e0 * 32u + 1);
          st_relaxed(&g_epoch[cta * 32 + 3], e0 + 1);
        }
        __syncwarp();
        named_bar_arrive(2, 64);
      }
      if (wl == 2 && k < 4) named_bar_sync(2, 64);
      if (wl < 3 && lane < 4) {
        const uint32_t e0 = ld_relaxed(&g_epoch[cta * 32 + wl]);
#pragma unroll 1
        for (int it = wl;; it += 3) {
          const int t = k + it * kProjCtas;
          if (t >= kProjTiles) break;
          const int st = it % kStages;
          const int g = t / 28, tp = t - 28 * g;
          uint32_t sp = 0;
          while (true) {
            const bool ok = (int)(ld_acquire(&g_oflag[tp * 32 + lane]) - (e0 * 32u + g + 1)) >= 0;
            if (__all_sync(15u, ok)) break;
            if (DEV_PS) __nanosleep(DEV_PS);
            if (++sp > LIMIT) { BAIL(0x2000000 + t); break; }
          }
          if (it >= kStages) mbar_wait(bar + 64 + 8 * st, ((it / kStages) & 1) ^ 1);
          TRACE(16 + it * 4 + 0);
          if (lane == 0) {
            mbar_expect_tx(bar + 8 * st, kOTileBytes);
            bulk_load(sA + st * kOTileBytes, g_o + (size_t)t * kOTileBytes, kOTileBytes, bar + 8 * st);
          }
          __syncwarp(15u);
        }
        if (lane == 0) st_relaxed(&g_epoch[cta * 32 + wl], e0 + 1);
      }
    }
  }
}

}

namespace {

typedef CUresult (*EncodeTiledFn)(CUtensorMap*, CUtensorMapDataType, cuuint32_t, void*, const cuuint64_t*,
                                  const cuuint64_t*, const cuuint32_t*, const cuuint32_t*, CUtensorMapInterleave,
                                  CUtensorMapSwizzle, CUtensorMapL2promotion, CUtensorMapFloatOOBfill);

EncodeTiledFn get_encode_fn() {
  static EncodeTiledFn fn = nullptr;
  if (!fn) {
    void* p = nullptr;
    cudaDriverEntryPointQueryResult qres;
    if (cudaGetDriverEntryPoint("cuTensorMapEncodeTiled", &p, cudaEnableDefault, &qres) == cudaSuccess)
      fn = reinterpret_cast<EncodeTiledFn>(p);
  }
  return fn;
}

CUtensorMap make_map(void* base, int rank, const cuuint64_t* dims, const cuuint64_t* strides, const cuuint32_t* box,
                     CUtensorMapSwizzle swz) {
  CUtensorMap m;
  cuuint32_t es[5] = {1, 1, 1, 1, 1};
  get_encode_fn()(&m, CU_TENSOR_MAP_DATA_TYPE_BFLOAT16, (cuuint32_t)rank, base, dims, strides, box, es,
                  CU_TENSOR_MAP_INTERLEAVE_NONE, swz, CU_TENSOR_MAP_L2_PROMOTION_L2_128B,
                  CU_TENSOR_MAP_FLOAT_OOB_FILL_NONE);
  return m;
}

}

extern "C" void kernel_launch(void* const* d_in, const int* in_sizes, int n_in, void* d_out, int out_size) {
  using namespace nat;
  (void)in_sizes; (void)n_in; (void)out_size;
  const __nv_bfloat16* x = (const __nv_bfloat16*)d_in[0];
  const __nv_bfloat16* wqkv = (const __nv_bfloat16*)d_in[1];
  const __nv_bfloat16* wo = (const __nv_bfloat16*)d_in[2];
  const __nv_bfloat16* rpb = (const __nv_bfloat16*)d_in[3];
  __nv_bfloat16* out = (__nv_bfloat16*)d_out;

  CUtensorMap tm_x, tm_h, tm_r, tm_w, tm_wo, tm_out, tm_wo2, tm_o2;
  {
    cuuint64_t dims[5] = {64, 112, 112, 6, 2};
    cuuint64_t str[4] = {768, 2ull * 224 * 384, 128, 224ull * 384};
    cuuint32_t box[5] = {64, 16, 4, 3, 1};
    tm_x = make_map((void*)x, 5, dims, str, box, CU_TENSOR_MAP_SWIZZLE_128B);
    cuuint32_t boxh[5] = {64, 3, 5, 1, 1}, boxr[5] = {64, 16, 1, 1, 1};
    tm_h = make_map((void*)x, 5, dims, str, boxh, CU_TENSOR_MAP_SWIZZLE_128B);
    tm_r = make_map((void*)x, 5, dims, str, boxr, CU_TENSOR_MAP_SWIZZLE_128B);
  }
  {
    cuuint64_t dims[2] = {576, 192};
    cuuint64_t str[1] = {1152};
    cuuint32_t box[2] = {16, 192};
    tm_w = make_map((void*)wqkv, 2, dims, str, box, CU_TENSOR_MAP_SWIZZLE_32B);
  }
  {
    cuuint64_t dims[2] = {192, 192};
    cuuint64_t str[1] = {384};
    cuuint32_t box[2] = {16, 192};
    tm_wo = make_map((void*)wo, 2, dims, str, box, CU_TENSOR_MAP_SWIZZLE_32B);
    cuuint32_t box2[2] = {64, 192};
    tm_wo2 = make_map((void*)wo, 2, dims, str, box2, CU_TENSOR_MAP_SWIZZLE_128B);
  }
  {
    cuuint64_t dims[5] = {192, 112, 112, 2, 2};
    cuuint64_t str[4] = {2ull * 224 * 384, 768, 384, 224ull * 384};
    cuuint32_t box[5] = {48, 4, 16, 1, 1};
    tm_out = make_map((void*)out, 5, dims, str, box, CU_TENSOR_MAP_SWIZZLE_NONE);
  }
  {
    cuuint64_t dims[5] = {64, 112, 112, 6, 2};
    cuuint64_t str[4] = {2ull * 224 * 384, 768, 128, 224ull * 384};
    cuuint32_t box[5] = {64, 4, 16, 1, 1};
    tm_o2 = make_map((void*)out, 5, dims, str, box, CU_TENSOR_MAP_SWIZZLE_128B);
  }
  cudaFuncSetAttribute(nat_kernel, cudaFuncAttributeMaxDynamicSharedMemorySize, kSmemBytes);
  nat_kernel<<<kStripCtas + kProjCtas, kThreads, kSmemBytes>>>(wqkv, rpb, tm_x, tm_w, tm_h, tm_r, tm_wo, tm_out, tm_wo2, tm_o2);
}
```

```cpp
#include <cuda_runtime.h>
#include <cuda_bf16.h>
#include <cuda.h>
#include <stdint.h>

#define DEVI __device__ __forceinline__

namespace nat {

DEVI uint32_t smem_u32(const void* p) { return (uint32_t)__cvta_generic_to_shared(p); }

DEVI void mbar_init(uint32_t bar, uint32_t count) {
  asm volatile("mbarrier.init.shared::cta.b64 [%0], %1;" ::"r"(bar), "r"(count) : "memory");
}
DEVI void mbar_expect_tx(uint32_t bar, uint32_t bytes) {
  asm volatile("mbarrier.arrive.expect_tx.shared::cta.b64 _, [%0], %1;" ::"r"(bar), "r"(bytes) : "memory");
}
DEVI void mbar_arrive(uint32_t bar) {
  asm volatile("mbarrier.arrive.shared::cta.b64 _, [%0];" ::"r"(bar) : "memory");
}
DEVI bool mbar_try_wait(uint32_t bar, uint32_t parity) {
  uint32_t ok;
  asm volatile(
      "{\n.reg .pred p;\nmbarrier.try_wait.parity.shared::cta.b64 p, [%1], %2;\nselp.u32 %0, 1, 0, p;\n}\n"
      : "=r"(ok)
      : "r"(bar), "r"(parity)
      : "memory");
  return ok != 0;
}
DEVI bool mbar_test_wait(uint32_t bar, uint32_t parity) {
  uint32_t ok;
  asm volatile(
      "{\n.reg .pred p;\nmbarrier.test_wait.parity.shared::cta.b64 p, [%1], %2;\nselp.u32 %0, 1, 0, p;\n}\n"
      : "=r"(ok)
      : "r"(bar), "r"(parity)
      : "memory");
  return ok != 0;
}
#define BAIL(code) __trap()
#define LIMIT (1u << 20)
DEVI void mbar_wait(uint32_t bar, uint32_t parity) {
  uint32_t it = 0;
  while (!mbar_try_wait(bar, parity)) {
    if (++it > LIMIT) { BAIL(bar & 0xfffff); break; }
  }
}
DEVI void fence_mbar_init() { asm volatile("fence.mbarrier_init.release.cluster;" ::: "memory"); }

DEVI void tma_load_2d(uint32_t dst, const CUtensorMap* tm, uint32_t bar, int c0, int c1) {
  asm volatile(
      "cp.async.bulk.tensor.2d.shared::cluster.global.mbarrier::complete_tx::bytes [%0], [%1, {%3, %4}], [%2];"
      ::"r"(dst), "l"(tm), "r"(bar), "r"(c0), "r"(c1)
      : "memory");
}
DEVI void tma_store_5d(const CUtensorMap* tm, uint32_t src, int c0, int c1, int c2, int c3, int c4) {
  asm volatile("cp.async.bulk.tensor.5d.global.shared::cta.bulk_group [%0, {%2, %3, %4, %5, %6}], [%1];"
               ::"l"(tm), "r"(src), "r"(c0), "r"(c1), "r"(c2), "r"(c3), "r"(c4)
               : "memory");
}
DEVI void bulk_wait_read1() { asm volatile("cp.async.bulk.wait_group.read 1;" ::: "memory"); }
DEVI void bulk_wait_read() { asm volatile("cp.async.bulk.wait_group.read 0;" ::: "memory"); }
DEVI void tma_load_4d(uint32_t dst, const CUtensorMap* tm, uint32_t bar, int c0, int c1, int c2, int c3) {
  asm volatile(
      "cp.async.bulk.tensor.4d.shared::cluster.global.mbarrier::complete_tx::bytes [%0], [%1, {%3, %4, %5, %6}], [%2];"
      ::"r"(dst), "l"(tm), "r"(bar), "r"(c0), "r"(c1), "r"(c2), "r"(c3)
      : "memory");
}
DEVI void tma_load_5d(uint32_t dst, const CUtensorMap* tm, uint32_t bar, int c0, int c1, int c2, int c3, int c4) {
  asm volatile(
      "cp.async.bulk.tensor.5d.shared::cluster.global.mbarrier::complete_tx::bytes [%0], [%1, {%3, %4, %5, %6, %7}], [%2];"
      ::"r"(dst), "l"(tm), "r"(bar), "r"(c0), "r"(c1), "r"(c2), "r"(c3), "r"(c4)
      : "memory");
}
DEVI void tma_load_5d_mc(uint32_t dst, const CUtensorMap* tm, uint32_t bar, int c0, int c1, int c2, int c3, int c4, uint16_t mask) {
  asm volatile(
      "cp.async.bulk.tensor.5d.shared::cluster.global.mbarrier::complete_tx::bytes.multicast::cluster [%0], [%1, {%3, %4, %5, %6, %7}], [%2], %8;"
      ::"r"(dst), "l"(tm), "r"(bar), "r"(c0), "r"(c1), "r"(c2), "r"(c3), "r"(c4), "h"(mask)
      : "memory");
}
DEVI uint32_t mapa(uint32_t addr, uint32_t rank) {
  uint32_t r;
  asm("mapa.shared::cluster.u32 %0, %1, %2;" : "=r"(r) : "r"(addr), "r"(rank));
  return r;
}
DEVI void mbar_arrive_cluster(uint32_t cluster_bar) {
  asm volatile("mbarrier.arrive.shared::cluster.b64 _, [%0];" ::"r"(cluster_bar) : "memory");
}
DEVI void cluster_arrive_relaxed() { asm volatile("barrier.cluster.arrive.relaxed.aligned;" ::: "memory"); }
DEVI void cluster_wait() { asm volatile("barrier.cluster.wait.aligned;" ::: "memory"); }
DEVI void tma_prefetch_5d(const CUtensorMap* tm, int c0, int c1, int c2, int c3, int c4) {
  asm volatile("cp.async.bulk.prefetch.tensor.5d.L2.global [%0, {%1, %2, %3, %4, %5}];"
               ::"l"(tm), "r"(c0), "r"(c1), "r"(c2), "r"(c3), "r"(c4)
               : "memory");
}
DEVI void bulk_load(uint32_t dst, const void* src, uint32_t bytes, uint32_t bar) {
  asm volatile("cp.async.bulk.shared::cluster.global.mbarrier::complete_tx::bytes [%0], [%1], %2, [%3];"
               ::"r"(dst), "l"(src), "r"(bytes), "r"(bar) : "memory");
}
DEVI void bulk_store(void* dst, uint32_t src, uint32_t bytes) {
  asm volatile("cp.async.bulk.global.shared::cta.bulk_group [%0], [%1], %2;" ::"l"(dst), "r"(src), "r"(bytes) : "memory");
}
DEVI void bulk_commit() { asm volatile("cp.async.bulk.commit_group;" ::: "memory"); }
template <int N>
DEVI void bulk_wait() { asm volatile("cp.async.bulk.wait_group %0;" ::"n"(N) : "memory"); }

template <int N>
DEVI void reg_dec() { asm volatile("setmaxnreg.dec.sync.aligned.u32 %0;" ::"n"(N)); }
template <int N>
DEVI void reg_inc() { asm volatile("setmaxnreg.inc.sync.aligned.u32 %0;" ::"n"(N)); }

DEVI void wg_fence() { asm volatile("wgmma.fence.sync.aligned;" ::: "memory"); }
DEVI void wg_commit() { asm volatile("wgmma.commit_group.sync.aligned;" ::: "memory"); }
template <int N>
DEVI void wg_wait() { asm volatile("wgmma.wait_group.sync.aligned %0;" ::"n"(N) : "memory"); }
template <int N>
DEVI void fence_regs(float (&d)[N]) {
#pragma unroll
  for (int i = 0; i < N; i++) asm volatile("" : "+f"(d[i])::"memory");
}

DEVI uint64_t make_desc(uint32_t addr, uint32_t lbo, uint32_t sbo, uint32_t swz) {
  return (uint64_t)((addr & 0x3FFFFu) >> 4) | ((uint64_t)((lbo & 0x3FFFFu) >> 4) << 16) |
         ((uint64_t)((sbo & 0x3FFFFu) >> 4) << 32) | ((uint64_t)swz << 62);
}

DEVI uint64_t desc64(uint32_t lo, uint32_t hi) {
  uint64_t d;
  asm("mov.b64 %0, {%1, %2};" : "=l"(d) : "r"(lo), "r"(hi));
  return d;
}
DEVI uint32_t pack_bf16(float lo, float hi) {
  uint32_t r;
  asm("cvt.rn.bf16x2.f32 %0, %1, %2;" : "=r"(r) : "f"(hi), "f"(lo));
  return r;
}
DEVI float ex2(float x) {
  float r;
  asm("ex2.approx.ftz.f32 %0, %1;" : "=f"(r) : "f"(x));
  return r;
}
DEVI float rcp_approx(float x) {
  float r;
  asm("rcp.approx.ftz.f32 %0, %1;" : "=f"(r) : "f"(x));
  return r;
}
DEVI uint32_t movmatrix_t(uint32_t a) {
  uint32_t r;
  asm("movmatrix.sync.aligned.m8n8.trans.b16 %0, %1;" : "=r"(r) : "r"(a));
  return r;
}
DEVI void ldmatrix_x4(uint32_t (&r)[4], uint32_t addr) {
  asm volatile("ldmatrix.sync.aligned.m8n8.x4.shared.b16 {%0, %1, %2, %3}, [%4];"
               : "=r"(r[0]), "=r"(r[1]), "=r"(r[2]), "=r"(r[3]) : "r"(addr) : "memory");
}
DEVI void ldmatrix_x4(uint32_t& r0, uint32_t& r1, uint32_t& r2, uint32_t& r3, uint32_t addr) {
  asm volatile("ldmatrix.sync.aligned.m8n8.x4.shared.b16 {%0, %1, %2, %3}, [%4];"
               : "=r"(r0), "=r"(r1), "=r"(r2), "=r"(r3) : "r"(addr) : "memory");
}
DEVI void ldmatrix_x2(uint32_t& r0, uint32_t& r1, uint32_t addr) {
  asm volatile("ldmatrix.sync.aligned.m8n8.x2.shared.b16 {%0, %1}, [%2];"
               : "=r"(r0), "=r"(r1) : "r"(addr) : "memory");
}
DEVI void ldmatrix_x4_t(uint32_t (&r)[4], uint32_t addr) {
  asm volatile("ldmatrix.sync.aligned.m8n8.x4.trans.shared.b16 {%0, %1, %2, %3}, [%4];"
               : "=r"(r[0]), "=r"(r[1]), "=r"(r[2]), "=r"(r[3]) : "r"(addr) : "memory");
}
DEVI void stmatrix_x4(uint32_t addr, uint32_t r0, uint32_t r1, uint32_t r2, uint32_t r3) {
  asm volatile("stmatrix.sync.aligned.m8n8.x4.shared.b16 [%0], {%1, %2, %3, %4};"
               ::"r"(addr), "r"(r0), "r"(r1), "r"(r2), "r"(r3) : "memory");
}
DEVI void stmatrix_x4_t(uint32_t addr, uint32_t r0, uint32_t r1, uint32_t r2, uint32_t r3) {
  asm volatile("stmatrix.sync.aligned.m8n8.x4.trans.shared.b16 [%0], {%1, %2, %3, %4};"
               ::"r"(addr), "r"(r0), "r"(r1), "r"(r2), "r"(r3) : "memory");
}
DEVI void mma16816(float (&d)[4], const uint32_t (&a)[4], uint32_t b0, uint32_t b1) {
  asm volatile("mma.sync.aligned.m16n8k16.row.col.f32.bf16.bf16.f32 {%0, %1, %2, %3}, {%4, %5, %6, %7}, {%8, %9}, {%0, %1, %2, %3};"
               : "+f"(d[0]), "+f"(d[1]), "+f"(d[2]), "+f"(d[3])
               : "r"(a[0]), "r"(a[1]), "r"(a[2]), "r"(a[3]), "r"(b0), "r"(b1));
}
DEVI void mma16816_z(float (&d)[4], const uint32_t (&a)[4], uint32_t b0, uint32_t b1) {
  asm volatile("mma.sync.aligned.m16n8k16.row.col.f32.bf16.bf16.f32 {%0, %1, %2, %3}, {%4, %5, %6, %7}, {%8, %9}, {%10, %10, %10, %10};"
               : "=f"(d[0]), "=f"(d[1]), "=f"(d[2]), "=f"(d[3])
               : "r"(a[0]), "r"(a[1]), "r"(a[2]), "r"(a[3]), "r"(b0), "r"(b1), "f"(0.f));
}
DEVI void mma16816_c(float (&d)[4], const uint32_t (&a)[4], uint32_t b0, uint32_t b1, const float (&c)[4]) {
  asm volatile("mma.sync.aligned.m16n8k16.row.col.f32.bf16.bf16.f32 {%0, %1, %2, %3}, {%4, %5, %6, %7}, {%8, %9}, {%10, %11, %12, %13};"
               : "=f"(d[0]), "=f"(d[1]), "=f"(d[2]), "=f"(d[3])
               : "r"(a[0]), "r"(a[1]), "r"(a[2]), "r"(a[3]), "r"(b0), "r"(b1), "f"(c[0]), "f"(c[1]), "f"(c[2]), "f"(c[3]));
}
template <int BIT>
DEVI void sel2(uint32_t mask, float& r0, float& r1, float a0, float a1, float b0, float b1) {
  asm("{\n.reg .pred p;\n.reg .b32 t;\nand.b32 t, %2, %7;\nsetp.ne.b32 p, t, 0;\nselp.f32 %0, %3, %5, p;\nselp.f32 %1, %4, %6, p;\n}"
      : "=f"(r0), "=f"(r1) : "r"(mask), "f"(a0), "f"(a1), "f"(b0), "f"(b1), "n"(BIT));
}
template <int BIT>
DEVI void split2(uint32_t mask, uint32_t& r0, uint32_t& r1, uint32_t v) {
  asm("{\n.reg .pred p;\n.reg .b32 t;\nand.b32 t, %2, %4;\nsetp.ne.b32 p, t, 0;\nselp.b32 %0, %3, 0, p;\nselp.b32 %1, 0, %3, p;\n}"
      : "=r"(r0), "=r"(r1) : "r"(mask), "r"(v), "n"(BIT));
}
DEVI void red_add1(uint32_t* p) {
  asm volatile("red.relaxed.gpu.global.add.u32 [%0], 1;" ::"l"(p) : "memory");
}
DEVI bool named_bar_or(int id, int n, bool v) {
  uint32_t r;
  asm volatile("{\n.reg .pred p, q;\nsetp.ne.u32 p, %1, 0;\nbar.red.or.pred q, %2, %3, p;\nselp.u32 %0, 1, 0, q;\n}"
               : "=r"(r) : "r"((uint32_t)v), "r"(id), "r"(n) : "memory");
  return r != 0;
}
DEVI void cp_async16(uint32_t dst, const void* src) {
  asm volatile("cp.async.cg.shared.global [%0], [%1], 16;" ::"r"(dst), "l"(src) : "memory");
}
DEVI void cp_async_wait_all() { asm volatile("cp.async.wait_all;" ::: "memory"); }
DEVI void stg128(void* p, uint4 v) {
  asm volatile("st.relaxed.gpu.global.v4.u32 [%0], {%1, %2, %3, %4};" ::"l"(p), "r"(v.x), "r"(v.y), "r"(v.z), "r"(v.w) : "memory");
}
DEVI void red_max(uint32_t* p, uint32_t v) {
  asm volatile("red.relaxed.gpu.global.max.u32 [%0], %1;" ::"l"(p), "r"(v) : "memory");
}
DEVI uint4 ldg128(const void* p) {
  uint4 v;
  asm volatile("ld.global.nc.v4.u32 {%0, %1, %2, %3}, [%4];" : "=r"(v.x), "=r"(v.y), "=r"(v.z), "=r"(v.w) : "l"(p));
  return v;
}
DEVI uint32_t ld_acquire(const uint32_t* p) {
  uint32_t v;
  asm volatile("ld.acquire.gpu.global.u32 %0, [%1];" : "=r"(v) : "l"(p) : "memory");
  return v;
}
DEVI uint32_t ld_relaxed(const uint32_t* p) {
  uint32_t v;
  asm volatile("ld.relaxed.gpu.global.u32 %0, [%1];" : "=r"(v) : "l"(p) : "memory");
  return v;
}
DEVI void st_relaxed(uint32_t* p, uint32_t v) {
  asm volatile("st.relaxed.gpu.global.u32 [%0], %1;" ::"l"(p), "r"(v) : "memory");
}
DEVI void st_release(uint32_t* p, uint32_t v) {
  asm volatile("st.release.gpu.global.u32 [%0], %1;" ::"l"(p), "r"(v) : "memory");
}
DEVI void fence_gpu() { asm volatile("fence.acq_rel.gpu;" ::: "memory"); }
DEVI uint32_t lds32(uint32_t addr) {
  uint32_t v;
  asm volatile("ld.shared.u32 %0, [%1];" : "=r"(v) : "r"(addr) : "memory");
  return v;
}
DEVI uint4 lds128(uint32_t addr) {
  uint4 v;
  asm volatile("ld.shared.v4.u32 {%0, %1, %2, %3}, [%4];" : "=r"(v.x), "=r"(v.y), "=r"(v.z), "=r"(v.w) : "r"(addr) : "memory");
  return v;
}
DEVI int lds32v(uint32_t addr) {
  int v;
  asm volatile("ld.volatile.shared.s32 %0, [%1];" : "=r"(v) : "r"(addr) : "memory");
  return v;
}
DEVI void sts32(uint32_t addr, uint32_t v) {
  asm volatile("st.shared.u32 [%0], %1;" ::"r"(addr), "r"(v) : "memory");
}
DEVI void sts128(uint32_t addr, uint4 v) {
  asm volatile("st.shared.v4.u32 [%0], {%1, %2, %3, %4};" ::"r"(addr), "r"(v.x), "r"(v.y), "r"(v.z), "r"(v.w) : "memory");
}
DEVI void named_bar_arrive(int id, int n) { asm volatile("bar.arrive %0, %1;" ::"r"(id), "r"(n) : "memory"); }
DEVI void named_bar_sync(int id, int n) { asm volatile("bar.sync %0, %1;" ::"r"(id), "r"(n) : "memory"); }
DEVI void fence_proxy_async() { asm volatile("fence.proxy.async.shared::cta;" ::: "memory"); }
DEVI void fence_proxy_async_global() { asm volatile("fence.proxy.async.global;" ::: "memory"); }
DEVI int clampi(int v, int lo, int hi) { return v < lo ? lo : (v > hi ? hi : v); }

template <int TA, int TB> DEVI void wgmma_m64n144k16_ss(float (&d)[72], uint64_t descA, uint64_t descB, int scaleD) {
  asm volatile("{\n.reg .pred p;\nsetp.ne.b32 p, %74, 0;\nwgmma.mma_async.sync.aligned.m64n144k16.f32.bf16.bf16 {%0, %1, %2, %3, %4, %5, %6, %7, %8, %9, %10, %11, %12, %13, %14, %15, %16, %17, %18, %19, %20, %21, %22, %23, %24, %25, %26, %27, %28, %29, %30, %31, %32, %33, %34, %35, %36, %37, %38, %39, %40, %41, %42, %43, %44, %45, %46, %47, %48, %49, %50, %51, %52, %53, %54, %55, %56, %57, %58, %59, %60, %61, %62, %63, %64, %65, %66, %67, %68, %69, %70, %71}, %72, %73, p, 1, 1, %75, %76;\n}\n"
    : "+f"(d[0]), "+f"(d[1]), "+f"(d[2]), "+f"(d[3]), "+f"(d[4]), "+f"(d[5]), "+f"(d[6]), "+f"(d[7]), "+f"(d[8]), "+f"(d[9]), "+f"(d[10]), "+f"(d[11]), "+f"(d[12]), "+f"(d[13]), "+f"(d[14]), "+f"(d[15]), "+f"(d[16]), "+f"(d[17]), "+f"(d[18]), "+f"(d[19]), "+f"(d[20]), "+f"(d[21]), "+f"(d[22]), "+f"(d[23]), "+f"(d[24]), "+f"(d[25]), "+f"(d[26]), "+f"(d[27]), "+f"(d[28]), "+f"(d[29]), "+f"(d[30]), "+f"(d[31]), "+f"(d[32]), "+f"(d[33]), "+f"(d[34]), "+f"(d[35]), "+f"(d[36]), "+f"(d[37]), "+f"(d[38]), "+f"(d[39]), "+f"(d[40]), "+f"(d[41]), "+f"(d[42]), "+f"(d[43]), "+f"(d[44]), "+f"(d[45]), "+f"(d[46]), "+f"(d[47]), "+f"(d[48]), "+f"(d[49]), "+f"(d[50]), "+f"(d[51]), "+f"(d[52]), "+f"(d[53]), "+f"(d[54]), "+f"(d[55]), "+f"(d[56]), "+f"(d[57]), "+f"(d[58]), "+f"(d[59]), "+f"(d[60]), "+f"(d[61]), "+f"(d[62]), "+f"(d[63]), "+f"(d[64]), "+f"(d[65]), "+f"(d[66]), "+f"(d[67]), "+f"(d[68]), "+f"(d[69]), "+f"(d[70]), "+f"(d[71])
    : "l"(descA), "l"(descB), "r"(scaleD), "n"(TA), "n"(TB));
}

template <int TB> DEVI void wgmma_m64n64k16_rs(float (&d)[32], uint32_t a0, uint32_t a1, uint32_t a2, uint32_t a3, uint64_t descB, int scaleD) {
  asm volatile("{\n.reg .pred p;\nsetp.ne.b32 p, %37, 0;\nwgmma.mma_async.sync.aligned.m64n64k16.f32.bf16.bf16 {%0, %1, %2, %3, %4, %5, %6, %7, %8, %9, %10, %11, %12, %13, %14, %15, %16, %17, %18, %19, %20, %21, %22, %23, %24, %25, %26, %27, %28, %29, %30, %31}, {%32, %33, %34, %35}, %36, p, 1, 1, %38;\n}\n"
    : "+f"(d[0]), "+f"(d[1]), "+f"(d[2]), "+f"(d[3]), "+f"(d[4]), "+f"(d[5]), "+f"(d[6]), "+f"(d[7]), "+f"(d[8]), "+f"(d[9]), "+f"(d[10]), "+f"(d[11]), "+f"(d[12]), "+f"(d[13]), "+f"(d[14]), "+f"(d[15]), "+f"(d[16]), "+f"(d[17]), "+f"(d[18]), "+f"(d[19]), "+f"(d[20]), "+f"(d[21]), "+f"(d[22]), "+f"(d[23]), "+f"(d[24]), "+f"(d[25]), "+f"(d[26]), "+f"(d[27]), "+f"(d[28]), "+f"(d[29]), "+f"(d[30]), "+f"(d[31])
    : "r"(a0), "r"(a1), "r"(a2), "r"(a3), "l"(descB), "r"(scaleD), "n"(TB));
}

template <int TA, int TB> DEVI void wgmma_m64n48k16_ss(float (&d)[24], uint64_t descA, uint64_t descB, int scaleD) {
  asm volatile("{\n.reg .pred p;\nsetp.ne.b32 p, %26, 0;\nwgmma.mma_async.sync.aligned.m64n48k16.f32.bf16.bf16 {%0, %1, %2, %3, %4, %5, %6, %7, %8, %9, %10, %11, %12, %13, %14, %15, %16, %17, %18, %19, %20, %21, %22, %23}, %24, %25, p, 1, 1, %27, %28;\n}\n"
    : "+f"(d[0]), "+f"(d[1]), "+f"(d[2]), "+f"(d[3]), "+f"(d[4]), "+f"(d[5]), "+f"(d[6]), "+f"(d[7]), "+f"(d[8]), "+f"(d[9]), "+f"(d[10]), "+f"(d[11]), "+f"(d[12]), "+f"(d[13]), "+f"(d[14]), "+f"(d[15]), "+f"(d[16]), "+f"(d[17]), "+f"(d[18]), "+f"(d[19]), "+f"(d[20]), "+f"(d[21]), "+f"(d[22]), "+f"(d[23])
    : "l"(descA), "l"(descB), "r"(scaleD), "n"(TA), "n"(TB));
}

template <int TA, int TB> DEVI void wgmma_m64n96k16_ss(float (&d)[48], uint64_t descA, uint64_t descB, int scaleD) {
  asm volatile("{\n.reg .pred p;\nsetp.ne.b32 p, %50, 0;\nwgmma.mma_async.sync.aligned.m64n96k16.f32.bf16.bf16 {%0, %1, %2, %3, %4, %5, %6, %7, %8, %9, %10, %11, %12, %13, %14, %15, %16, %17, %18, %19, %20, %21, %22, %23, %24, %25, %26, %27, %28, %29, %30, %31, %32, %33, %34, %35, %36, %37, %38, %39, %40, %41, %42, %43, %44, %45, %46, %47}, %48, %49, p, 1, 1, %51, %52;\n}\n"
    : "+f"(d[0]), "+f"(d[1]), "+f"(d[2]), "+f"(d[3]), "+f"(d[4]), "+f"(d[5]), "+f"(d[6]), "+f"(d[7]), "+f"(d[8]), "+f"(d[9]), "+f"(d[10]), "+f"(d[11]), "+f"(d[12]), "+f"(d[13]), "+f"(d[14]), "+f"(d[15]), "+f"(d[16]), "+f"(d[17]), "+f"(d[18]), "+f"(d[19]), "+f"(d[20]), "+f"(d[21]), "+f"(d[22]), "+f"(d[23]), "+f"(d[24]), "+f"(d[25]), "+f"(d[26]), "+f"(d[27]), "+f"(d[28]), "+f"(d[29]), "+f"(d[30]), "+f"(d[31]), "+f"(d[32]), "+f"(d[33]), "+f"(d[34]), "+f"(d[35]), "+f"(d[36]), "+f"(d[37]), "+f"(d[38]), "+f"(d[39]), "+f"(d[40]), "+f"(d[41]), "+f"(d[42]), "+f"(d[43]), "+f"(d[44]), "+f"(d[45]), "+f"(d[46]), "+f"(d[47])
    : "l"(descA), "l"(descB), "r"(scaleD), "n"(TA), "n"(TB));
}

#define DEV_NB 7
#define DEV_D 6
#define DEV_WTMA 2
#define DEV_WOD 2000
#define DEV_PB 7
#define DEV_SEND 0
#define DEV_NV 2
#define DEV_BE 0
#define DEV_ONORM 0
#define DEV_GF 1
#define X_NOV 0
#define X_NOK 0
#define X_NOSH 0
#define X_NOMV 0
#define X_NOST 0
#define X_NOH 0
#define X_NOSTSM 0
#define DEV_ORD 0
#define DEV_HSUM 1
#define DEV_DEPH 24
#define DEV_PS 200
#define PWAIT mbar_wait_sleep
#define DEV_TURN 1
#define DEV_WG 1
#define DEV_GATE 0
#define HPOLL ld_acquire
#define DEV_GG 27
#define DEV_GI 0
#define DEV_NS 200

constexpr int kS = 112;
constexpr int kStripCtas = 112;
constexpr int kProjCtas = 20;
constexpr int kThreads = 512;
constexpr int kArr = 29;
constexpr int kExch = 27;
constexpr int kSteps = 28;
constexpr int kTiles = kSteps * 28;
constexpr int kOTileBytes = 64 * 192 * 2;
constexpr int kTailBands = DEV_NB;
constexpr int kTail0 = kSteps - kTailBands;
constexpr int kProjTiles = (kSteps - kTailBands) * 28;
constexpr int kHaloBytes = 3 * 784 - 16, kHaloPitch = 2432;

__device__ __align__(1024) uint8_t g_o[(size_t)kTiles * kOTileBytes];
__device__ __align__(1024) uint8_t g_halo[(size_t)kStripCtas * 2 * kExch * kHaloPitch];
__device__ __align__(1024) uint8_t g_wop[4 * 3 * 192 * 32];
__device__ uint32_t g_hflag[kStripCtas * 32];
__device__ uint32_t g_oflag[28 * 32];
__device__ uint32_t g_wflag[4 * 32];
__device__ uint32_t g_epoch[132 * 32];

namespace ka {
constexpr int kWAtom = 192 * 32;
constexpr int kWBytes = 9 * kWAtom;
constexpr int kXBytes = 64 * 384;
constexpr int kCol = 784;
constexpr int kQCol = 400;
constexpr int kSlot = 22 * kCol;
constexpr int kQSlot = 16 * kQCol;
constexpr int kQOff = 5 * kSlot + 32;
constexpr int kOffX = kWBytes;
constexpr int kOffRing = kOffX + 2 * kXBytes;
constexpr int kOffBar = kOffRing + kQOff + 6 * kQSlot;
constexpr int kOffStage = kOffX, kOffWo = kOffX + 2 * kWAtom;
constexpr int kOffDummy = kOffBar + 896;
DEVI uint32_t tail_buf(int i) { return i < 2 ? i * kOTileBytes : kOffRing + (i - 2) * 2 * kSlot; }
constexpr int kLastBytes = 3 * (16 + 2 * 15) * 128;
constexpr int kBarX = 0, kBarFull = 256, kBarO = 512, kBarT = 768, kBarJunk = 896;
constexpr int kSmemBytes = kOffBar + 896 + 704;
constexpr int kD = DEV_D;
static_assert(kD == 5 || kD == 6, "ring");
static_assert(kTailBands <= 8, "buffers");
constexpr int kNbInit = 0, kNbMisc = 1, kNbBurst = 2, kNbTile = 7, kNbFirst = 13, kNbX = 14;
}

namespace kb {
constexpr int kWoBlk = 192 * 128;
constexpr int kStages = 6;
constexpr int kOffA = 3 * kWoBlk;
constexpr int kOffBar = kOffA + kStages * kOTileBytes;
constexpr int kSmemBytes = kOffBar + 128;
}

constexpr int kSmemBytes = ka::kSmemBytes > kb::kSmemBytes ? ka::kSmemBytes : kb::kSmemBytes;
static_assert(kSmemBytes <= 232448, "smem");

#define TRACE(idx)
#define GT(i)
#define ATRACE(k)
#define TRBASE (sbase + kTraceOff)

DEVI void mbar_wait_sleep(uint32_t bar, uint32_t parity) {
  uint32_t it = 0;
  while (!mbar_test_wait(bar, parity)) {
    __nanosleep(DEV_NS);
    if (++it > LIMIT) { BAIL(bar & 0xfffff); break; }
  }
}

DEVI void publish_fence() {
  fence_proxy_async_global();
  fence_gpu();
}

DEVI uint32_t sched_fence() {
  uint32_t t;
  asm volatile("mov.u32 %0, %clock;" : "=r"(t)::"memory");
  return t;
}

struct AttnState {
  uint32_t kf[5][3][4];
  uint32_t vf[5][3][4];
  float bias[5][4];
  uint32_t p[5][2];
  uint32_t kaddr, vaddr, qaddr, bar, junk, fence;
  float sum0, sum1;
  uint32_t pm;
  uint32_t* optr;
};

DEVI void store_o(AttnState& s, float (&o)[3][4], float i0, float i1, int g) {
  if (g >= 0) {
#pragma unroll
    for (int mt = 0; mt < 3; mt++) {
      if (!X_NOST || o[mt][0] == 123.f) s.optr[(2 * mt) * 32] = pack_bf16(o[mt][0] * i0, o[mt][1] * i1);
      if (!X_NOST || o[mt][0] == 123.f) s.optr[(2 * mt + 1) * 32] = pack_bf16(o[mt][2] * i0, o[mt][3] * i1);
    }
  }
  __syncwarp();
  if ((s.pm & 64) && g >= (DEV_NV ? -1 : 0)) mbar_arrive(s.bar + ka::kBarO + 8 * g);
  s.optr += 28 * kOTileBytes / 4;
}

template <int PH>
DEVI void attn_step(AttnState& s, int g, int warp, const __nv_bfloat16* __restrict__ rpb) {
  using namespace ka;
  constexpr int R = (2 * PH) % 5, N0 = (R + 3) % 5, N1 = (R + 4) % 5;
  constexpr int SL = ((PH + 1) % 5) * kSlot;
  if (PH == 0 && g == 0) {
    {
      const int lane = threadIdx.x & 31, qc0 = 16 * ((blockIdx.x >> 2) % 7) + 2 * warp;
      const int kc = clampi(qc0 - 3, 0, kS - 8) + (lane >> 2);
      const unsigned short* r = reinterpret_cast<const unsigned short*>(rpb) + (blockIdx.x & 3) * 169 + (3 - (lane & 3)) * 13 + kc - qc0 + 6;
      const int sw0 = clampi(qc0 - 3, 0, kS - 7), sw1 = clampi(qc0 - 2, 0, kS - 7);
      const bool ok0 = kc >= sw0 && kc < sw0 + 7, ok1 = kc >= sw1 && kc < sw1 + 7;
#pragma unroll
      for (int i = 0; i < 10; i++) {
        const uint32_t v0 = ok0 ? (uint32_t)__ldg(r + i * 13) : 0xFF80u;
        const uint32_t v1 = ok1 ? (uint32_t)__ldg(r + i * 13 - 1) : 0xFF80u;
        s.bias[i >> 1][2 * (i & 1)] = __uint_as_float(v0 << 16) * 6.928203230275509f;
        s.bias[i >> 1][2 * (i & 1) + 1] = __uint_as_float(v1 << 16) * 6.928203230275509f;
      }
    }
    named_bar_sync(kNbMisc, 384);
    mbar_wait(s.bar + kBarFull, 0);
#pragma unroll
    for (int k = 0; k < 3; k++) {
      ldmatrix_x4(s.kf[1][k], s.kaddr + k * 32);
      ldmatrix_x4(s.kf[2][k], s.kaddr + 384 + k * 32);
      ldmatrix_x4_t(s.vf[1][k], s.vaddr + k * 32);
      ldmatrix_x4_t(s.vf[2][k], s.vaddr + 384 + k * 32);
      s.vf[0][k][0] = s.vf[0][k][1] = s.vf[0][k][2] = s.vf[0][k][3] = 0u;
    }
    named_bar_arrive(kNbFirst, 384);
  }
  if (PH < 3 || g >= 0) mbar_wait(s.bar + kBarFull + 8 * (g + 1), 0);
  if (DEV_DEPH && PH == DEV_DEPH % 5 && g == DEV_DEPH && warp >= 4) named_bar_sync(kNbInit, 256);
  ATRACE(0);
  float t[5][4], o[3][4], z[4];
  uint32_t q[6];
  const uint32_t ones[4] = {0x3F803F80u, s.kaddr, 0x3F803F80u, s.vaddr};
#define LDV(n) if (!X_NOV) ldmatrix_x4_t(s.vf[(n) < 3 ? N0 : N1][(n) % 3], s.vaddr + SL + ((n) / 3) * 384 + ((n) % 3) * 32);
#define LDK(n) if (!X_NOK) ldmatrix_x4(s.kf[(n) & 1 ? N1 : N0][(n) >> 1], s.kaddr + SL + ((n) & 1) * 384 + ((n) >> 1) * 32);
#define PV(i) { _Pragma("unroll") for (int mt = 0; mt < 3; mt++) { \
                  if ((i) == 0) mma16816_z(o[mt], s.vf[N0][mt], s.p[0][0], s.p[0][1]); \
                  else mma16816(o[mt], s.vf[(R + 3 + (i)) % 5][mt], s.p[i][0], s.p[i][1]); } \
                if (DEV_HSUM) { if ((i) == 0) mma16816_z(z, ones, s.p[0][0], s.p[0][1]); else mma16816(z, ones, s.p[i][0], s.p[i][1]); } }
#define QK(i, ks) { if ((ks) == 0) mma16816_c(t[i], s.kf[(R + (i)) % 5][0], q[0], q[1], s.bias[i]); \
                    else mma16816(t[i], s.kf[(R + (i)) % 5][ks], q[2 * (ks)], q[2 * (ks) + 1]); }
#define REL named_bar_arrive(kNbBurst + (PH + kD) % 5, 384);
  ldmatrix_x4(q[0], q[1], q[2], q[3], s.qaddr);
  ldmatrix_x2(q[4], q[5], s.qaddr + 64);
  uint32_t f0 = 0, f1, f2, f3 = 0;
  LDK(0) LDK(1) LDK(2) LDK(3) LDK(4) LDK(5)
  PV(0) PV(1) PV(2) PV(3) PV(4)
  f1 = sched_fence();
  s.junk ^= s.fence;
#pragma unroll
  for (int n = 5; n >= DEV_NV; n--) LDV(n)
#pragma unroll
  for (int n = 0; n < 15 - DEV_BE; n++) QK(n % 5, n / 5)
  f2 = sched_fence();
  REL
#pragma unroll
  for (int n = 15 - DEV_BE; n < 15; n++) QK(n % 5, n / 5)
  s.fence = sched_fence();
  if (DEV_DEPH && PH == DEV_DEPH % 5 && g == DEV_DEPH && warp < 4) named_bar_arrive(kNbInit, 256);
  ATRACE(1);
  uint32_t pm = s.pm;
  if (PH == 0 && g == 0) pm &= ~0x3Fu;
  if (PH == 2 && g == kSteps - 1) pm |= 0x3Fu;
  float x[7][2];
  sel2<1>(pm, x[0][0], x[0][1], t[0][0], t[0][1], t[3][2], t[3][3]);
  sel2<2>(pm, x[1][0], x[1][1], t[0][2], t[0][3], t[4][0], t[4][1]);
  sel2<4>(pm, x[2][0], x[2][1], t[1][0], t[1][1], t[4][2], t[4][3]);
#pragma unroll
  for (int e = 0; e < 2; e++) {
    x[3][e] = t[1][2 + e]; x[4][e] = t[2][e]; x[5][e] = t[2][2 + e]; x[6][e] = t[3][e];
  }
  float m0 = fmaxf(fmaxf(fmaxf(x[0][0], x[1][0]), fmaxf(x[2][0], x[3][0])), fmaxf(fmaxf(x[4][0], x[5][0]), x[6][0]));
  float m1 = fmaxf(fmaxf(fmaxf(x[0][1], x[1][1]), fmaxf(x[2][1], x[3][1])), fmaxf(fmaxf(x[4][1], x[5][1]), x[6][1]));
#pragma unroll
  for (int d = 4; d <= (X_NOSH ? 0 : 16); d <<= 1) {
    m0 = fmaxf(m0, __shfl_xor_sync(0xffffffffu, m0, d));
    m1 = fmaxf(m1, __shfl_xor_sync(0xffffffffu, m1, d));
    if (!DEV_HSUM) {
      s.sum0 += __shfl_xor_sync(0xffffffffu, s.sum0, d);
      s.sum1 += __shfl_xor_sync(0xffffffffu, s.sum1, d);
    }
  }
  if (!DEV_HSUM) { z[0] = s.sum0; z[1] = s.sum1; }
  uint32_t f4 = 0;
  if (DEV_NV > 0) {
    f4 = sched_fence();
#pragma unroll
    for (int n = 0; n < DEV_NV; n++) LDV(n)
  }
  const float c = 0.14433756729740643f * 1.4426950408889634f;
  const float n0 = -m0 * c, n1 = -m1 * c;
  uint32_t pt[7];
#pragma unroll
  for (int i = 0; i < 7; i++) {
    const float e0 = ex2(fmaf(x[i][0], c, n0)), e1 = ex2(fmaf(x[i][1], c, n1));
    if (!DEV_HSUM) {
      s.sum0 = i ? s.sum0 + e0 : e0;
      s.sum1 = i ? s.sum1 + e1 : e1;
    }
    pt[i] = X_NOMV ? pack_bf16(e0, e1) : movmatrix_t(pack_bf16(e0, e1));
  }
  split2<8>(pm, s.p[0][0], s.p[3][1], pt[0]);
  split2<16>(pm, s.p[0][1], s.p[4][0], pt[1]);
  split2<32>(pm, s.p[1][0], s.p[4][1], pt[2]);
  s.p[1][1] = pt[3]; s.p[2][0] = pt[4]; s.p[2][1] = pt[5]; s.p[3][0] = pt[6];
#pragma unroll
  for (int i = 0; i < 5; i++) asm volatile("" : "+r"(s.p[i][0]), "+r"(s.p[i][1])::"memory");
  if (!DEV_HSUM) asm volatile("" : "+f"(s.sum0), "+f"(s.sum1)::"memory");
  store_o(s, o, rcp_approx(z[0]), rcp_approx(z[1]), g - 1);
  s.junk ^= f0 ^ f1 ^ f2 ^ f3;
  s.fence ^= f4;
  s.qaddr += kQSlot;
  if (s.qaddr >= s.bar) s.qaddr -= 6 * kQSlot;
  asm volatile("" : "+r"(s.junk)::"memory");
  ATRACE(2);
}

__global__ void __launch_bounds__(kThreads, 1)
nat_kernel(const __nv_bfloat16* __restrict__ wqkv, const __nv_bfloat16* __restrict__ rpb,
           const __grid_constant__ CUtensorMap tm_x, const __grid_constant__ CUtensorMap tm_w,
           const __grid_constant__ CUtensorMap tm_h, const __grid_constant__ CUtensorMap tm_r,
           const __grid_constant__ CUtensorMap tm_wo, const __grid_constant__ CUtensorMap tm_out,
           const __grid_constant__ CUtensorMap tm_wo2, const __grid_constant__ CUtensorMap tm_o2) {
  extern __shared__ __align__(1024) uint8_t smem_raw[];
  const uint32_t sbase = smem_u32(smem_raw);
  if (sbase & 1023u) __trap();
  const int warp = __shfl_sync(0xffffffffu, (int)(threadIdx.x >> 5), 0), lane = threadIdx.x & 31;
  const int wg = warp >> 2, wl = warp & 3;
  const int cta = blockIdx.x;
  const bool strip_cta = cta < kStripCtas;
  const int head = cta & 3, ps = cta >> 2, par = ps / 7, strip = ps - 7 * par;
  if (threadIdx.x == 0) TRACE(0);

  if (strip_cta && threadIdx.x == 384) {
    using namespace ka;
    const uint32_t bar = sbase + kOffBar;
    mbar_init(bar + kBarX, 1);
    mbar_expect_tx(bar + kBarX, kXBytes + DEV_WTMA * 3 * kWAtom);
    tma_load_5d(sbase + kOffX, &tm_x, bar + kBarX, 0, 16 * strip, -1, 3 * (par & 1), par >> 1);
#pragma unroll
    for (int i = 9 - 3 * DEV_WTMA; i < 9; i++)
      tma_load_2d(sbase + i * kWAtom, &tm_w, bar + kBarX, (i / 3) * 192 + head * 48 + (i % 3) * 16, 0);
    TRACE(10);
  }
  __syncwarp();
  if (DEV_WTMA < 3 && strip_cta && wg == 2 && threadIdx.x < 256 + 96) {
    using namespace ka;
    constexpr int kSec = DEV_WTMA < 3 ? 3 - DEV_WTMA : 1;
    uint4 v[12 * kSec];
    const int wk = ((int)threadIdx.x - 256) / 6, wu = (int)threadIdx.x - 256 - 6 * wk;
    const uint8_t* src = reinterpret_cast<const uint8_t*>(wqkv) + wk * 1152 + head * 96 + wu * 16;
#pragma unroll
    for (int i = 0; i < 12 * kSec; i++) v[i] = ldg128(src + (i / kSec) * 16 * 1152 + (i % kSec) * 384);
    const uint32_t dst = sbase + (wu >> 1) * kWAtom + wk * 32 + (((wu ^ (wk >> 2)) & 1) << 4);
#pragma unroll
    for (int i = 0; i < 12 * kSec; i++) sts128(dst + (i / kSec) * 16 * 32 + (i % kSec) * 3 * kWAtom, v[i]);
    if (warp == 8) TRACE(6);
    fence_proxy_async();
  }
  if (threadIdx.x == 480) GT(0);

  if (strip_cta) {
    using namespace ka;
    const uint32_t bar = sbase + kOffBar, ring = sbase + kOffRing;
    if (wg < 2) {
      if (DEV_WG == 0) named_bar_arrive(kNbX, 416);
      reg_inc<184>();
      AttnState s;
      const int qc0 = 16 * strip + 2 * warp;
      const int kc0 = clampi(qc0 - 3, 0, kS - 8);
      const uint32_t colb = ring + (kc0 - (16 * strip - 3) + (lane & 7)) * kCol;
      s.kaddr = colb + ((lane >> 3) & 1) * 192 + (lane >> 4) * 16;
      s.vaddr = colb + 96 + (lane >> 4) * 192 + ((lane >> 3) & 1) * 16;
      {
        const int qr = (lane & 7) >> 1;
        const uint32_t qa = ring + kQOff + (2 * warp + (lane & 1)) * kQCol + (lane >> 3) * 16;
        s.qaddr = qa + (qr == 3 ? 5 * kQSlot : 4 * kQSlot + (qr + 1) * 96);
      }
      s.bar = bar;
      s.optr = reinterpret_cast<uint32_t*>(g_o + (size_t)(ps * 4 + head) * 6144 + warp * 768) + lane - 3 * 28 * kOTileBytes / 4;
#pragma unroll
      for (int i = 0; i < 5; i++) {
        s.p[i][0] = s.p[i][1] = 0u;
        s.bias[i][0] = s.bias[i][1] = s.bias[i][2] = s.bias[i][3] = 0.f;
#pragma unroll
        for (int k = 0; k < 3; k++)
#pragma unroll
          for (int c = 0; c < 4; c++) s.kf[i][k][c] = s.vf[i][k][c] = 0u;
      }
      s.junk = s.fence = 0;
      s.sum0 = s.sum1 = 1.f;
      s.pm = (7u << (lane & 3) & 7u) | ((7u << (lane >> 3) & 7u) << 3) | (lane == 0 ? 64u : 0u);
      s.pm = __shfl_sync(0xffffffffu, s.pm, lane);
#pragma unroll 1
      for (int g = -2; g < kSteps; g += 5) {
        attn_step<3>(s, g, warp, rpb);
        attn_step<4>(s, g + 1, warp, rpb);
        attn_step<0>(s, g + 2, warp, rpb);
        attn_step<1>(s, g + 3, warp, rpb);
        attn_step<2>(s, g + 4, warp, rpb);
      }
      {
        float o[3][4], z[4];
        const uint32_t ones[4] = {0x3F803F80u, s.kaddr, 0x3F803F80u, s.vaddr};
#pragma unroll
        for (int mt = 0; mt < 3; mt++) mma16816_z(o[mt], s.vf[4][mt], s.p[0][0], s.p[0][1]);
        mma16816_z(z, ones, s.p[0][0], s.p[0][1]);
#pragma unroll
        for (int i = 1; i < 5; i++) {
#pragma unroll
          for (int mt = 0; mt < 3; mt++) mma16816(o[mt], s.vf[i - 1][mt], s.p[i][0], s.p[i][1]);
          mma16816(z, ones, s.p[i][0], s.p[i][1]);
        }
        store_o(s, o, rcp_approx(z[0]), rcp_approx(z[1]), kSteps - 1);
      }
      s.junk ^= s.fence;
      if (s.junk == 0x9e3779b9u) sts32(bar + kBarJunk, 0);
      if (warp == 0) TRACE(1);
      if (threadIdx.x == 128) GT(3);
    } else if (wg == 2) {
      reg_dec<104>();
      const int col = ((lane >> 3) & 1) * 8 + (lane & 7);
      uint32_t kva = ring + (3 + col) * kCol + wl * 192 + (lane >> 4) * 16;
      uint32_t qa = ring + kQOff + col * kQCol + wl * 96 + (lane >> 4) * 16;
      const uint32_t alo = (uint32_t)make_desc(sbase + kOffX, 16, 1024, 1), blo = (uint32_t)make_desc(sbase, kWAtom, 256, 3);
      constexpr uint32_t ahi = (1u << 30) | (1024 >> 4), bhi = (3u << 30) | (256 >> 4);
      if (wl == 0) TRACE(2);
      uint32_t gj = 0;
      int bid = kNbBurst, tid = kNbTile;
      named_bar_arrive(kNbBurst + (kD - 2) % 5, 384);
      named_bar_arrive(kNbBurst + (kD - 1) % 5, 384);
      named_bar_sync(kNbX, DEV_WG ? 160 : 416);
      if (wl == 0) TRACE(7);
      mbar_wait(bar + kBarX, 0);
      if (wl == 0) TRACE(16 + 0);
#pragma unroll 1
      for (int a = 0; a < kArr; a++) {
        float acc[72];
        const uint32_t al = alo + (a & 1) * (kXBytes >> 4);
        if (a >= kD) named_bar_sync(bid, 384);
        if (wl == 0) TRACE(16 + a * 4 + 1);
        wg_fence();
#pragma unroll
        for (int k = 0; k < 12; k++)
          wgmma_m64n144k16_ss<0, 1>(acc, desc64(al + (((k >> 2) * 8192 + (k & 3) * 32) >> 4), ahi), desc64(blo + k * 32, bhi), k != 0);
        wg_commit();
        if (DEV_GF) gj ^= sched_fence();
        bid = bid == kNbBurst + 4 ? kNbBurst : bid + 1;
        if (a == 0) named_bar_sync(kNbInit, 256);
        const bool xok = mbar_test_wait(bar + kBarX + 8 * (a + 1), 0);
        if (a == kArr - 1 && wl != 0) {
          const int r = col / 3, c = col - 3 * r;
          qa = sbase + kOffDummy + lane * 16;
          kva = col < 15 && wl < 3 ? ring + ((kExch + (r >> 2)) % 5) * kSlot + ((wl - 1) * 19 + c) * kCol + (r & 3) * 192 + (lane >> 4) * 16
                                   : qa;
        }
        wg_wait<0>();
        fence_regs(acc);
        named_bar_arrive(kNbX + (a & 1), 160);
        if (kD == 6 && a == 5) named_bar_sync(kNbFirst, 384);
        if (DEV_NV && a >= 6) mbar_wait(bar + kBarO + 8 * (a - 7), 0);
        if (wl == 0) TRACE(16 + a * 4 + 2);
#pragma unroll
        for (int jp = 0; jp < 9; jp++) {
          const int j = jp < 6 ? jp + 3 : jp - 6;
          if (!X_NOSTSM || acc[8 * j] == 123.f) stmatrix_x4(j < 3 ? qa + j * 32 : kva + (j - 3) * 32, pack_bf16(acc[8 * j + 0], acc[8 * j + 1]),
                      pack_bf16(acc[8 * j + 2], acc[8 * j + 3]), pack_bf16(acc[8 * j + 4], acc[8 * j + 5]),
                      pack_bf16(acc[8 * j + 6], acc[8 * j + 7]));
        }
        if (a < kExch) named_bar_arrive(tid, 160);
        tid = tid == kNbTile + 5 ? kNbTile : tid + 1;
        if (wl == 0) TRACE(16 + a * 4 + 3);
        if (!xok && a + 1 < kArr) mbar_wait(bar + kBarX + 8 * (a + 1), 0);
        if (wl == 0) TRACE(16 + (a + 1) * 4 + 0);
        kva += kSlot;
        if (kva >= ring + 5 * kSlot) kva -= 5 * kSlot;
        qa += kQSlot;
        if (qa >= bar) qa -= 6 * kQSlot;
      }
      __syncwarp();
      if (lane < kArr - kExch) mbar_arrive(bar + kBarFull + 8 * (kExch + lane));
      if (gj == 0x9e3779b9u) sts32(bar + kBarJunk, 0);
      if (kD == 5) named_bar_arrive(kNbFirst, 384);
#pragma unroll 1
      for (int g = kArr - kD; g < kSteps; g++) {
        if (g != DEV_GG) named_bar_arrive(bid, 384);
        bid = bid == kNbBurst + 4 ? kNbBurst : bid + 1;
      }
      {
        const uint32_t wlo = (uint32_t)make_desc(sbase + kOffWo, kWAtom, 256, 3);
        const int n = lane & 7, j = 2 * wl + ((lane >> 3) & 1);
        const uint32_t sta = sbase + kOffStage + ((2 * j + (n & 1)) * 4 + (n >> 1)) * 96 + (lane >> 4) * 16;
        mbar_wait(bar + kBarX + 8 * kArr, 0);
#pragma unroll 1
        for (int g = kTail0 + ((kTail0 ^ (head >> 1)) & 1), i = 0; g < kSteps; g += 2, i++) {
          float acc[48];
          if (DEV_GG && i == DEV_GI) named_bar_sync(kNbBurst + (DEV_GG + kD) % 5, 384);
          mbar_wait(bar + kBarT + 8 * i, 0);
          if (wl == 0) TRACE(144 + i * 2);
          const uint32_t tlo = (uint32_t)make_desc(sbase + tail_buf(i), 128, 768, 0);
          wg_fence();
#pragma unroll
          for (int k = 0; k < 12; k++)
            wgmma_m64n96k16_ss<1, 1>(acc, desc64(tlo + (((k / 3) * 6144 + (k % 3) * 256) >> 4), 768 >> 4), desc64(wlo + k * 32, bhi), k != 0);
          wg_commit();
          if (threadIdx.x == 256) bulk_wait_read();
          named_bar_sync(kNbMisc, 128);
          wg_wait<0>();
          fence_regs(acc);
#pragma unroll
          for (int jp = 0; jp < 6; jp++)
            stmatrix_x4(sta + (jp / 3) * kWAtom + (jp % 3) * 32, pack_bf16(acc[8 * jp + 0], acc[8 * jp + 1]),
                        pack_bf16(acc[8 * jp + 2], acc[8 * jp + 3]), pack_bf16(acc[8 * jp + 4], acc[8 * jp + 5]),
                        pack_bf16(acc[8 * jp + 6], acc[8 * jp + 7]));
          fence_proxy_async();
          named_bar_sync(kNbMisc, 128);
          if (threadIdx.x == 256) {
            tma_store_5d(&tm_out, sbase + kOffStage, (head & 1) * 96, 4 * g, 16 * strip, par & 1, par >> 1);
            tma_store_5d(&tm_out, sbase + kOffStage + kWAtom, (head & 1) * 96 + 48, 4 * g, 16 * strip, par & 1, par >> 1);
            bulk_commit();
          }
          __syncwarp();
          if (wl == 0) TRACE(145 + i * 2);
        }
        if (threadIdx.x == 256) {
          bulk_wait<0>();
          GT(2);
        }
      }
    } else {
      reg_dec<40>();
      if (wl == 0) named_bar_arrive(kNbX, DEV_WG ? 160 : 416);
      if (lane == 0) {
        const uint32_t b0 = bar + 64 * wl;
        if (wl == 1 && head == 1) tma_prefetch_5d(&tm_x, 0, 16 * strip, 3, 3 * (par & 1), par >> 1);
#pragma unroll
        for (int i = 0; i < 64; i += 8) {
          if (i || wl) mbar_init(b0 + kBarX + i, 1);
          mbar_init(b0 + kBarFull + i, wl < 3 || i < 8 * (kExch - 24) ? 2 : (i == 56 ? 8 : 4));
          mbar_init(b0 + kBarO + i, 8);
          if (wl == 0 && i < 32) mbar_init(b0 + kBarT + i, 1);
        }
#pragma unroll
        for (int i = 0; i < 64; i += 8) {
          if (i || wl)
            mbar_expect_tx(b0 + kBarX + i, wl < 3 || i < 32 ? kXBytes : (i == 32 ? kLastBytes : 6 * kWAtom));
          if (wl == 0 && i < 32) mbar_expect_tx(bar + kBarT + i, kOTileBytes);
        }
        fence_mbar_init();
        if (wl == 0) {
          tma_load_5d(sbase + kOffX + kXBytes, &tm_x, bar + kBarX + 8, 0, 16 * strip, 3, 3 * (par & 1), par >> 1);
          tma_prefetch_5d(&tm_x, 0, 16 * strip, 4 * (2 + ((head - 2) & 3)) - 1, 3 * (par & 1), par >> 1);
          TRACE(5);
        }
      }
      __syncwarp();
      const uint32_t ep = ld_relaxed(&g_epoch[cta * 32 + wl]) * 32u;
      named_bar_arrive(kNbMisc, 384);
      named_bar_sync(kNbInit, 256);
      if (wl == 0) {
#pragma unroll 1
        for (int a = 2; a < kArr - 1; a++) {
          named_bar_sync(kNbX + (a & 1), 160);
          if (lane == 0) {
            tma_load_5d(sbase + kOffX + (a & 1) * kXBytes, &tm_x, bar + kBarX + 8 * a, 0, 16 * strip, 4 * a - 1,
                        3 * (par & 1), par >> 1);
            const int ap = a + 4;
            if (ap < kArr && (ap & 3) == head) tma_prefetch_5d(&tm_x, 0, 16 * strip, 4 * ap - 1, 3 * (par & 1), par >> 1);
          }
          __syncwarp();
        }
        named_bar_sync(kNbX, 160);
        if (lane < 9) {
          const int kb = lane / 3, w = lane - 3 * kb;
          tma_load_5d(sbase + kOffX + kb * 8192 + w * 2048, w == 0 ? &tm_r : &tm_h, bar + kBarX + 8 * (kArr - 1), 0,
                      16 * strip + (w == 0 ? 0 : (w == 1 ? -3 : 16)), w == 0 ? kS - 1 : 4 * kExch - 1, 3 * (par & 1) + kb, par >> 1);
        }
        {
          uint32_t it = 0;
          while (!__all_sync(0xffffffffu, (int)(ld_acquire(&g_wflag[(lane & 3) * 32]) - (ep + 1)) >= 0))
            if (++it > LIMIT) { BAIL(0x5000000); break; }
        }
        const uint8_t* wsrc = g_wop + (head & 1) * 6 * kWAtom;
        named_bar_sync(kNbX + 1, 160);
        if (lane == 0) bulk_load(sbase + kOffWo + 2 * kWAtom, wsrc + 2 * kWAtom, 4 * kWAtom, bar + kBarX + 8 * kArr);
        uint32_t seen = ld_acquire(&g_oflag[ps * 32 + (lane & 3)]);
        named_bar_sync(kNbX, 160);
        if (lane == 0) bulk_load(sbase + kOffWo, wsrc, 2 * kWAtom, bar + kBarX + 8 * kArr);
#pragma unroll 1
        for (int g = kTail0 + ((kTail0 ^ (head >> 1)) & 1), i = 0; g < kSteps; g += 2, i++) {
          uint32_t it = 0;
          while (!__all_sync(0xffffffffu, (int)(seen - (ep + g + 1)) >= 0)) {
            seen = ld_acquire(&g_oflag[ps * 32 + (lane & 3)]);
            if (++it > LIMIT) { BAIL(0x3000000 + g); break; }
          }
          if (lane == 0)
            bulk_load(sbase + tail_buf(i), g_o + (size_t)(g * 28 + ps) * kOTileBytes, kOTileBytes, bar + kBarT + 8 * i);
          __syncwarp();
        }
      } else {
        const int p = wl - 1;
        const bool on = !X_NOH && (lane == 0 ? strip > 0 : strip < 6);
        const int nb = on ? cta + (lane == 0 ? -4 : 4) : cta;
        const uint32_t bytes = X_NOH ? 0 : ((strip > 0 && strip < 6) ? 2 * kHaloBytes : kHaloBytes);
        int slot = p, g = 0;
#pragma unroll 1
        for (int a = p; a < kExch; a += 3) {
          named_bar_sync(kNbTile + a % 6, 160);
          const uint32_t sl = ring + slot * kSlot;
          if (lane < 2) {
            fence_proxy_async();
            if (on) bulk_store(g_halo + (size_t)((cta * 2 + lane) * kExch + a) * kHaloPitch, sl + (3 + 13 * lane) * kCol, kHaloBytes);
            bulk_commit();
          }
          __syncwarp();
          g += __ffs(~__ballot_sync(0xffffffffu, lane < 4 && mbar_test_wait(bar + kBarO + 8 * (g + lane), 0))) - 1;
          __syncwarp();
          if (lane < 2) {
            bulk_wait<0>();
            if (lane == 0) mbar_expect_tx(bar + kBarFull + 8 * a, bytes);
            else mbar_arrive(bar + kBarFull + 8 * a);
            TRACE(160 + a * 4 + 0);
            publish_fence();
            st_relaxed(&g_hflag[cta * 32 + 4 * lane + p], ep + a + 1);
            if (lane == 0 && g) red_max(&g_oflag[ps * 32 + head], ep + g);
            TRACE(160 + a * 4 + 1);
            uint32_t it = 0;
            while (true) {
              const bool ok = !on || (int)(HPOLL(&g_hflag[nb * 32 + 4 * (lane ^ 1) + p]) - (ep + a + 1)) >= 0;
              if (__all_sync(3u, ok)) break;
              if (++it > LIMIT) { BAIL(0x1000000 + a); break; }
            }
            TRACE(160 + a * 4 + 2);
            if (on) bulk_load(sl + lane * 19 * kCol, g_halo + (size_t)((nb * 2 + (lane ^ 1)) * kExch + a) * kHaloPitch, kHaloBytes,
                              bar + kBarFull + 8 * a);
            TRACE(160 + a * 4 + 3);
          }
          __syncwarp();
          slot = slot >= 2 ? slot - 2 : slot + 3;
        }
        if (lane == 0) {
#pragma unroll 1
          for (g = kSteps - DEV_PB + p; g < kSteps; g += 3) {
            if (g < kSteps - 3) mbar_wait_sleep(bar + kBarO + 8 * g, 0);
            else mbar_wait(bar + kBarO + 8 * g, 0);
            TRACE(370 + g * 2);
            publish_fence();
            red_max(&g_oflag[ps * 32 + head], ep + g + 1);
            TRACE(371 + g * 2);
          }
          if (p == (DEV_PB - 1) % 3) GT(1);
        }
      }
      __syncwarp();
      if (lane == 0) st_relaxed(&g_epoch[cta * 32 + wl], (ep >> 5) + 1);
    }
  } else {
    using namespace kb;
    const uint32_t bar = sbase + kOffBar, sA = sbase + kOffA;
    const int k = cta - kStripCtas;
    if (wg < 3) {
      reg_inc<160>();
      named_bar_sync(0, 512);
      uint32_t wf[12][4];
      mbar_wait(bar + 56, 0);
      {
        const int kr = (lane & 7) + ((lane >> 4) << 3);
        const uint32_t wa = sbase + wg * kWoBlk + kr * 128 + (((2 * wl + ((lane >> 3) & 1)) ^ (lane & 7)) << 4);
#pragma unroll
        for (int kk = 0; kk < 12; kk++) ldmatrix_x4_t(wf[kk], wa + kk * 2048);
      }
      named_bar_sync(3 + wg, 128);
      const int px = (2 * (lane >> 4) + (lane & 1)) * 4 + ((lane & 7) >> 1);
      const uint32_t sto = sbase + wg * kWoBlk + px * 128 + (((2 * wl + ((lane >> 3) & 1)) ^ (px & 7)) << 4);
      int st = 0, sb = 0;
      uint32_t ph = 0;
      uint32_t pk[16];
#pragma unroll
      for (int i = 0; i < 16; i++) pk[i] = 0u;
      auto store = [&](int tq) {
        const int g = tq / 28, tp = tq - 28 * g, tpar = tp / 7, tstrip = tp - 7 * tpar;
#pragma unroll
        for (int jp = 0; jp < 4; jp++)
          stmatrix_x4_t(sto + sb * 8192 + jp * 2048, pk[4 * jp], pk[4 * jp + 1], pk[4 * jp + 2], pk[4 * jp + 3]);
        fence_proxy_async();
        if (wl == 0 && lane == 0) bulk_wait_read1();
        named_bar_sync(3 + wg, 128);
        if (wl == 0 && lane == 0 && tq >= 0) {
          tma_store_5d(&tm_o2, sbase + wg * kWoBlk + sb * 8192, 0, 4 * g, 16 * tstrip, 3 * (tpar & 1) + wg, tpar >> 1);
          bulk_commit();
        }
        __syncwarp();
        sb = sb == 2 ? 0 : sb + 1;
      };
      int t = k;
#pragma unroll 1
      for (; t < kProjTiles; t += kProjCtas) {
        float acc[32];
        PWAIT(bar + 8 * st, ph);
        if (warp == 0) TRACE(16 + (t / kProjCtas) * 4 + 1);
        const uint32_t blo = (uint32_t)make_desc(sA + st * kOTileBytes, 128, 768, 0);
        if (DEV_TURN && (t > k || wg)) named_bar_sync(6 + wg, 256);
        wg_fence();
#pragma unroll
        for (int kk = 0; kk < 12; kk++)
          wgmma_m64n64k16_rs<1>(acc, wf[kk][0], wf[kk][1], wf[kk][2], wf[kk][3],
                                desc64(blo + (((kk / 3) * 6144 + (kk % 3) * 256) >> 4), 768 >> 4), kk != 0);
        wg_commit();
        if (DEV_TURN && (wg < 2 || t + kProjCtas < kProjTiles)) named_bar_arrive(6 + (wg == 2 ? 0 : wg + 1), 256);
        store(t - kProjCtas);
        if (warp == 0) TRACE(12 + (t / kProjCtas) * 4 + 3);
        wg_wait<0>();
        fence_regs(acc);
        if (lane == 0) mbar_arrive(bar + 64 + 8 * st);
        if (warp == 0) TRACE(16 + (t / kProjCtas) * 4 + 2);
#pragma unroll
        for (int i = 0; i < 16; i++) pk[i] = pack_bf16(acc[2 * i], acc[2 * i + 1]);
        if (++st == kStages) { st = 0; ph ^= 1; }
      }
      store(t - kProjCtas);
      if (warp == 0) TRACE(12 + (t / kProjCtas) * 4 + 3);
      if (wl == 0 && lane == 0) bulk_wait<0>();
      if (threadIdx.x == 0) GT(1);
    } else {
      reg_dec<32>();
      if (lane == 0) {
        mbar_init(bar + 16 * wl, 1);
        mbar_init(bar + 16 * wl + 8, 1);
        mbar_init(bar + 64 + 16 * wl, 12);
        mbar_init(bar + 64 + 16 * wl + 8, 12);
        fence_mbar_init();
      }
      __syncwarp();
      named_bar_sync(0, 512);
      if (wl == 3 && lane == 0) {
        if (DEV_WOD) __nanosleep(DEV_WOD);
        mbar_expect_tx(bar + 56, 3 * kWoBlk);
#pragma unroll 1
        for (int i = 0; i < 3; i++) tma_load_2d(sbase + i * kWoBlk, &tm_wo2, bar + 56, i * 64, 0);
      }
      __syncwarp();
      if (wl == 3 && k < 4) {
        if (lane == 0) {
          const uint32_t e0 = ld_relaxed(&g_epoch[cta * 32 + 3]);
          const uint32_t stg = sA + (kStages - 1) * kOTileBytes;
          mbar_expect_tx(bar + 48, 3 * ka::kWAtom);
#pragma unroll 1
          for (int i = 0; i < 3; i++) tma_load_2d(stg + i * ka::kWAtom, &tm_wo, bar + 48, k * 48 + i * 16, 0);
          mbar_wait(bar + 48, 0);
          bulk_store(g_wop + k * 3 * ka::kWAtom, stg, 3 * ka::kWAtom);
          bulk_commit();
          bulk_wait<0>();
          publish_fence();
          st_relaxed(&g_wflag[k * 32], e0 * 32u + 1);
          st_relaxed(&g_epoch[cta * 32 + 3], e0 + 1);
        }
        __syncwarp();
        named_bar_arrive(2, 64);
      }
      if (wl == 2 && k < 4) named_bar_sync(2, 64);
      if (wl < 3 && lane < 4) {
        const uint32_t e0 = ld_relaxed(&g_epoch[cta * 32 + wl]);
#pragma unroll 1
        for (int it = wl;; it += 3) {
          const int t = k + it * kProjCtas;
          if (t >= kProjTiles) break;
          const int st = it % kStages;
          const int g = t / 28, tp = t - 28 * g;
          uint32_t sp = 0;
          while (true) {
            const bool ok = (int)(ld_acquire(&g_oflag[tp * 32 + lane]) - (e0 * 32u + g + 1)) >= 0;
            if (__all_sync(15u, ok)) break;
            if (DEV_PS) __nanosleep(DEV_PS);
            if (++sp > LIMIT) { BAIL(0x2000000 + t); break; }
          }
          if (it >= kStages) mbar_wait(bar + 64 + 8 * st, ((it / kStages) & 1) ^ 1);
          TRACE(16 + it * 4 + 0);
          if (lane == 0) {
            mbar_expect_tx(bar + 8 * st, kOTileBytes);
            bulk_load(sA + st * kOTileBytes, g_o + (size_t)t * kOTileBytes, kOTileBytes, bar + 8 * st);
          }
          __syncwarp(15u);
        }
        if (lane == 0) st_relaxed(&g_epoch[cta * 32 + wl], e0 + 1);
      }
    }
  }
}

}

namespace {

typedef CUresult (*EncodeTiledFn)(CUtensorMap*, CUtensorMapDataType, cuuint32_t, void*, const cuuint64_t*,
                                  const cuuint64_t*, const cuuint32_t*, const cuuint32_t*, CUtensorMapInterleave,
                                  CUtensorMapSwizzle, CUtensorMapL2promotion, CUtensorMapFloatOOBfill);

EncodeTiledFn get_encode_fn() {
  static EncodeTiledFn fn = nullptr;
  if (!fn) {
    void* p = nullptr;
    cudaDriverEntryPointQueryResult qres;
    if (cudaGetDriverEntryPoint("cuTensorMapEncodeTiled", &p, cudaEnableDefault, &qres) == cudaSuccess)
      fn = reinterpret_cast<EncodeTiledFn>(p);
  }
  return fn;
}

CUtensorMap make_map(void* base, int rank, const cuuint64_t* dims, const cuuint64_t* strides, const cuuint32_t* box,
                     CUtensorMapSwizzle swz) {
  CUtensorMap m;
  cuuint32_t es[5] = {1, 1, 1, 1, 1};
  get_encode_fn()(&m, CU_TENSOR_MAP_DATA_TYPE_BFLOAT16, (cuuint32_t)rank, base, dims, strides, box, es,
                  CU_TENSOR_MAP_INTERLEAVE_NONE, swz, CU_TENSOR_MAP_L2_PROMOTION_L2_128B,
                  CU_TENSOR_MAP_FLOAT_OOB_FILL_NONE);
  return m;
}

}

extern "C" void kernel_launch(void* const* d_in, const int* in_sizes, int n_in, void* d_out, int out_size) {
  using namespace nat;
  (void)in_sizes; (void)n_in; (void)out_size;
  const __nv_bfloat16* x = (const __nv_bfloat16*)d_in[0];
  const __nv_bfloat16* wqkv = (const __nv_bfloat16*)d_in[1];
  const __nv_bfloat16* wo = (const __nv_bfloat16*)d_in[2];
  const __nv_bfloat16* rpb = (const __nv_bfloat16*)d_in[3];
  __nv_bfloat16* out = (__nv_bfloat16*)d_out;

  CUtensorMap tm_x, tm_h, tm_r, tm_w, tm_wo, tm_out, tm_wo2, tm_o2;
  {
    cuuint64_t dims[5] = {64, 112, 112, 6, 2};
    cuuint64_t str[4] = {768, 2ull * 224 * 384, 128, 224ull * 384};
    cuuint32_t box[5] = {64, 16, 4, 3, 1};
    tm_x = make_map((void*)x, 5, dims, str, box, CU_TENSOR_MAP_SWIZZLE_128B);
    cuuint32_t boxh[5] = {64, 3, 5, 1, 1}, boxr[5] = {64, 16, 1, 1, 1};
    tm_h = make_map((void*)x, 5, dims, str, boxh, CU_TENSOR_MAP_SWIZZLE_128B);
    tm_r = make_map((void*)x, 5, dims, str, boxr, CU_TENSOR_MAP_SWIZZLE_128B);
  }
  {
    cuuint64_t dims[2] = {576, 192};
    cuuint64_t str[1] = {1152};
    cuuint32_t box[2] = {16, 192};
    tm_w = make_map((void*)wqkv, 2, dims, str, box, CU_TENSOR_MAP_SWIZZLE_32B);
  }
  {
    cuuint64_t dims[2] = {192, 192};
    cuuint64_t str[1] = {384};
    cuuint32_t box[2] = {16, 192};
    tm_wo = make_map((void*)wo, 2, dims, str, box, CU_TENSOR_MAP_SWIZZLE_32B);
    cuuint32_t box2[2] = {64, 192};
    tm_wo2 = make_map((void*)wo, 2, dims, str, box2, CU_TENSOR_MAP_SWIZZLE_128B);
  }
  {
    cuuint64_t dims[5] = {192, 112, 112, 2, 2};
    cuuint64_t str[4] = {2ull * 224 * 384, 768, 384, 224ull * 384};
    cuuint32_t box[5] = {48, 4, 16, 1, 1};
    tm_out = make_map((void*)out, 5, dims, str, box, CU_TENSOR_MAP_SWIZZLE_NONE);
  }
  {
    cuuint64_t dims[5] = {64, 112, 112, 6, 2};
    cuuint64_t str[4] = {2ull * 224 * 384, 768, 128, 224ull * 384};
    cuuint32_t box[5] = {64, 4, 16, 1, 1};
    tm_o2 = make_map((void*)out, 5, dims, str, box, CU_TENSOR_MAP_SWIZZLE_128B);
  }
  cudaFuncSetAttribute(nat_kernel, cudaFuncAttributeMaxDynamicSharedMemorySize, kSmemBytes);
  nat_kernel<<<kStripCtas + kProjCtas, kThreads, kSmemBytes>>>(wqkv, rpb, tm_x, tm_w, tm_h, tm_r, tm_wo, tm_out, tm_wo2, tm_o2);
}
```

```cpp
#include <cuda_runtime.h>
#include <cuda_bf16.h>
#include <cuda.h>
#include <stdint.h>

#define DEVI __device__ __forceinline__

namespace nat {

DEVI uint32_t smem_u32(const void* p) { return (uint32_t)__cvta_generic_to_shared(p); }

DEVI void mbar_init(uint32_t bar, uint32_t count) {
  asm volatile("mbarrier.init.shared::cta.b64 [%0], %1;" ::"r"(bar), "r"(count) : "memory");
}
DEVI void mbar_expect_tx(uint32_t bar, uint32_t bytes) {
  asm volatile("mbarrier.arrive.expect_tx.shared::cta.b64 _, [%0], %1;" ::"r"(bar), "r"(bytes) : "memory");
}
DEVI void mbar_arrive(uint32_t bar) {
  asm volatile("mbarrier.arrive.shared::cta.b64 _, [%0];" ::"r"(bar) : "memory");
}
DEVI bool mbar_try_wait(uint32_t bar, uint32_t parity) {
  uint32_t ok;
  asm volatile(
      "{\n.reg .pred p;\nmbarrier.try_wait.parity.shared::cta.b64 p, [%1], %2;\nselp.u32 %0, 1, 0, p;\n}\n"
      : "=r"(ok)
      : "r"(bar), "r"(parity)
      : "memory");
  return ok != 0;
}
DEVI bool mbar_test_wait(uint32_t bar, uint32_t parity) {
  uint32_t ok;
  asm volatile(
      "{\n.reg .pred p;\nmbarrier.test_wait.parity.shared::cta.b64 p, [%1], %2;\nselp.u32 %0, 1, 0, p;\n}\n"
      : "=r"(ok)
      : "r"(bar), "r"(parity)
      : "memory");
  return ok != 0;
}
#define BAIL(code) __trap()
#define LIMIT (1u << 20)
DEVI void mbar_wait(uint32_t bar, uint32_t parity) {
  uint32_t it = 0;
  while (!mbar_try_wait(bar, parity)) {
    if (++it > LIMIT) { BAIL(bar & 0xfffff); break; }
  }
}
DEVI void fence_mbar_init() { asm volatile("fence.mbarrier_init.release.cluster;" ::: "memory"); }

DEVI void tma_load_2d(uint32_t dst, const CUtensorMap* tm, uint32_t bar, int c0, int c1) {
  asm volatile(
      "cp.async.bulk.tensor.2d.shared::cluster.global.mbarrier::complete_tx::bytes [%0], [%1, {%3, %4}], [%2];"
      ::"r"(dst), "l"(tm), "r"(bar), "r"(c0), "r"(c1)
      : "memory");
}
DEVI void tma_store_5d(const CUtensorMap* tm, uint32_t src, int c0, int c1, int c2, int c3, int c4) {
  asm volatile("cp.async.bulk.tensor.5d.global.shared::cta.bulk_group [%0, {%2, %3, %4, %5, %6}], [%1];"
               ::"l"(tm), "r"(src), "r"(c0), "r"(c1), "r"(c2), "r"(c3), "r"(c4)
               : "memory");
}
DEVI void bulk_wait_read1() { asm volatile("cp.async.bulk.wait_group.read 1;" ::: "memory"); }
DEVI void bulk_wait_read() { asm volatile("cp.async.bulk.wait_group.read 0;" ::: "memory"); }
DEVI void tma_load_4d(uint32_t dst, const CUtensorMap* tm, uint32_t bar, int c0, int c1, int c2, int c3) {
  asm volatile(
      "cp.async.bulk.tensor.4d.shared::cluster.global.mbarrier::complete_tx::bytes [%0], [%1, {%3, %4, %5, %6}], [%2];"
      ::"r"(dst), "l"(tm), "r"(bar), "r"(c0), "r"(c1), "r"(c2), "r"(c3)
      : "memory");
}
DEVI void tma_load_5d(uint32_t dst, const CUtensorMap* tm, uint32_t bar, int c0, int c1, int c2, int c3, int c4) {
  asm volatile(
      "cp.async.bulk.tensor.5d.shared::cluster.global.mbarrier::complete_tx::bytes [%0], [%1, {%3, %4, %5, %6, %7}], [%2];"
      ::"r"(dst), "l"(tm), "r"(bar), "r"(c0), "r"(c1), "r"(c2), "r"(c3), "r"(c4)
      : "memory");
}
DEVI void tma_load_5d_mc(uint32_t dst, const CUtensorMap* tm, uint32_t bar, int c0, int c1, int c2, int c3, int c4, uint16_t mask) {
  asm volatile(
      "cp.async.bulk.tensor.5d.shared::cluster.global.mbarrier::complete_tx::bytes.multicast::cluster [%0], [%1, {%3, %4, %5, %6, %7}], [%2], %8;"
      ::"r"(dst), "l"(tm), "r"(bar), "r"(c0), "r"(c1), "r"(c2), "r"(c3), "r"(c4), "h"(mask)
      : "memory");
}
DEVI uint32_t mapa(uint32_t addr, uint32_t rank) {
  uint32_t r;
  asm("mapa.shared::cluster.u32 %0, %1, %2;" : "=r"(r) : "r"(addr), "r"(rank));
  return r;
}
DEVI void mbar_arrive_cluster(uint32_t cluster_bar) {
  asm volatile("mbarrier.arrive.shared::cluster.b64 _, [%0];" ::"r"(cluster_bar) : "memory");
}
DEVI void cluster_arrive_relaxed() { asm volatile("barrier.cluster.arrive.relaxed.aligned;" ::: "memory"); }
DEVI void cluster_wait() { asm volatile("barrier.cluster.wait.aligned;" ::: "memory"); }
DEVI void tma_prefetch_5d(const CUtensorMap* tm, int c0, int c1, int c2, int c3, int c4) {
  asm volatile("cp.async.bulk.prefetch.tensor.5d.L2.global [%0, {%1, %2, %3, %4, %5}];"
               ::"l"(tm), "r"(c0), "r"(c1), "r"(c2), "r"(c3), "r"(c4)
               : "memory");
}
DEVI void bulk_load(uint32_t dst, const void* src, uint32_t bytes, uint32_t bar) {
  asm volatile("cp.async.bulk.shared::cluster.global.mbarrier::complete_tx::bytes [%0], [%1], %2, [%3];"
               ::"r"(dst), "l"(src), "r"(bytes), "r"(bar) : "memory");
}
DEVI void bulk_store(void* dst, uint32_t src, uint32_t bytes) {
  asm volatile("cp.async.bulk.global.shared::cta.bulk_group [%0], [%1], %2;" ::"l"(dst), "r"(src), "r"(bytes) : "memory");
}
DEVI void bulk_commit() { asm volatile("cp.async.bulk.commit_group;" ::: "memory"); }
template <int N>
DEVI void bulk_wait() { asm volatile("cp.async.bulk.wait_group %0;" ::"n"(N) : "memory"); }

template <int N>
DEVI void reg_dec() { asm volatile("setmaxnreg.dec.sync.aligned.u32 %0;" ::"n"(N)); }
template <int N>
DEVI void reg_inc() { asm volatile("setmaxnreg.inc.sync.aligned.u32 %0;" ::"n"(N)); }

DEVI void wg_fence() { asm volatile("wgmma.fence.sync.aligned;" ::: "memory"); }
DEVI void wg_commit() { asm volatile("wgmma.commit_group.sync.aligned;" ::: "memory"); }
template <int N>
DEVI void wg_wait() { asm volatile("wgmma.wait_group.sync.aligned %0;" ::"n"(N) : "memory"); }
template <int N>
DEVI void fence_regs(float (&d)[N]) {
#pragma unroll
  for (int i = 0; i < N; i++) asm volatile("" : "+f"(d[i])::"memory");
}

DEVI uint64_t make_desc(uint32_t addr, uint32_t lbo, uint32_t sbo, uint32_t swz) {
  return (uint64_t)((addr & 0x3FFFFu) >> 4) | ((uint64_t)((lbo & 0x3FFFFu) >> 4) << 16) |
         ((uint64_t)((sbo & 0x3FFFFu) >> 4) << 32) | ((uint64_t)swz << 62);
}

DEVI uint64_t desc64(uint32_t lo, uint32_t hi) {
  uint64_t d;
  asm("mov.b64 %0, {%1, %2};" : "=l"(d) : "r"(lo), "r"(hi));
  return d;
}
DEVI uint32_t pack_bf16(float lo, float hi) {
  uint32_t r;
  asm("cvt.rn.bf16x2.f32 %0, %1, %2;" : "=r"(r) : "f"(hi), "f"(lo));
  return r;
}
DEVI float ex2(float x) {
  float r;
  asm("ex2.approx.ftz.f32 %0, %1;" : "=f"(r) : "f"(x));
  return r;
}
DEVI float rcp_approx(float x) {
  float r;
  asm("rcp.approx.ftz.f32 %0, %1;" : "=f"(r) : "f"(x));
  return r;
}
DEVI uint32_t movmatrix_t(uint32_t a) {
  uint32_t r;
  asm("movmatrix.sync.aligned.m8n8.trans.b16 %0, %1;" : "=r"(r) : "r"(a));
  return r;
}
DEVI void ldmatrix_x4(uint32_t (&r)[4], uint32_t addr) {
  asm volatile("ldmatrix.sync.aligned.m8n8.x4.shared.b16 {%0, %1, %2, %3}, [%4];"
               : "=r"(r[0]), "=r"(r[1]), "=r"(r[2]), "=r"(r[3]) : "r"(addr) : "memory");
}
DEVI void ldmatrix_x4(uint32_t& r0, uint32_t& r1, uint32_t& r2, uint32_t& r3, uint32_t addr) {
  asm volatile("ldmatrix.sync.aligned.m8n8.x4.shared.b16 {%0, %1, %2, %3}, [%4];"
               : "=r"(r0), "=r"(r1), "=r"(r2), "=r"(r3) : "r"(addr) : "memory");
}
DEVI void ldmatrix_x2(uint32_t& r0, uint32_t& r1, uint32_t addr) {
  asm volatile("ldmatrix.sync.aligned.m8n8.x2.shared.b16 {%0, %1}, [%2];"
               : "=r"(r0), "=r"(r1) : "r"(addr) : "memory");
}
DEVI void ldmatrix_x4_t(uint32_t (&r)[4], uint32_t addr) {
  asm volatile("ldmatrix.sync.aligned.m8n8.x4.trans.shared.b16 {%0, %1, %2, %3}, [%4];"
               : "=r"(r[0]), "=r"(r[1]), "=r"(r[2]), "=r"(r[3]) : "r"(addr) : "memory");
}
DEVI void stmatrix_x4(uint32_t addr, uint32_t r0, uint32_t r1, uint32_t r2, uint32_t r3) {
  asm volatile("stmatrix.sync.aligned.m8n8.x4.shared.b16 [%0], {%1, %2, %3, %4};"
               ::"r"(addr), "r"(r0), "r"(r1), "r"(r2), "r"(r3) : "memory");
}
DEVI void stmatrix_x4_t(uint32_t addr, uint32_t r0, uint32_t r1, uint32_t r2, uint32_t r3) {
  asm volatile("stmatrix.sync.aligned.m8n8.x4.trans.shared.b16 [%0], {%1, %2, %3, %4};"
               ::"r"(addr), "r"(r0), "r"(r1), "r"(r2), "r"(r3) : "memory");
}
DEVI void mma16816(float (&d)[4], const uint32_t (&a)[4], uint32_t b0, uint32_t b1) {
  asm volatile("mma.sync.aligned.m16n8k16.row.col.f32.bf16.bf16.f32 {%0, %1, %2, %3}, {%4, %5, %6, %7}, {%8, %9}, {%0, %1, %2, %3};"
               : "+f"(d[0]), "+f"(d[1]), "+f"(d[2]), "+f"(d[3])
               : "r"(a[0]), "r"(a[1]), "r"(a[2]), "r"(a[3]), "r"(b0), "r"(b1));
}
DEVI void mma16816_z(float (&d)[4], const uint32_t (&a)[4], uint32_t b0, uint32_t b1) {
  asm volatile("mma.sync.aligned.m16n8k16.row.col.f32.bf16.bf16.f32 {%0, %1, %2, %3}, {%4, %5, %6, %7}, {%8, %9}, {%10, %10, %10, %10};"
               : "=f"(d[0]), "=f"(d[1]), "=f"(d[2]), "=f"(d[3])
               : "r"(a[0]), "r"(a[1]), "r"(a[2]), "r"(a[3]), "r"(b0), "r"(b1), "f"(0.f));
}
DEVI void mma16816_c(float (&d)[4], const uint32_t (&a)[4], uint32_t b0, uint32_t b1, const float (&c)[4]) {
  asm volatile("mma.sync.aligned.m16n8k16.row.col.f32.bf16.bf16.f32 {%0, %1, %2, %3}, {%4, %5, %6, %7}, {%8, %9}, {%10, %11, %12, %13};"
               : "=f"(d[0]), "=f"(d[1]), "=f"(d[2]), "=f"(d[3])
               : "r"(a[0]), "r"(a[1]), "r"(a[2]), "r"(a[3]), "r"(b0), "r"(b1), "f"(c[0]), "f"(c[1]), "f"(c[2]), "f"(c[3]));
}
template <int BIT>
DEVI void sel2(uint32_t mask, float& r0, float& r1, float a0, float a1, float b0, float b1) {
  asm("{\n.reg .pred p;\n.reg .b32 t;\nand.b32 t, %2, %7;\nsetp.ne.b32 p, t, 0;\nselp.f32 %0, %3, %5, p;\nselp.f32 %1, %4, %6, p;\n}"
      : "=f"(r0), "=f"(r1) : "r"(mask), "f"(a0), "f"(a1), "f"(b0), "f"(b1), "n"(BIT));
}
template <int BIT>
DEVI void split2(uint32_t mask, uint32_t& r0, uint32_t& r1, uint32_t v) {
  asm("{\n.reg .pred p;\n.reg .b32 t;\nand.b32 t, %2, %4;\nsetp.ne.b32 p, t, 0;\nselp.b32 %0, %3, 0, p;\nselp.b32 %1, 0, %3, p;\n}"
      : "=r"(r0), "=r"(r1) : "r"(mask), "r"(v), "n"(BIT));
}
DEVI void red_add1(uint32_t* p) {
  asm volatile("red.relaxed.gpu.global.add.u32 [%0], 1;" ::"l"(p) : "memory");
}
DEVI bool named_bar_or(int id, int n, bool v) {
  uint32_t r;
  asm volatile("{\n.reg .pred p, q;\nsetp.ne.u32 p, %1, 0;\nbar.red.or.pred q, %2, %3, p;\nselp.u32 %0, 1, 0, q;\n}"
               : "=r"(r) : "r"((uint32_t)v), "r"(id), "r"(n) : "memory");
  return r != 0;
}
DEVI void cp_async16(uint32_t dst, const void* src) {
  asm volatile("cp.async.cg.shared.global [%0], [%1], 16;" ::"r"(dst), "l"(src) : "memory");
}
DEVI void cp_async_wait_all() { asm volatile("cp.async.wait_all;" ::: "memory"); }
DEVI void stg128(void* p, uint4 v) {
  asm volatile("st.relaxed.gpu.global.v4.u32 [%0], {%1, %2, %3, %4};" ::"l"(p), "r"(v.x), "r"(v.y), "r"(v.z), "r"(v.w) : "memory");
}
DEVI void stg32_if(uint32_t* p, uint32_t v, bool on) {
  asm volatile("{\n.reg .pred q;\nsetp.ne.u32 q, %2, 0;\n@q st.global.u32 [%0], %1;\n}" ::"l"(p), "r"(v), "r"((uint32_t)on) : "memory");
}
DEVI void red_max(uint32_t* p, uint32_t v) {
  asm volatile("red.relaxed.gpu.global.max.u32 [%0], %1;" ::"l"(p), "r"(v) : "memory");
}
DEVI uint4 ldg128(const void* p) {
  uint4 v;
  asm volatile("ld.global.nc.v4.u32 {%0, %1, %2, %3}, [%4];" : "=r"(v.x), "=r"(v.y), "=r"(v.z), "=r"(v.w) : "l"(p));
  return v;
}
DEVI uint32_t ld_acquire(const uint32_t* p) {
  uint32_t v;
  asm volatile("ld.acquire.gpu.global.u32 %0, [%1];" : "=r"(v) : "l"(p) : "memory");
  return v;
}
DEVI uint32_t ld_relaxed(const uint32_t* p) {
  uint32_t v;
  asm volatile("ld.relaxed.gpu.global.u32 %0, [%1];" : "=r"(v) : "l"(p) : "memory");
  return v;
}
DEVI void st_relaxed(uint32_t* p, uint32_t v) {
  asm volatile("st.relaxed.gpu.global.u32 [%0], %1;" ::"l"(p), "r"(v) : "memory");
}
DEVI void st_release(uint32_t* p, uint32_t v) {
  asm volatile("st.release.gpu.global.u32 [%0], %1;" ::"l"(p), "r"(v) : "memory");
}
DEVI void fence_gpu() { asm volatile("fence.acq_rel.gpu;" ::: "memory"); }
DEVI uint32_t lds32(uint32_t addr) {
  uint32_t v;
  asm volatile("ld.shared.u32 %0, [%1];" : "=r"(v) : "r"(addr) : "memory");
  return v;
}
DEVI uint4 lds128(uint32_t addr) {
  uint4 v;
  asm volatile("ld.shared.v4.u32 {%0, %1, %2, %3}, [%4];" : "=r"(v.x), "=r"(v.y), "=r"(v.z), "=r"(v.w) : "r"(addr) : "memory");
  return v;
}
DEVI int lds32v(uint32_t addr) {
  int v;
  asm volatile("ld.volatile.shared.s32 %0, [%1];" : "=r"(v) : "r"(addr) : "memory");
  return v;
}
DEVI void sts32(uint32_t addr, uint32_t v) {
  asm volatile("st.shared.u32 [%0], %1;" ::"r"(addr), "r"(v) : "memory");
}
DEVI void sts128(uint32_t addr, uint4 v) {
  asm volatile("st.shared.v4.u32 [%0], {%1, %2, %3, %4};" ::"r"(addr), "r"(v.x), "r"(v.y), "r"(v.z), "r"(v.w) : "memory");
}
DEVI void named_bar_arrive(int id, int n) { asm volatile("bar.arrive %0, %1;" ::"r"(id), "r"(n) : "memory"); }
DEVI void named_bar_sync(int id, int n) { asm volatile("bar.sync %0, %1;" ::"r"(id), "r"(n) : "memory"); }
DEVI void fence_proxy_async() { asm volatile("fence.proxy.async.shared::cta;" ::: "memory"); }
DEVI void fence_proxy_async_global() { asm volatile("fence.proxy.async.global;" ::: "memory"); }
DEVI int clampi(int v, int lo, int hi) { return v < lo ? lo : (v > hi ? hi : v); }

template <int TA, int TB> DEVI void wgmma_m64n144k16_ss(float (&d)[72], uint64_t descA, uint64_t descB, int scaleD) {
  asm volatile("{\n.reg .pred p;\nsetp.ne.b32 p, %74, 0;\nwgmma.mma_async.sync.aligned.m64n144k16.f32.bf16.bf16 {%0, %1, %2, %3, %4, %5, %6, %7, %8, %9, %10, %11, %12, %13, %14, %15, %16, %17, %18, %19, %20, %21, %22, %23, %24, %25, %26, %27, %28, %29, %30, %31, %32, %33, %34, %35, %36, %37, %38, %39, %40, %41, %42, %43, %44, %45, %46, %47, %48, %49, %50, %51, %52, %53, %54, %55, %56, %57, %58, %59, %60, %61, %62, %63, %64, %65, %66, %67, %68, %69, %70, %71}, %72, %73, p, 1, 1, %75, %76;\n}\n"
    : "+f"(d[0]), "+f"(d[1]), "+f"(d[2]), "+f"(d[3]), "+f"(d[4]), "+f"(d[5]), "+f"(d[6]), "+f"(d[7]), "+f"(d[8]), "+f"(d[9]), "+f"(d[10]), "+f"(d[11]), "+f"(d[12]), "+f"(d[13]), "+f"(d[14]), "+f"(d[15]), "+f"(d[16]), "+f"(d[17]), "+f"(d[18]), "+f"(d[19]), "+f"(d[20]), "+f"(d[21]), "+f"(d[22]), "+f"(d[23]), "+f"(d[24]), "+f"(d[25]), "+f"(d[26]), "+f"(d[27]), "+f"(d[28]), "+f"(d[29]), "+f"(d[30]), "+f"(d[31]), "+f"(d[32]), "+f"(d[33]), "+f"(d[34]), "+f"(d[35]), "+f"(d[36]), "+f"(d[37]), "+f"(d[38]), "+f"(d[39]), "+f"(d[40]), "+f"(d[41]), "+f"(d[42]), "+f"(d[43]), "+f"(d[44]), "+f"(d[45]), "+f"(d[46]), "+f"(d[47]), "+f"(d[48]), "+f"(d[49]), "+f"(d[50]), "+f"(d[51]), "+f"(d[52]), "+f"(d[53]), "+f"(d[54]), "+f"(d[55]), "+f"(d[56]), "+f"(d[57]), "+f"(d[58]), "+f"(d[59]), "+f"(d[60]), "+f"(d[61]), "+f"(d[62]), "+f"(d[63]), "+f"(d[64]), "+f"(d[65]), "+f"(d[66]), "+f"(d[67]), "+f"(d[68]), "+f"(d[69]), "+f"(d[70]), "+f"(d[71])
    : "l"(descA), "l"(descB), "r"(scaleD), "n"(TA), "n"(TB));
}

template <int TB> DEVI void wgmma_m64n64k16_rs(float (&d)[32], uint32_t a0, uint32_t a1, uint32_t a2, uint32_t a3, uint64_t descB, int scaleD) {
  asm volatile("{\n.reg .pred p;\nsetp.ne.b32 p, %37, 0;\nwgmma.mma_async.sync.aligned.m64n64k16.f32.bf16.bf16 {%0, %1, %2, %3, %4, %5, %6, %7, %8, %9, %10, %11, %12, %13, %14, %15, %16, %17, %18, %19, %20, %21, %22, %23, %24, %25, %26, %27, %28, %29, %30, %31}, {%32, %33, %34, %35}, %36, p, 1, 1, %38;\n}\n"
    : "+f"(d[0]), "+f"(d[1]), "+f"(d[2]), "+f"(d[3]), "+f"(d[4]), "+f"(d[5]), "+f"(d[6]), "+f"(d[7]), "+f"(d[8]), "+f"(d[9]), "+f"(d[10]), "+f"(d[11]), "+f"(d[12]), "+f"(d[13]), "+f"(d[14]), "+f"(d[15]), "+f"(d[16]), "+f"(d[17]), "+f"(d[18]), "+f"(d[19]), "+f"(d[20]), "+f"(d[21]), "+f"(d[22]), "+f"(d[23]), "+f"(d[24]), "+f"(d[25]), "+f"(d[26]), "+f"(d[27]), "+f"(d[28]), "+f"(d[29]), "+f"(d[30]), "+f"(d[31])
    : "r"(a0), "r"(a1), "r"(a2), "r"(a3), "l"(descB), "r"(scaleD), "n"(TB));
}

template <int TA, int TB> DEVI void wgmma_m64n48k16_ss(float (&d)[24], uint64_t descA, uint64_t descB, int scaleD) {
  asm volatile("{\n.reg .pred p;\nsetp.ne.b32 p, %26, 0;\nwgmma.mma_async.sync.aligned.m64n48k16.f32.bf16.bf16 {%0, %1, %2, %3, %4, %5, %6, %7, %8, %9, %10, %11, %12, %13, %14, %15, %16, %17, %18, %19, %20, %21, %22, %23}, %24, %25, p, 1, 1, %27, %28;\n}\n"
    : "+f"(d[0]), "+f"(d[1]), "+f"(d[2]), "+f"(d[3]), "+f"(d[4]), "+f"(d[5]), "+f"(d[6]), "+f"(d[7]), "+f"(d[8]), "+f"(d[9]), "+f"(d[10]), "+f"(d[11]), "+f"(d[12]), "+f"(d[13]), "+f"(d[14]), "+f"(d[15]), "+f"(d[16]), "+f"(d[17]), "+f"(d[18]), "+f"(d[19]), "+f"(d[20]), "+f"(d[21]), "+f"(d[22]), "+f"(d[23])
    : "l"(descA), "l"(descB), "r"(scaleD), "n"(TA), "n"(TB));
}

template <int TA, int TB> DEVI void wgmma_m64n96k16_ss(float (&d)[48], uint64_t descA, uint64_t descB, int scaleD) {
  asm volatile("{\n.reg .pred p;\nsetp.ne.b32 p, %50, 0;\nwgmma.mma_async.sync.aligned.m64n96k16.f32.bf16.bf16 {%0, %1, %2, %3, %4, %5, %6, %7, %8, %9, %10, %11, %12, %13, %14, %15, %16, %17, %18, %19, %20, %21, %22, %23, %24, %25, %26, %27, %28, %29, %30, %31, %32, %33, %34, %35, %36, %37, %38, %39, %40, %41, %42, %43, %44, %45, %46, %47}, %48, %49, p, 1, 1, %51, %52;\n}\n"
    : "+f"(d[0]), "+f"(d[1]), "+f"(d[2]), "+f"(d[3]), "+f"(d[4]), "+f"(d[5]), "+f"(d[6]), "+f"(d[7]), "+f"(d[8]), "+f"(d[9]), "+f"(d[10]), "+f"(d[11]), "+f"(d[12]), "+f"(d[13]), "+f"(d[14]), "+f"(d[15]), "+f"(d[16]), "+f"(d[17]), "+f"(d[18]), "+f"(d[19]), "+f"(d[20]), "+f"(d[21]), "+f"(d[22]), "+f"(d[23]), "+f"(d[24]), "+f"(d[25]), "+f"(d[26]), "+f"(d[27]), "+f"(d[28]), "+f"(d[29]), "+f"(d[30]), "+f"(d[31]), "+f"(d[32]), "+f"(d[33]), "+f"(d[34]), "+f"(d[35]), "+f"(d[36]), "+f"(d[37]), "+f"(d[38]), "+f"(d[39]), "+f"(d[40]), "+f"(d[41]), "+f"(d[42]), "+f"(d[43]), "+f"(d[44]), "+f"(d[45]), "+f"(d[46]), "+f"(d[47])
    : "l"(descA), "l"(descB), "r"(scaleD), "n"(TA), "n"(TB));
}

#define DEV_NB 7
#define DEV_D 6
#define DEV_WTMA 2
#define DEV_WOD 2000
#define DEV_PB 7
#define DEV_SEND 0
#define DEV_NV 2
#define DEV_BE 0
#define DEV_ONORM 0
#define DEV_GF 1
#define X_NOV 0
#define X_NOK 0
#define X_NOSH 0
#define X_NOMV 0
#define X_NOST 0
#define X_NOH 0
#define X_NOSTSM 0
#define DEV_ORD 0
#define DEV_HSUM 2
#define DEV_DEPH 24
#define DEV_PS 200
#define PWAIT mbar_wait_sleep
#define DEV_TURN 1
#define DEV_WG 1
#define DEV_GATE 0
#define HPOLL ld_acquire
#define DEV_GG 27
#define DEV_GI 0
#define DEV_OMAJ 1
#define OIDX(g, ps) ((ps) * 28 + (g))
#define OSTEP 1
#define DEV_HMERGE 1
#define DEV_OE 0
#define DEV_F1 1
#define DEV_F2 1
#define DEV_F3 1
#define DEV_F4 1
#define DEV_NS 200

constexpr int kS = 112;
constexpr int kStripCtas = 112;
constexpr int kProjCtas = 20;
constexpr int kThreads = 512;
constexpr int kArr = 29;
constexpr int kExch = 27;
constexpr int kSteps = 28;
constexpr int kTiles = kSteps * 28;
constexpr int kOTileBytes = 64 * 192 * 2;
constexpr int kTailBands = DEV_NB;
constexpr int kTail0 = kSteps - kTailBands;
constexpr int kProjTiles = (kSteps - kTailBands) * 28;
constexpr int kHaloBytes = 3 * 784 - 16, kHaloPitch = 2432;

__device__ __align__(1024) uint8_t g_o[(size_t)kTiles * kOTileBytes];
constexpr int kHaloBlock = (2 * kExch + 1) * kHaloPitch;
__device__ __align__(1024) uint8_t g_halo[(size_t)kStripCtas * kHaloBlock];
__device__ __align__(1024) uint8_t g_wop[4 * 3 * 192 * 32];
__device__ uint32_t g_hflag[kStripCtas * 32];
__device__ uint32_t g_oflag[28 * 32];
__device__ uint32_t g_wflag[4 * 32];
__device__ uint32_t g_epoch[132 * 32];

#define HFLAG(c) reinterpret_cast<uint32_t*>(g_halo + (size_t)(c) * kHaloBlock + 2 * kExch * kHaloPitch)
#define HEPOCH(c) (HFLAG(c) + 32)

namespace ka {
constexpr int kWAtom = 192 * 32;
constexpr int kWBytes = 9 * kWAtom;
constexpr int kXBytes = 64 * 384;
constexpr int kCol = 784;
constexpr int kQCol = 400;
constexpr int kSlot = 22 * kCol;
constexpr int kQSlot = 16 * kQCol;
constexpr int kQOff = 5 * kSlot + 32;
constexpr int kOffX = kWBytes;
constexpr int kOffRing = kOffX + 2 * kXBytes;
constexpr int kOffBar = kOffRing + kQOff + 6 * kQSlot;
constexpr int kOffStage = kOffX, kOffWo = kOffX + 2 * kWAtom;
constexpr int kOffDummy = kOffBar + 896;
DEVI uint32_t tail_buf(int i) { return i < 2 ? i * kOTileBytes : kOffRing + (i - 2) * 2 * kSlot; }
constexpr int kLastBytes = 3 * (16 + 2 * 15) * 128;
constexpr int kBarX = 0, kBarFull = 256, kBarO = 512, kBarT = 768, kBarJunk = 896;
constexpr int kSmemBytes = kOffBar + 896 + 704;
constexpr int kD = DEV_D;
static_assert(kD == 5 || kD == 6, "ring");
static_assert(kTailBands <= 8, "buffers");
constexpr int kNbInit = 0, kNbMisc = 1, kNbBurst = 2, kNbTile = 7, kNbFirst = 13, kNbX = 14;
}

namespace kb {
constexpr int kWoBlk = 192 * 128;
constexpr int kStages = 6;
constexpr int kOffA = 3 * kWoBlk;
constexpr int kOffBar = kOffA + kStages * kOTileBytes;
constexpr int kSmemBytes = kOffBar + 128;
}

constexpr int kSmemBytes = ka::kSmemBytes > kb::kSmemBytes ? ka::kSmemBytes : kb::kSmemBytes;
static_assert(kSmemBytes <= 232448, "smem");

#define TRACE(idx)
#define GT(i)
#define ATRACE(k)
#define TRBASE (sbase + kTraceOff)

DEVI void mbar_wait_sleep(uint32_t bar, uint32_t parity) {
  uint32_t it = 0;
  while (!mbar_test_wait(bar, parity)) {
    __nanosleep(DEV_NS);
    if (++it > LIMIT) { BAIL(bar & 0xfffff); break; }
  }
}

DEVI void publish_fence() {
  fence_proxy_async_global();
  fence_gpu();
}

DEVI uint32_t sched_fence() {
  uint32_t t;
  asm volatile("mov.u32 %0, %clock;" : "=r"(t)::"memory");
  return t;
}

struct AttnState {
  uint32_t kf[5][3][4];
  uint32_t vf[5][3][4];
  float bias[5][4];
  uint32_t p[5][2];
  uint32_t kaddr, vaddr, qaddr, bar, junk, fence;
  float sum0, sum1;
  uint32_t ones[4];
  bool rdy;
  uint32_t pm;
  uint32_t* optr;
};

DEVI void store_o(AttnState& s, float (&o)[3][4], float i0, float i1, bool on) {
#pragma unroll
  for (int mt = 0; mt < 3; mt++) {
    stg32_if(s.optr + (2 * mt) * 32, pack_bf16(o[mt][0] * i0, o[mt][1] * i1), on);
    stg32_if(s.optr + (2 * mt + 1) * 32, pack_bf16(o[mt][2] * i0, o[mt][3] * i1), on);
  }
  s.optr += OSTEP * kOTileBytes / 4;
}

template <int PH>
DEVI void attn_step(AttnState& s, int g, int warp, const __nv_bfloat16* __restrict__ rpb) {
  using namespace ka;
  constexpr int R = (2 * PH) % 5, N0 = (R + 3) % 5, N1 = (R + 4) % 5;
  constexpr int SL = ((PH + 1) % 5) * kSlot;
  if (PH == 0 && g == 0) {
    {
      const int lane = threadIdx.x & 31, qc0 = 16 * ((blockIdx.x >> 2) % 7) + 2 * warp;
      const int kc = clampi(qc0 - 3, 0, kS - 8) + (lane >> 2);
      const unsigned short* r = reinterpret_cast<const unsigned short*>(rpb) + (blockIdx.x & 3) * 169 + (3 - (lane & 3)) * 13 + kc - qc0 + 6;
      const int sw0 = clampi(qc0 - 3, 0, kS - 7), sw1 = clampi(qc0 - 2, 0, kS - 7);
      const bool ok0 = kc >= sw0 && kc < sw0 + 7, ok1 = kc >= sw1 && kc < sw1 + 7;
#pragma unroll
      for (int i = 0; i < 10; i++) {
        const uint32_t v0 = ok0 ? (uint32_t)__ldg(r + i * 13) : 0xFF80u;
        const uint32_t v1 = ok1 ? (uint32_t)__ldg(r + i * 13 - 1) : 0xFF80u;
        s.bias[i >> 1][2 * (i & 1)] = __uint_as_float(v0 << 16) * 6.928203230275509f;
        s.bias[i >> 1][2 * (i & 1) + 1] = __uint_as_float(v1 << 16) * 6.928203230275509f;
      }
    }
    named_bar_sync(kNbMisc, 384);
    mbar_wait(s.bar + kBarFull, 0);
#pragma unroll
    for (int k = 0; k < 3; k++) {
      ldmatrix_x4(s.kf[1][k], s.kaddr + k * 32);
      ldmatrix_x4(s.kf[2][k], s.kaddr + 384 + k * 32);
      ldmatrix_x4_t(s.vf[1][k], s.vaddr + k * 32);
      ldmatrix_x4_t(s.vf[2][k], s.vaddr + 384 + k * 32);
      s.vf[0][k][0] = s.vf[0][k][1] = s.vf[0][k][2] = s.vf[0][k][3] = 0u;
    }
    named_bar_arrive(kNbFirst, 384);
  }
  if (!s.rdy) mbar_wait(s.bar + kBarFull + 8 * (g + 1), 0);
  if (DEV_DEPH && PH == DEV_DEPH % 5 && g == DEV_DEPH && warp >= 4) named_bar_sync(kNbInit, 256);
  ATRACE(0);
  float t[5][4], o[3][4], z[4];
  uint32_t q[6];
  const uint32_t (&ones)[4] = s.ones;
#define LDV(n) if (!X_NOV) ldmatrix_x4_t(s.vf[(n) < 3 ? N0 : N1][(n) % 3], s.vaddr + SL + ((n) / 3) * 384 + ((n) % 3) * 32);
#define LDK(n) if (!X_NOK) ldmatrix_x4(s.kf[(n) & 1 ? N1 : N0][(n) >> 1], s.kaddr + SL + ((n) & 1) * 384 + ((n) >> 1) * 32);
#define PV(i) { _Pragma("unroll") for (int mt = 0; mt < 3; mt++) { \
                  if ((i) == 0) mma16816_z(o[mt], s.vf[N0][mt], s.p[0][0], s.p[0][1]); \
                  else mma16816(o[mt], s.vf[(R + 3 + (i)) % 5][mt], s.p[i][0], s.p[i][1]); } \
                if (DEV_HSUM == 1) { if ((i) == 0) mma16816_z(z, ones, s.p[0][0], s.p[0][1]); else mma16816(z, ones, s.p[i][0], s.p[i][1]); } \
                if (DEV_HSUM == 2) { if ((i) == 0) mma16816_z(z, ones, s.p[0][0] | s.p[4][0], s.p[0][1] | s.p[4][1]); \
                                     else if ((i) < 4) mma16816(z, ones, s.p[i][0], s.p[i][1]); } }
#define QK(i, ks) { if ((ks) == 0) mma16816_c(t[i], s.kf[(R + (i)) % 5][0], q[0], q[1], s.bias[i]); \
                    else mma16816(t[i], s.kf[(R + (i)) % 5][ks], q[2 * (ks)], q[2 * (ks) + 1]); }
#define REL named_bar_arrive(kNbBurst + (PH + kD) % 5, 384);
  ldmatrix_x4(q[0], q[1], q[2], q[3], s.qaddr);
  ldmatrix_x2(q[4], q[5], s.qaddr + 64);
  uint32_t f0 = 0, f1, f2, f3 = 0;
  LDK(0) LDK(1) LDK(2) LDK(3) LDK(4) LDK(5)
  PV(0) PV(1) PV(2) PV(3) PV(4)
  f1 = DEV_F1 ? sched_fence() : 0;
  s.junk ^= s.fence;
#pragma unroll
  for (int n = 5; n >= DEV_NV; n--) LDV(n)
#pragma unroll
  for (int n = 0; n < 15 - DEV_BE; n++) QK(n % 5, n / 5)
  f2 = DEV_F2 ? sched_fence() : 0;
  REL
#pragma unroll
  for (int n = 15 - DEV_BE; n < 15; n++) QK(n % 5, n / 5)
  s.fence = DEV_F3 ? sched_fence() : 0;
  if (DEV_DEPH && PH == DEV_DEPH % 5 && g == DEV_DEPH && warp < 4) named_bar_arrive(kNbInit, 256);
  ATRACE(1);
  uint32_t pm = s.pm;
  if (PH == 0 && g == 0) pm &= ~0x3Fu;
  if (PH == 2 && g == kSteps - 1) pm |= 0x3Fu;
  float x[7][2];
  sel2<1>(pm, x[0][0], x[0][1], t[0][0], t[0][1], t[3][2], t[3][3]);
  sel2<2>(pm, x[1][0], x[1][1], t[0][2], t[0][3], t[4][0], t[4][1]);
  sel2<4>(pm, x[2][0], x[2][1], t[1][0], t[1][1], t[4][2], t[4][3]);
#pragma unroll
  for (int e = 0; e < 2; e++) {
    x[3][e] = t[1][2 + e]; x[4][e] = t[2][e]; x[5][e] = t[2][2 + e]; x[6][e] = t[3][e];
  }
  float m0 = fmaxf(fmaxf(fmaxf(x[0][0], x[1][0]), fmaxf(x[2][0], x[3][0])), fmaxf(fmaxf(x[4][0], x[5][0]), x[6][0]));
  float m1 = fmaxf(fmaxf(fmaxf(x[0][1], x[1][1]), fmaxf(x[2][1], x[3][1])), fmaxf(fmaxf(x[4][1], x[5][1]), x[6][1]));
#pragma unroll
  for (int d = 4; d <= (X_NOSH ? 0 : 16); d <<= 1) {
    m0 = fmaxf(m0, __shfl_xor_sync(0xffffffffu, m0, d));
    m1 = fmaxf(m1, __shfl_xor_sync(0xffffffffu, m1, d));
    if (!DEV_HSUM) {
      s.sum0 += __shfl_xor_sync(0xffffffffu, s.sum0, d);
      s.sum1 += __shfl_xor_sync(0xffffffffu, s.sum1, d);
    }
  }
  if (!DEV_HSUM) { z[0] = s.sum0; z[1] = s.sum1; }
  if (DEV_OE) store_o(s, o, rcp_approx(z[0]), rcp_approx(z[1]), PH == 1 || PH == 2 || g > 0);
  uint32_t f4 = 0;
  if (DEV_NV > 0) {
    f4 = DEV_F4 ? sched_fence() : 0;
#pragma unroll
    for (int n = 0; n < DEV_NV; n++) LDV(n)
  }
  s.rdy = PH == 3 && g < 0;
  if (PH < 3 || g >= 0) s.rdy = mbar_test_wait(s.bar + kBarFull + 8 * (g + 2), 0);
  const float c = 0.14433756729740643f * 1.4426950408889634f;
  const float n0 = -m0 * c, n1 = -m1 * c;
  uint32_t pt[7];
#pragma unroll
  for (int i = 0; i < 7; i++) {
    const float e0 = ex2(fmaf(x[i][0], c, n0)), e1 = ex2(fmaf(x[i][1], c, n1));
    if (!DEV_HSUM) {
      s.sum0 = i ? s.sum0 + e0 : e0;
      s.sum1 = i ? s.sum1 + e1 : e1;
    }
    pt[i] = X_NOMV ? pack_bf16(e0, e1) : movmatrix_t(pack_bf16(e0, e1));
  }
  split2<8>(pm, s.p[0][0], s.p[3][1], pt[0]);
  split2<16>(pm, s.p[0][1], s.p[4][0], pt[1]);
  split2<32>(pm, s.p[1][0], s.p[4][1], pt[2]);
  s.p[1][1] = pt[3]; s.p[2][0] = pt[4]; s.p[2][1] = pt[5]; s.p[3][0] = pt[6];
#pragma unroll
  for (int i = 0; i < 5; i++) asm volatile("" : "+r"(s.p[i][0]), "+r"(s.p[i][1])::"memory");
  if (!DEV_HSUM) asm volatile("" : "+f"(s.sum0), "+f"(s.sum1)::"memory");
  if (!DEV_OE) store_o(s, o, rcp_approx(z[0]), rcp_approx(z[1]), PH == 1 || PH == 2 || g > 0);
  __syncwarp();
  if ((s.pm & 64) && (PH < 3 || g >= 0)) mbar_arrive(s.bar + kBarO + 8 * (g - 1));
  s.junk ^= f0 ^ f1 ^ f2 ^ f3;
  s.fence ^= f4;
  s.qaddr += kQSlot;
  if (s.qaddr >= s.bar) s.qaddr -= 6 * kQSlot;
  asm volatile("" : "+r"(s.junk)::"memory");
  ATRACE(2);
}

__global__ void __launch_bounds__(kThreads, 1)
nat_kernel(const __nv_bfloat16* __restrict__ wqkv, const __nv_bfloat16* __restrict__ rpb,
           const __grid_constant__ CUtensorMap tm_x, const __grid_constant__ CUtensorMap tm_w,
           const __grid_constant__ CUtensorMap tm_h, const __grid_constant__ CUtensorMap tm_r,
           const __grid_constant__ CUtensorMap tm_wo, const __grid_constant__ CUtensorMap tm_out,
           const __grid_constant__ CUtensorMap tm_wo2, const __grid_constant__ CUtensorMap tm_o2) {
  extern __shared__ __align__(1024) uint8_t smem_raw[];
  const uint32_t sbase = smem_u32(smem_raw);
  if (sbase & 1023u) __trap();
  const int warp = __shfl_sync(0xffffffffu, (int)(threadIdx.x >> 5), 0), lane = threadIdx.x & 31;
  const int wg = warp >> 2, wl = warp & 3;
  const int cta = blockIdx.x;
  const bool strip_cta = cta < kStripCtas;
  const int head = cta & 3, ps = cta >> 2, par = ps / 7, strip = ps - 7 * par;
  if (threadIdx.x == 0) TRACE(0);

  if (strip_cta && threadIdx.x == 384) {
    using namespace ka;
    const uint32_t bar = sbase + kOffBar;
    mbar_init(bar + kBarX, 1);
    mbar_expect_tx(bar + kBarX, kXBytes + DEV_WTMA * 3 * kWAtom);
    tma_load_5d(sbase + kOffX, &tm_x, bar + kBarX, 0, 16 * strip, -1, 3 * (par & 1), par >> 1);
#pragma unroll
    for (int i = 9 - 3 * DEV_WTMA; i < 9; i++)
      tma_load_2d(sbase + i * kWAtom, &tm_w, bar + kBarX, (i / 3) * 192 + head * 48 + (i % 3) * 16, 0);
    TRACE(10);
  }
  __syncwarp();
  if (DEV_WTMA < 3 && strip_cta && wg == 2 && threadIdx.x < 256 + 96) {
    using namespace ka;
    constexpr int kSec = DEV_WTMA < 3 ? 3 - DEV_WTMA : 1;
    uint4 v[12 * kSec];
    const int wk = ((int)threadIdx.x - 256) / 6, wu = (int)threadIdx.x - 256 - 6 * wk;
    const uint8_t* src = reinterpret_cast<const uint8_t*>(wqkv) + wk * 1152 + head * 96 + wu * 16;
#pragma unroll
    for (int i = 0; i < 12 * kSec; i++) v[i] = ldg128(src + (i / kSec) * 16 * 1152 + (i % kSec) * 384);
    const uint32_t dst = sbase + (wu >> 1) * kWAtom + wk * 32 + (((wu ^ (wk >> 2)) & 1) << 4);
#pragma unroll
    for (int i = 0; i < 12 * kSec; i++) sts128(dst + (i / kSec) * 16 * 32 + (i % kSec) * 3 * kWAtom, v[i]);
    if (warp == 8) TRACE(6);
    fence_proxy_async();
  }
  if (threadIdx.x == 480) GT(0);

  if (strip_cta) {
    using namespace ka;
    const uint32_t bar = sbase + kOffBar, ring = sbase + kOffRing;
    if (wg < 2) {
      if (DEV_WG == 0) named_bar_arrive(kNbX, 416);
      reg_inc<184>();
      AttnState s;
      const int qc0 = 16 * strip + 2 * warp;
      const int kc0 = clampi(qc0 - 3, 0, kS - 8);
      const uint32_t colb = ring + (kc0 - (16 * strip - 3) + (lane & 7)) * kCol;
      s.kaddr = colb + ((lane >> 3) & 1) * 192 + (lane >> 4) * 16;
      s.vaddr = colb + 96 + (lane >> 4) * 192 + ((lane >> 3) & 1) * 16;
      {
        const int qr = (lane & 7) >> 1;
        const uint32_t qa = ring + kQOff + (2 * warp + (lane & 1)) * kQCol + (lane >> 3) * 16;
        s.qaddr = qa + (qr == 3 ? 5 * kQSlot : 4 * kQSlot + (qr + 1) * 96);
      }
      s.bar = bar;
      s.optr = reinterpret_cast<uint32_t*>(g_o + (size_t)OIDX(0, ps) * kOTileBytes + head * 6144 + warp * 768) + lane - 3 * OSTEP * kOTileBytes / 4;
#pragma unroll
      for (int i = 0; i < 5; i++) {
        s.p[i][0] = s.p[i][1] = 0u;
        s.bias[i][0] = s.bias[i][1] = s.bias[i][2] = s.bias[i][3] = 0.f;
#pragma unroll
        for (int k = 0; k < 3; k++)
#pragma unroll
          for (int c = 0; c < 4; c++) s.kf[i][k][c] = s.vf[i][k][c] = 0u;
      }
      s.junk = s.fence = 0;
      s.rdy = true;
#pragma unroll
      for (int i = 0; i < 4; i++) s.ones[i] = __shfl_sync(0xffffffffu, 0x3F803F80u, i);
      s.sum0 = s.sum1 = 1.f;
      s.pm = (7u << (lane & 3) & 7u) | ((7u << (lane >> 3) & 7u) << 3) | (lane == 0 ? 64u : 0u);
      s.pm = __shfl_sync(0xffffffffu, s.pm, lane);
#pragma unroll 1
      for (int g = -2; g < kSteps; g += 5) {
        attn_step<3>(s, g, warp, rpb);
        attn_step<4>(s, g + 1, warp, rpb);
        attn_step<0>(s, g + 2, warp, rpb);
        attn_step<1>(s, g + 3, warp, rpb);
        attn_step<2>(s, g + 4, warp, rpb);
      }
      {
        float o[3][4], z[4];
        const uint32_t (&ones)[4] = s.ones;
#pragma unroll
        for (int mt = 0; mt < 3; mt++) mma16816_z(o[mt], s.vf[4][mt], s.p[0][0], s.p[0][1]);
        mma16816_z(z, ones, s.p[0][0], s.p[0][1]);
#pragma unroll
        for (int i = 1; i < 5; i++) {
#pragma unroll
          for (int mt = 0; mt < 3; mt++) mma16816(o[mt], s.vf[i - 1][mt], s.p[i][0], s.p[i][1]);
          mma16816(z, ones, s.p[i][0], s.p[i][1]);
        }
        store_o(s, o, rcp_approx(z[0]), rcp_approx(z[1]), true);
        __syncwarp();
        if (lane == 0) mbar_arrive(bar + kBarO + 8 * (kSteps - 1));
      }
      s.junk ^= s.fence;
      if (s.junk == 0x9e3779b9u) sts32(bar + kBarJunk, 0);
      if (warp == 0) TRACE(1);
      if (threadIdx.x == 128) GT(3);
    } else if (wg == 2) {
      reg_dec<104>();
      const int col = ((lane >> 3) & 1) * 8 + (lane & 7);
      uint32_t kva = ring + (3 + col) * kCol + wl * 192 + (lane >> 4) * 16;
      uint32_t qa = ring + kQOff + col * kQCol + wl * 96 + (lane >> 4) * 16;
      const uint32_t alo = (uint32_t)make_desc(sbase + kOffX, 16, 1024, 1), blo = (uint32_t)make_desc(sbase, kWAtom, 256, 3);
      constexpr uint32_t ahi = (1u << 30) | (1024 >> 4), bhi = (3u << 30) | (256 >> 4);
      if (wl == 0) TRACE(2);
      uint32_t gj = 0;
      int bid = kNbBurst, tid = kNbTile;
      named_bar_arrive(kNbBurst + (kD - 2) % 5, 384);
      named_bar_arrive(kNbBurst + (kD - 1) % 5, 384);
      named_bar_sync(kNbX, DEV_WG ? 160 : 416);
      if (wl == 0) TRACE(7);
      mbar_wait(bar + kBarX, 0);
      if (wl == 0) TRACE(16 + 0);
#pragma unroll 1
      for (int a = 0; a < kArr; a++) {
        float acc[72];
        const uint32_t al = alo + (a & 1) * (kXBytes >> 4);
        if (a >= kD) named_bar_sync(bid, 384);
        if (wl == 0) TRACE(16 + a * 4 + 1);
        wg_fence();
#pragma unroll
        for (int k = 0; k < 12; k++)
          wgmma_m64n144k16_ss<0, 1>(acc, desc64(al + (((k >> 2) * 8192 + (k & 3) * 32) >> 4), ahi), desc64(blo + k * 32, bhi), k != 0);
        wg_commit();
        if (DEV_GF) gj ^= sched_fence();
        bid = bid == kNbBurst + 4 ? kNbBurst : bid + 1;
        if (a == 0) named_bar_sync(kNbInit, 256);
        const bool xok = mbar_test_wait(bar + kBarX + 8 * (a + 1), 0);
        if (a == kArr - 1 && wl != 0) {
          const int r = col / 3, c = col - 3 * r;
          qa = sbase + kOffDummy + lane * 16;
          kva = col < 15 && wl < 3 ? ring + ((kExch + (r >> 2)) % 5) * kSlot + ((wl - 1) * 19 + c) * kCol + (r & 3) * 192 + (lane >> 4) * 16
                                   : qa;
        }
        wg_wait<0>();
        fence_regs(acc);
        named_bar_arrive(kNbX + (a & 1), 160);
        if (kD == 6 && a == 5) named_bar_sync(kNbFirst, 384);
        if (a >= 6) mbar_wait(bar + kBarO + 8 * (a - 7), 0);
        if (wl == 0) TRACE(16 + a * 4 + 2);
#pragma unroll
        for (int jp = 0; jp < 9; jp++) {
          const int j = jp < 6 ? jp + 3 : jp - 6;
          if (!X_NOSTSM || acc[8 * j] == 123.f) stmatrix_x4(j < 3 ? qa + j * 32 : kva + (j - 3) * 32, pack_bf16(acc[8 * j + 0], acc[8 * j + 1]),
                      pack_bf16(acc[8 * j + 2], acc[8 * j + 3]), pack_bf16(acc[8 * j + 4], acc[8 * j + 5]),
                      pack_bf16(acc[8 * j + 6], acc[8 * j + 7]));
        }
        if (a < kExch) named_bar_arrive(tid, 160);
        tid = tid == kNbTile + 5 ? kNbTile : tid + 1;
        if (wl == 0) TRACE(16 + a * 4 + 3);
        if (!xok && a + 1 < kArr) mbar_wait(bar + kBarX + 8 * (a + 1), 0);
        if (wl == 0) TRACE(16 + (a + 1) * 4 + 0);
        kva += kSlot;
        if (kva >= ring + 5 * kSlot) kva -= 5 * kSlot;
        qa += kQSlot;
        if (qa >= bar) qa -= 6 * kQSlot;
      }
      __syncwarp();
      if (lane < kArr - kExch) mbar_arrive(bar + kBarFull + 8 * (kExch + lane));
      if (gj == 0x9e3779b9u) sts32(bar + kBarJunk, 0);
      if (kD == 5) named_bar_arrive(kNbFirst, 384);
#pragma unroll 1
      for (int g = kArr - kD; g < kSteps; g++) {
        if (g != DEV_GG) named_bar_arrive(bid, 384);
        bid = bid == kNbBurst + 4 ? kNbBurst : bid + 1;
      }
      {
        const uint32_t wlo = (uint32_t)make_desc(sbase + kOffWo, kWAtom, 256, 3);
        const int n = lane & 7, j = 2 * wl + ((lane >> 3) & 1);
        const uint32_t sta = sbase + kOffStage + ((2 * j + (n & 1)) * 4 + (n >> 1)) * 96 + (lane >> 4) * 16;
        mbar_wait(bar + kBarX + 8 * kArr, 0);
#pragma unroll 1
        for (int g = kTail0 + ((kTail0 ^ (head >> 1)) & 1), i = 0; g < kSteps; g += 2, i++) {
          float acc[48];
          if (DEV_GG && i == DEV_GI) named_bar_sync(kNbBurst + (DEV_GG + kD) % 5, 384);
          mbar_wait(bar + kBarT + 8 * i, 0);
          if (wl == 0) TRACE(144 + i * 2);
          const uint32_t tlo = (uint32_t)make_desc(sbase + tail_buf(i), 128, 768, 0);
          wg_fence();
#pragma unroll
          for (int k = 0; k < 12; k++)
            wgmma_m64n96k16_ss<1, 1>(acc, desc64(tlo + (((k / 3) * 6144 + (k % 3) * 256) >> 4), 768 >> 4), desc64(wlo + k * 32, bhi), k != 0);
          wg_commit();
          if (threadIdx.x == 256) bulk_wait_read();
          named_bar_sync(kNbMisc, 128);
          wg_wait<0>();
          fence_regs(acc);
#pragma unroll
          for (int jp = 0; jp < 6; jp++)
            stmatrix_x4(sta + (jp / 3) * kWAtom + (jp % 3) * 32, pack_bf16(acc[8 * jp + 0], acc[8 * jp + 1]),
                        pack_bf16(acc[8 * jp + 2], acc[8 * jp + 3]), pack_bf16(acc[8 * jp + 4], acc[8 * jp + 5]),
                        pack_bf16(acc[8 * jp + 6], acc[8 * jp + 7]));
          fence_proxy_async();
          named_bar_sync(kNbMisc, 128);
          if (threadIdx.x == 256) {
            tma_store_5d(&tm_out, sbase + kOffStage, (head & 1) * 96, 4 * g, 16 * strip, par & 1, par >> 1);
            tma_store_5d(&tm_out, sbase + kOffStage + kWAtom, (head & 1) * 96 + 48, 4 * g, 16 * strip, par & 1, par >> 1);
            bulk_commit();
          }
          __syncwarp();
          if (wl == 0) TRACE(145 + i * 2);
        }
        if (threadIdx.x == 256) {
          bulk_wait<0>();
          GT(2);
        }
      }
    } else {
      reg_dec<40>();
      if (wl == 0) named_bar_arrive(kNbX, DEV_WG ? 160 : 416);
      if (lane == 0) {
        const uint32_t b0 = bar + 64 * wl;
        if (wl == 1 && head == 1) tma_prefetch_5d(&tm_x, 0, 16 * strip, 3, 3 * (par & 1), par >> 1);
#pragma unroll
        for (int i = 0; i < 64; i += 8) {
          if (i || wl) mbar_init(b0 + kBarX + i, 1);
          mbar_init(b0 + kBarFull + i, wl < 3 || i < 8 * (kExch - 24) ? 2 : (i == 56 ? 8 : 4));
          mbar_init(b0 + kBarO + i, 8);
          if (wl == 0 && i < 32) mbar_init(b0 + kBarT + i, 1);
        }
#pragma unroll
        for (int i = 0; i < 64; i += 8) {
          if (i || wl)
            mbar_expect_tx(b0 + kBarX + i, wl < 3 || i < 32 ? kXBytes : (i == 32 ? kLastBytes : 6 * kWAtom));
          if (wl == 0 && i < 32) mbar_expect_tx(bar + kBarT + i, kOTileBytes);
        }
        fence_mbar_init();
        if (wl == 0) {
          tma_load_5d(sbase + kOffX + kXBytes, &tm_x, bar + kBarX + 8, 0, 16 * strip, 3, 3 * (par & 1), par >> 1);
          tma_prefetch_5d(&tm_x, 0, 16 * strip, 4 * (2 + ((head - 2) & 3)) - 1, 3 * (par & 1), par >> 1);
          TRACE(5);
        }
      }
      __syncwarp();
      const uint32_t ep = ld_relaxed(HEPOCH(cta) + wl) * 32u;
      named_bar_arrive(kNbMisc, 384);
      named_bar_sync(kNbInit, 256);
      if (wl == 0) {
#pragma unroll 1
        for (int a = 2; a < kArr - 1; a++) {
          named_bar_sync(kNbX + (a & 1), 160);
          if (lane == 0) {
            tma_load_5d(sbase + kOffX + (a & 1) * kXBytes, &tm_x, bar + kBarX + 8 * a, 0, 16 * strip, 4 * a - 1,
                        3 * (par & 1), par >> 1);
            const int ap = a + 4;
            if (ap < kArr && (ap & 3) == head) tma_prefetch_5d(&tm_x, 0, 16 * strip, 4 * ap - 1, 3 * (par & 1), par >> 1);
          }
          __syncwarp();
        }
        named_bar_sync(kNbX, 160);
        if (lane < 9) {
          const int kb = lane / 3, w = lane - 3 * kb;
          tma_load_5d(sbase + kOffX + kb * 8192 + w * 2048, w == 0 ? &tm_r : &tm_h, bar + kBarX + 8 * (kArr - 1), 0,
                      16 * strip + (w == 0 ? 0 : (w == 1 ? -3 : 16)), w == 0 ? kS - 1 : 4 * kExch - 1, 3 * (par & 1) + kb, par >> 1);
        }
        {
          uint32_t it = 0;
          while (!__all_sync(0xffffffffu, (int)(ld_acquire(&g_wflag[(lane & 3) * 32]) - (ep + 1)) >= 0))
            if (++it > LIMIT) { BAIL(0x5000000); break; }
        }
        const uint8_t* wsrc = g_wop + (head & 1) * 6 * kWAtom;
        named_bar_sync(kNbX + 1, 160);
        if (lane == 0) bulk_load(sbase + kOffWo + 2 * kWAtom, wsrc + 2 * kWAtom, 4 * kWAtom, bar + kBarX + 8 * kArr);
        uint32_t seen = ld_acquire(&g_oflag[ps * 32 + (lane & 3)]);
        named_bar_sync(kNbX, 160);
        if (lane == 0) bulk_load(sbase + kOffWo, wsrc, 2 * kWAtom, bar + kBarX + 8 * kArr);
#pragma unroll 1
        for (int g = kTail0 + ((kTail0 ^ (head >> 1)) & 1), i = 0; g < kSteps; g += 2, i++) {
          uint32_t it = 0;
          while (!__all_sync(0xffffffffu, (int)(seen - (ep + g + 1)) >= 0)) {
            seen = ld_acquire(&g_oflag[ps * 32 + (lane & 3)]);
            if (++it > LIMIT) { BAIL(0x3000000 + g); break; }
          }
          if (lane == 0)
            bulk_load(sbase + tail_buf(i), g_o + (size_t)OIDX(g, ps) * kOTileBytes, kOTileBytes, bar + kBarT + 8 * i);
          __syncwarp();
        }
      } else {
        const int p = wl - 1;
        const bool on = !X_NOH && (lane == 0 ? strip > 0 : strip < 6);
        const int nb = on ? cta + (lane == 0 ? -4 : 4) : cta;
        const uint32_t bytes = X_NOH ? 0 : ((strip > 0 && strip < 6) ? 2 * kHaloBytes : kHaloBytes);
        int slot = p, g = 0;
#pragma unroll 1
        for (int a = p; a < kExch; a += 3) {
          named_bar_sync(kNbTile + a % 6, 160);
          const uint32_t sl = ring + slot * kSlot;
          if (lane < 2) {
            fence_proxy_async();
            if (on) bulk_store(g_halo + (size_t)cta * kHaloBlock + (lane * kExch + a) * kHaloPitch, sl + (3 + 13 * lane) * kCol, kHaloBytes);
            bulk_commit();
          }
          __syncwarp();
          g += __ffs(~__ballot_sync(0xffffffffu, lane < 4 && mbar_test_wait(bar + kBarO + 8 * (g + lane), 0))) - 1;
          __syncwarp();
          if (lane < 2) {
            bulk_wait<0>();
            if (lane == 0) mbar_expect_tx(bar + kBarFull + 8 * a, bytes);
            else mbar_arrive(bar + kBarFull + 8 * a);
            TRACE(160 + a * 4 + 0);
            publish_fence();
            st_relaxed(HFLAG(cta) + 4 * lane + p, ep + a + 1);
            if (lane == 0 && g) red_max(&g_oflag[ps * 32 + head], ep + g);
            TRACE(160 + a * 4 + 1);
            uint32_t it = 0;
            while (true) {
              const bool ok = !on || (int)(HPOLL(HFLAG(nb) + 4 * (lane ^ 1) + p) - (ep + a + 1)) >= 0;
              if (__all_sync(3u, ok)) break;
              if (++it > LIMIT) { BAIL(0x1000000 + a); break; }
            }
            TRACE(160 + a * 4 + 2);
            if (on) bulk_load(sl + lane * 19 * kCol, g_halo + (size_t)nb * kHaloBlock + ((lane ^ 1) * kExch + a) * kHaloPitch, kHaloBytes,
                              bar + kBarFull + 8 * a);
            TRACE(160 + a * 4 + 3);
          }
          __syncwarp();
          slot = slot >= 2 ? slot - 2 : slot + 3;
        }
        if (lane == 0) {
#pragma unroll 1
          for (g = kSteps - DEV_PB + p; g < kSteps; g += 3) {
            if (g < kSteps - 3) mbar_wait_sleep(bar + kBarO + 8 * g, 0);
            else mbar_wait(bar + kBarO + 8 * g, 0);
            TRACE(370 + g * 2);
            publish_fence();
            red_max(&g_oflag[ps * 32 + head], ep + g + 1);
            TRACE(371 + g * 2);
          }
          if (p == (DEV_PB - 1) % 3) GT(1);
        }
      }
      __syncwarp();
      if (lane == 0) st_relaxed(HEPOCH(cta) + wl, (ep >> 5) + 1);
    }
  } else {
    using namespace kb;
    const uint32_t bar = sbase + kOffBar, sA = sbase + kOffA;
    const int k = cta - kStripCtas;
    if (wg < 3) {
      reg_inc<160>();
      named_bar_sync(0, 512);
      uint32_t wf[12][4];
      mbar_wait(bar + 56, 0);
      {
        const int kr = (lane & 7) + ((lane >> 4) << 3);
        const uint32_t wa = sbase + wg * kWoBlk + kr * 128 + (((2 * wl + ((lane >> 3) & 1)) ^ (lane & 7)) << 4);
#pragma unroll
        for (int kk = 0; kk < 12; kk++) ldmatrix_x4_t(wf[kk], wa + kk * 2048);
      }
      named_bar_sync(3 + wg, 128);
      const int px = (2 * (lane >> 4) + (lane & 1)) * 4 + ((lane & 7) >> 1);
      const uint32_t sto = sbase + wg * kWoBlk + px * 128 + (((2 * wl + ((lane >> 3) & 1)) ^ (px & 7)) << 4);
      int st = 0, sb = 0;
      uint32_t ph = 0;
      uint32_t pk[16];
#pragma unroll
      for (int i = 0; i < 16; i++) pk[i] = 0u;
      auto store = [&](int tq) {
        const int g = tq / 28, tp = tq - 28 * g, tpar = tp / 7, tstrip = tp - 7 * tpar;
#pragma unroll
        for (int jp = 0; jp < 4; jp++)
          stmatrix_x4_t(sto + sb * 8192 + jp * 2048, pk[4 * jp], pk[4 * jp + 1], pk[4 * jp + 2], pk[4 * jp + 3]);
        fence_proxy_async();
        if (wl == 0 && lane == 0) bulk_wait_read1();
        named_bar_sync(3 + wg, 128);
        if (wl == 0 && lane == 0 && tq >= 0) {
          tma_store_5d(&tm_o2, sbase + wg * kWoBlk + sb * 8192, 0, 4 * g, 16 * tstrip, 3 * (tpar & 1) + wg, tpar >> 1);
          bulk_commit();
        }
        __syncwarp();
        sb = sb == 2 ? 0 : sb + 1;
      };
      int t = k;
#pragma unroll 1
      for (; t < kProjTiles; t += kProjCtas) {
        float acc[32];
        PWAIT(bar + 8 * st, ph);
        if (warp == 0) TRACE(16 + (t / kProjCtas) * 4 + 1);
        const uint32_t blo = (uint32_t)make_desc(sA + st * kOTileBytes, 128, 768, 0);
        if (DEV_TURN && (t > k || wg)) named_bar_sync(6 + wg, 256);
        wg_fence();
#pragma unroll
        for (int kk = 0; kk < 12; kk++)
          wgmma_m64n64k16_rs<1>(acc, wf[kk][0], wf[kk][1], wf[kk][2], wf[kk][3],
                                desc64(blo + (((kk / 3) * 6144 + (kk % 3) * 256) >> 4), 768 >> 4), kk != 0);
        wg_commit();
        if (DEV_TURN && (wg < 2 || t + kProjCtas < kProjTiles)) named_bar_arrive(6 + (wg == 2 ? 0 : wg + 1), 256);
        store(t - kProjCtas);
        if (warp == 0) TRACE(12 + (t / kProjCtas) * 4 + 3);
        wg_wait<0>();
        fence_regs(acc);
        if (lane == 0) mbar_arrive(bar + 64 + 8 * st);
        if (warp == 0) TRACE(16 + (t / kProjCtas) * 4 + 2);
#pragma unroll
        for (int i = 0; i < 16; i++) pk[i] = pack_bf16(acc[2 * i], acc[2 * i + 1]);
        if (++st == kStages) { st = 0; ph ^= 1; }
      }
      store(t - kProjCtas);
      if (warp == 0) TRACE(12 + (t / kProjCtas) * 4 + 3);
      if (wl == 0 && lane == 0) bulk_wait<0>();
      if (threadIdx.x == 0) GT(1);
    } else {
      reg_dec<32>();
      if (lane == 0) {
        mbar_init(bar + 16 * wl, 1);
        mbar_init(bar + 16 * wl + 8, 1);
        mbar_init(bar + 64 + 16 * wl, 12);
        mbar_init(bar + 64 + 16 * wl + 8, 12);
        fence_mbar_init();
      }
      __syncwarp();
      named_bar_sync(0, 512);
      if (wl == 3 && lane == 0) {
        if (DEV_WOD) __nanosleep(DEV_WOD);
        mbar_expect_tx(bar + 56, 3 * kWoBlk);
#pragma unroll 1
        for (int i = 0; i < 3; i++) tma_load_2d(sbase + i * kWoBlk, &tm_wo2, bar + 56, i * 64, 0);
      }
      __syncwarp();
      if (wl == 3 && k < 4) {
        if (lane == 0) {
          const uint32_t e0 = ld_relaxed(&g_epoch[cta * 32 + 3]);
          const uint32_t stg = sA + (kStages - 1) * kOTileBytes;
          mbar_expect_tx(bar + 48, 3 * ka::kWAtom);
#pragma unroll 1
          for (int i = 0; i < 3; i++) tma_load_2d(stg + i * ka::kWAtom, &tm_wo, bar + 48, k * 48 + i * 16, 0);
          mbar_wait(bar + 48, 0);
          bulk_store(g_wop + k * 3 * ka::kWAtom, stg, 3 * ka::kWAtom);
          bulk_commit();
          bulk_wait<0>();
          publish_fence();
          st_relaxed(&g_wflag[k * 32], e0 * 32u + 1);
          st_relaxed(&g_epoch[cta * 32 + 3], e0 + 1);
        }
        __syncwarp();
        named_bar_arrive(2, 64);
      }
      if (wl == 2 && k < 4) named_bar_sync(2, 64);
      if (wl < 3 && lane < 4) {
        const uint32_t e0 = ld_relaxed(&g_epoch[cta * 32 + wl]);
#pragma unroll 1
        for (int it = wl;; it += 3) {
          const int t = k + it * kProjCtas;
          if (t >= kProjTiles) break;
          const int st = it % kStages;
          const int g = t / 28, tp = t - 28 * g;
          uint32_t sp = 0;
          while (true) {
            const bool ok = (int)(ld_acquire(&g_oflag[tp * 32 + lane]) - (e0 * 32u + g + 1)) >= 0;
            if (__all_sync(15u, ok)) break;
            if (DEV_PS) __nanosleep(DEV_PS);
            if (++sp > LIMIT) { BAIL(0x2000000 + t); break; }
          }
          if (it >= kStages) mbar_wait(bar + 64 + 8 * st, ((it / kStages) & 1) ^ 1);
          TRACE(16 + it * 4 + 0);
          if (lane == 0) {
            mbar_expect_tx(bar + 8 * st, kOTileBytes);
            bulk_load(sA + st * kOTileBytes, g_o + (size_t)OIDX(g, tp) * kOTileBytes, kOTileBytes, bar + 8 * st);
          }
          __syncwarp(15u);
        }
        if (lane == 0) st_relaxed(&g_epoch[cta * 32 + wl], e0 + 1);
      }
    }
  }
}

}

namespace {

typedef CUresult (*EncodeTiledFn)(CUtensorMap*, CUtensorMapDataType, cuuint32_t, void*, const cuuint64_t*,
                                  const cuuint64_t*, const cuuint32_t*, const cuuint32_t*, CUtensorMapInterleave,
                                  CUtensorMapSwizzle, CUtensorMapL2promotion, CUtensorMapFloatOOBfill);

EncodeTiledFn get_encode_fn() {
  static EncodeTiledFn fn = nullptr;
  if (!fn) {
    void* p = nullptr;
    cudaDriverEntryPointQueryResult qres;
    if (cudaGetDriverEntryPoint("cuTensorMapEncodeTiled", &p, cudaEnableDefault, &qres) == cudaSuccess)
      fn = reinterpret_cast<EncodeTiledFn>(p);
  }
  return fn;
}

CUtensorMap make_map(void* base, int rank, const cuuint64_t* dims, const cuuint64_t* strides, const cuuint32_t* box,
                     CUtensorMapSwizzle swz) {
  CUtensorMap m;
  cuuint32_t es[5] = {1, 1, 1, 1, 1};
  get_encode_fn()(&m, CU_TENSOR_MAP_DATA_TYPE_BFLOAT16, (cuuint32_t)rank, base, dims, strides, box, es,
                  CU_TENSOR_MAP_INTERLEAVE_NONE, swz, CU_TENSOR_MAP_L2_PROMOTION_L2_128B,
                  CU_TENSOR_MAP_FLOAT_OOB_FILL_NONE);
  return m;
}

}

extern "C" void kernel_launch(void* const* d_in, const int* in_sizes, int n_in, void* d_out, int out_size) {
  using namespace nat;
  (void)in_sizes; (void)n_in; (void)out_size;
  const __nv_bfloat16* x = (const __nv_bfloat16*)d_in[0];
  const __nv_bfloat16* wqkv = (const __nv_bfloat16*)d_in[1];
  const __nv_bfloat16* wo = (const __nv_bfloat16*)d_in[2];
  const __nv_bfloat16* rpb = (const __nv_bfloat16*)d_in[3];
  __nv_bfloat16* out = (__nv_bfloat16*)d_out;

  CUtensorMap tm_x, tm_h, tm_r, tm_w, tm_wo, tm_out, tm_wo2, tm_o2;
  {
    cuuint64_t dims[5] = {64, 112, 112, 6, 2};
    cuuint64_t str[4] = {768, 2ull * 224 * 384, 128, 224ull * 384};
    cuuint32_t box[5] = {64, 16, 4, 3, 1};
    tm_x = make_map((void*)x, 5, dims, str, box, CU_TENSOR_MAP_SWIZZLE_128B);
    cuuint32_t boxh[5] = {64, 3, 5, 1, 1}, boxr[5] = {64, 16, 1, 1, 1};
    tm_h = make_map((void*)x, 5, dims, str, boxh, CU_TENSOR_MAP_SWIZZLE_128B);
    tm_r = make_map((void*)x, 5, dims, str, boxr, CU_TENSOR_MAP_SWIZZLE_128B);
  }
  {
    cuuint64_t dims[2] = {576, 192};
    cuuint64_t str[1] = {1152};
    cuuint32_t box[2] = {16, 192};
    tm_w = make_map((void*)wqkv, 2, dims, str, box, CU_TENSOR_MAP_SWIZZLE_32B);
  }
  {
    cuuint64_t dims[2] = {192, 192};
    cuuint64_t str[1] = {384};
    cuuint32_t box[2] = {16, 192};
    tm_wo = make_map((void*)wo, 2, dims, str, box, CU_TENSOR_MAP_SWIZZLE_32B);
    cuuint32_t box2[2] = {64, 192};
    tm_wo2 = make_map((void*)wo, 2, dims, str, box2, CU_TENSOR_MAP_SWIZZLE_128B);
  }
  {
    cuuint64_t dims[5] = {192, 112, 112, 2, 2};
    cuuint64_t str[4] = {2ull * 224 * 384, 768, 384, 224ull * 384};
    cuuint32_t box[5] = {48, 4, 16, 1, 1};
    tm_out = make_map((void*)out, 5, dims, str, box, CU_TENSOR_MAP_SWIZZLE_NONE);
  }
  {
    cuuint64_t dims[5] = {64, 112, 112, 6, 2};
    cuuint64_t str[4] = {2ull * 224 * 384, 768, 128, 224ull * 384};
    cuuint32_t box[5] = {64, 4, 16, 1, 1};
    tm_o2 = make_map((void*)out, 5, dims, str, box, CU_TENSOR_MAP_SWIZZLE_128B);
  }
  cudaFuncSetAttribute(nat_kernel, cudaFuncAttributeMaxDynamicSharedMemorySize, kSmemBytes);
  nat_kernel<<<kStripCtas + kProjCtas, kThreads, kSmemBytes>>>(wqkv, rpb, tm_x, tm_w, tm_h, tm_r, tm_wo, tm_out, tm_wo2, tm_o2);
}
```

```cpp
#include <cuda_runtime.h>
#include <cuda_bf16.h>
#include <cuda.h>
#include <stdint.h>

#define DEVI __device__ __forceinline__

namespace nat {

DEVI uint32_t smem_u32(const void* p) { return (uint32_t)__cvta_generic_to_shared(p); }

DEVI void mbar_init(uint32_t bar, uint32_t count) {
  asm volatile("mbarrier.init.shared::cta.b64 [%0], %1;" ::"r"(bar), "r"(count) : "memory");
}
DEVI void mbar_expect_tx(uint32_t bar, uint32_t bytes) {
  asm volatile("mbarrier.arrive.expect_tx.shared::cta.b64 _, [%0], %1;" ::"r"(bar), "r"(bytes) : "memory");
}
DEVI void mbar_arrive(uint32_t bar) {
  asm volatile("mbarrier.arrive.shared::cta.b64 _, [%0];" ::"r"(bar) : "memory");
}
DEVI bool mbar_try_wait(uint32_t bar, uint32_t parity) {
  uint32_t ok;
  asm volatile(
      "{\n.reg .pred p;\nmbarrier.try_wait.parity.shared::cta.b64 p, [%1], %2;\nselp.u32 %0, 1, 0, p;\n}\n"
      : "=r"(ok)
      : "r"(bar), "r"(parity)
      : "memory");
  return ok != 0;
}
DEVI bool mbar_test_wait(uint32_t bar, uint32_t parity) {
  uint32_t ok;
  asm volatile(
      "{\n.reg .pred p;\nmbarrier.test_wait.parity.shared::cta.b64 p, [%1], %2;\nselp.u32 %0, 1, 0, p;\n}\n"
      : "=r"(ok)
      : "r"(bar), "r"(parity)
      : "memory");
  return ok != 0;
}
#define BAIL(code) __trap()
#define LIMIT (1u << 20)
DEVI void mbar_wait(uint32_t bar, uint32_t parity) {
  uint32_t it = 0;
  while (!mbar_try_wait(bar, parity)) {
    if (++it > LIMIT) { BAIL(bar & 0xfffff); break; }
  }
}
DEVI void fence_mbar_init() { asm volatile("fence.mbarrier_init.release.cluster;" ::: "memory"); }

DEVI void tma_load_2d(uint32_t dst, const CUtensorMap* tm, uint32_t bar, int c0, int c1) {
  asm volatile(
      "cp.async.bulk.tensor.2d.shared::cluster.global.mbarrier::complete_tx::bytes [%0], [%1, {%3, %4}], [%2];"
      ::"r"(dst), "l"(tm), "r"(bar), "r"(c0), "r"(c1)
      : "memory");
}
DEVI void tma_store_5d(const CUtensorMap* tm, uint32_t src, int c0, int c1, int c2, int c3, int c4) {
  asm volatile("cp.async.bulk.tensor.5d.global.shared::cta.bulk_group [%0, {%2, %3, %4, %5, %6}], [%1];"
               ::"l"(tm), "r"(src), "r"(c0), "r"(c1), "r"(c2), "r"(c3), "r"(c4)
               : "memory");
}
DEVI void bulk_wait_read1() { asm volatile("cp.async.bulk.wait_group.read 1;" ::: "memory"); }
DEVI void bulk_wait_read() { asm volatile("cp.async.bulk.wait_group.read 0;" ::: "memory"); }
DEVI void tma_load_4d(uint32_t dst, const CUtensorMap* tm, uint32_t bar, int c0, int c1, int c2, int c3) {
  asm volatile(
      "cp.async.bulk.tensor.4d.shared::cluster.global.mbarrier::complete_tx::bytes [%0], [%1, {%3, %4, %5, %6}], [%2];"
      ::"r"(dst), "l"(tm), "r"(bar), "r"(c0), "r"(c1), "r"(c2), "r"(c3)
      : "memory");
}
DEVI void tma_load_5d(uint32_t dst, const CUtensorMap* tm, uint32_t bar, int c0, int c1, int c2, int c3, int c4) {
  asm volatile(
      "cp.async.bulk.tensor.5d.shared::cluster.global.mbarrier::complete_tx::bytes [%0], [%1, {%3, %4, %5, %6, %7}], [%2];"
      ::"r"(dst), "l"(tm), "r"(bar), "r"(c0), "r"(c1), "r"(c2), "r"(c3), "r"(c4)
      : "memory");
}
DEVI void tma_load_5d_mc(uint32_t dst, const CUtensorMap* tm, uint32_t bar, int c0, int c1, int c2, int c3, int c4, uint16_t mask) {
  asm volatile(
      "cp.async.bulk.tensor.5d.shared::cluster.global.mbarrier::complete_tx::bytes.multicast::cluster [%0], [%1, {%3, %4, %5, %6, %7}], [%2], %8;"
      ::"r"(dst), "l"(tm), "r"(bar), "r"(c0), "r"(c1), "r"(c2), "r"(c3), "r"(c4), "h"(mask)
      : "memory");
}
DEVI uint32_t mapa(uint32_t addr, uint32_t rank) {
  uint32_t r;
  asm("mapa.shared::cluster.u32 %0, %1, %2;" : "=r"(r) : "r"(addr), "r"(rank));
  return r;
}
DEVI void mbar_arrive_cluster(uint32_t cluster_bar) {
  asm volatile("mbarrier.arrive.shared::cluster.b64 _, [%0];" ::"r"(cluster_bar) : "memory");
}
DEVI void cluster_arrive_relaxed() { asm volatile("barrier.cluster.arrive.relaxed.aligned;" ::: "memory"); }
DEVI void cluster_wait() { asm volatile("barrier.cluster.wait.aligned;" ::: "memory"); }
DEVI void tma_prefetch_5d(const CUtensorMap* tm, int c0, int c1, int c2, int c3, int c4) {
  asm volatile("cp.async.bulk.prefetch.tensor.5d.L2.global [%0, {%1, %2, %3, %4, %5}];"
               ::"l"(tm), "r"(c0), "r"(c1), "r"(c2), "r"(c3), "r"(c4)
               : "memory");
}
DEVI void bulk_load(uint32_t dst, const void* src, uint32_t bytes, uint32_t bar) {
  asm volatile("cp.async.bulk.shared::cluster.global.mbarrier::complete_tx::bytes [%0], [%1], %2, [%3];"
               ::"r"(dst), "l"(src), "r"(bytes), "r"(bar) : "memory");
}
DEVI void bulk_store(void* dst, uint32_t src, uint32_t bytes) {
  asm volatile("cp.async.bulk.global.shared::cta.bulk_group [%0], [%1], %2;" ::"l"(dst), "r"(src), "r"(bytes) : "memory");
}
DEVI void bulk_commit() { asm volatile("cp.async.bulk.commit_group;" ::: "memory"); }
template <int N>
DEVI void bulk_wait() { asm volatile("cp.async.bulk.wait_group %0;" ::"n"(N) : "memory"); }

template <int N>
DEVI void reg_dec() { asm volatile("setmaxnreg.dec.sync.aligned.u32 %0;" ::"n"(N)); }
template <int N>
DEVI void reg_inc() { asm volatile("setmaxnreg.inc.sync.aligned.u32 %0;" ::"n"(N)); }

DEVI void wg_fence() { asm volatile("wgmma.fence.sync.aligned;" ::: "memory"); }
DEVI void wg_commit() { asm volatile("wgmma.commit_group.sync.aligned;" ::: "memory"); }
template <int N>
DEVI void wg_wait() { asm volatile("wgmma.wait_group.sync.aligned %0;" ::"n"(N) : "memory"); }
template <int N>
DEVI void fence_regs(float (&d)[N]) {
#pragma unroll
  for (int i = 0; i < N; i++) asm volatile("" : "+f"(d[i])::"memory");
}

DEVI uint64_t make_desc(uint32_t addr, uint32_t lbo, uint32_t sbo, uint32_t swz) {
  return (uint64_t)((addr & 0x3FFFFu) >> 4) | ((uint64_t)((lbo & 0x3FFFFu) >> 4) << 16) |
         ((uint64_t)((sbo & 0x3FFFFu) >> 4) << 32) | ((uint64_t)swz << 62);
}

DEVI uint64_t desc64(uint32_t lo, uint32_t hi) {
  uint64_t d;
  asm("mov.b64 %0, {%1, %2};" : "=l"(d) : "r"(lo), "r"(hi));
  return d;
}
DEVI uint32_t pack_bf16(float lo, float hi) {
  uint32_t r;
  asm("cvt.rn.bf16x2.f32 %0, %1, %2;" : "=r"(r) : "f"(hi), "f"(lo));
  return r;
}
DEVI float ex2(float x) {
  float r;
  asm("ex2.approx.ftz.f32 %0, %1;" : "=f"(r) : "f"(x));
  return r;
}
DEVI float rcp_approx(float x) {
  float r;
  asm("rcp.approx.ftz.f32 %0, %1;" : "=f"(r) : "f"(x));
  return r;
}
DEVI uint32_t movmatrix_t(uint32_t a) {
  uint32_t r;
  asm("movmatrix.sync.aligned.m8n8.trans.b16 %0, %1;" : "=r"(r) : "r"(a));
  return r;
}
DEVI void ldmatrix_x4(uint32_t (&r)[4], uint32_t addr) {
  asm volatile("ldmatrix.sync.aligned.m8n8.x4.shared.b16 {%0, %1, %2, %3}, [%4];"
               : "=r"(r[0]), "=r"(r[1]), "=r"(r[2]), "=r"(r[3]) : "r"(addr) : "memory");
}
DEVI void ldmatrix_x4(uint32_t& r0, uint32_t& r1, uint32_t& r2, uint32_t& r3, uint32_t addr) {
  asm volatile("ldmatrix.sync.aligned.m8n8.x4.shared.b16 {%0, %1, %2, %3}, [%4];"
               : "=r"(r0), "=r"(r1), "=r"(r2), "=r"(r3) : "r"(addr) : "memory");
}
DEVI void ldmatrix_x2(uint32_t& r0, uint32_t& r1, uint32_t addr) {
  asm volatile("ldmatrix.sync.aligned.m8n8.x2.shared.b16 {%0, %1}, [%2];"
               : "=r"(r0), "=r"(r1) : "r"(addr) : "memory");
}
DEVI void ldmatrix_x4_t(uint32_t (&r)[4], uint32_t addr) {
  asm volatile("ldmatrix.sync.aligned.m8n8.x4.trans.shared.b16 {%0, %1, %2, %3}, [%4];"
               : "=r"(r[0]), "=r"(r[1]), "=r"(r[2]), "=r"(r[3]) : "r"(addr) : "memory");
}
DEVI void stmatrix_x4(uint32_t addr, uint32_t r0, uint32_t r1, uint32_t r2, uint32_t r3) {
  asm volatile("stmatrix.sync.aligned.m8n8.x4.shared.b16 [%0], {%1, %2, %3, %4};"
               ::"r"(addr), "r"(r0), "r"(r1), "r"(r2), "r"(r3) : "memory");
}
DEVI void stmatrix_x4_t(uint32_t addr, uint32_t r0, uint32_t r1, uint32_t r2, uint32_t r3) {
  asm volatile("stmatrix.sync.aligned.m8n8.x4.trans.shared.b16 [%0], {%1, %2, %3, %4};"
               ::"r"(addr), "r"(r0), "r"(r1), "r"(r2), "r"(r3) : "memory");
}
DEVI void mma16816(float (&d)[4], const uint32_t (&a)[4], uint32_t b0, uint32_t b1) {
  asm volatile("mma.sync.aligned.m16n8k16.row.col.f32.bf16.bf16.f32 {%0, %1, %2, %3}, {%4, %5, %6, %7}, {%8, %9}, {%0, %1, %2, %3};"
               : "+f"(d[0]), "+f"(d[1]), "+f"(d[2]), "+f"(d[3])
               : "r"(a[0]), "r"(a[1]), "r"(a[2]), "r"(a[3]), "r"(b0), "r"(b1));
}
DEVI void mma16816_z(float (&d)[4], const uint32_t (&a)[4], uint32_t b0, uint32_t b1) {
  asm volatile("mma.sync.aligned.m16n8k16.row.col.f32.bf16.bf16.f32 {%0, %1, %2, %3}, {%4, %5, %6, %7}, {%8, %9}, {%10, %10, %10, %10};"
               : "=f"(d[0]), "=f"(d[1]), "=f"(d[2]), "=f"(d[3])
               : "r"(a[0]), "r"(a[1]), "r"(a[2]), "r"(a[3]), "r"(b0), "r"(b1), "f"(0.f));
}
DEVI void mma16816_c(float (&d)[4], const uint32_t (&a)[4], uint32_t b0, uint32_t b1, const float (&c)[4]) {
  asm volatile("mma.sync.aligned.m16n8k16.row.col.f32.bf16.bf16.f32 {%0, %1, %2, %3}, {%4, %5, %6, %7}, {%8, %9}, {%10, %11, %12, %13};"
               : "=f"(d[0]), "=f"(d[1]), "=f"(d[2]), "=f"(d[3])
               : "r"(a[0]), "r"(a[1]), "r"(a[2]), "r"(a[3]), "r"(b0), "r"(b1), "f"(c[0]), "f"(c[1]), "f"(c[2]), "f"(c[3]));
}
template <int BIT>
DEVI void sel2(uint32_t mask, float& r0, float& r1, float a0, float a1, float b0, float b1) {
  asm("{\n.reg .pred p;\n.reg .b32 t;\nand.b32 t, %2, %7;\nsetp.ne.b32 p, t, 0;\nselp.f32 %0, %3, %5, p;\nselp.f32 %1, %4, %6, p;\n}"
      : "=f"(r0), "=f"(r1) : "r"(mask), "f"(a0), "f"(a1), "f"(b0), "f"(b1), "n"(BIT));
}
template <int BIT>
DEVI void split2(uint32_t mask, uint32_t& r0, uint32_t& r1, uint32_t v) {
  asm("{\n.reg .pred p;\n.reg .b32 t;\nand.b32 t, %2, %4;\nsetp.ne.b32 p, t, 0;\nselp.b32 %0, %3, 0, p;\nselp.b32 %1, 0, %3, p;\n}"
      : "=r"(r0), "=r"(r1) : "r"(mask), "r"(v), "n"(BIT));
}
DEVI void red_add1(uint32_t* p) {
  asm volatile("red.relaxed.gpu.global.add.u32 [%0], 1;" ::"l"(p) : "memory");
}
DEVI bool named_bar_or(int id, int n, bool v) {
  uint32_t r;
  asm volatile("{\n.reg .pred p, q;\nsetp.ne.u32 p, %1, 0;\nbar.red.or.pred q, %2, %3, p;\nselp.u32 %0, 1, 0, q;\n}"
               : "=r"(r) : "r"((uint32_t)v), "r"(id), "r"(n) : "memory");
  return r != 0;
}
DEVI void cp_async16(uint32_t dst, const void* src) {
  asm volatile("cp.async.cg.shared.global [%0], [%1], 16;" ::"r"(dst), "l"(src) : "memory");
}
DEVI void cp_async_wait_all() { asm volatile("cp.async.wait_all;" ::: "memory"); }
DEVI void stg128(void* p, uint4 v) {
  asm volatile("st.relaxed.gpu.global.v4.u32 [%0], {%1, %2, %3, %4};" ::"l"(p), "r"(v.x), "r"(v.y), "r"(v.z), "r"(v.w) : "memory");
}
DEVI void stg32_if(uint32_t* p, uint32_t v, bool on) {
  asm volatile("{\n.reg .pred q;\nsetp.ne.u32 q, %2, 0;\n@q st.global.u32 [%0], %1;\n}" ::"l"(p), "r"(v), "r"((uint32_t)on) : "memory");
}
DEVI void red_max(uint32_t* p, uint32_t v) {
  asm volatile("red.relaxed.gpu.global.max.u32 [%0], %1;" ::"l"(p), "r"(v) : "memory");
}
DEVI uint4 ldg128(const void* p) {
  uint4 v;
  asm volatile("ld.global.nc.v4.u32 {%0, %1, %2, %3}, [%4];" : "=r"(v.x), "=r"(v.y), "=r"(v.z), "=r"(v.w) : "l"(p));
  return v;
}
DEVI uint32_t ld_acquire(const uint32_t* p) {
  uint32_t v;
  asm volatile("ld.acquire.gpu.global.u32 %0, [%1];" : "=r"(v) : "l"(p) : "memory");
  return v;
}
DEVI uint32_t ld_relaxed(const uint32_t* p) {
  uint32_t v;
  asm volatile("ld.relaxed.gpu.global.u32 %0, [%1];" : "=r"(v) : "l"(p) : "memory");
  return v;
}
DEVI void st_relaxed(uint32_t* p, uint32_t v) {
  asm volatile("st.relaxed.gpu.global.u32 [%0], %1;" ::"l"(p), "r"(v) : "memory");
}
DEVI void st_release(uint32_t* p, uint32_t v) {
  asm volatile("st.release.gpu.global.u32 [%0], %1;" ::"l"(p), "r"(v) : "memory");
}
DEVI void fence_gpu() { asm volatile("fence.acq_rel.gpu;" ::: "memory"); }
DEVI uint32_t lds32(uint32_t addr) {
  uint32_t v;
  asm volatile("ld.shared.u32 %0, [%1];" : "=r"(v) : "r"(addr) : "memory");
  return v;
}
DEVI uint4 lds128(uint32_t addr) {
  uint4 v;
  asm volatile("ld.shared.v4.u32 {%0, %1, %2, %3}, [%4];" : "=r"(v.x), "=r"(v.y), "=r"(v.z), "=r"(v.w) : "r"(addr) : "memory");
  return v;
}
DEVI int lds32v(uint32_t addr) {
  int v;
  asm volatile("ld.volatile.shared.s32 %0, [%1];" : "=r"(v) : "r"(addr) : "memory");
  return v;
}
DEVI void sts32(uint32_t addr, uint32_t v) {
  asm volatile("st.shared.u32 [%0], %1;" ::"r"(addr), "r"(v) : "memory");
}
DEVI void sts128(uint32_t addr, uint4 v) {
  asm volatile("st.shared.v4.u32 [%0], {%1, %2, %3, %4};" ::"r"(addr), "r"(v.x), "r"(v.y), "r"(v.z), "r"(v.w) : "memory");
}
DEVI void named_bar_arrive(int id, int n) { asm volatile("bar.arrive %0, %1;" ::"r"(id), "r"(n) : "memory"); }
DEVI void named_bar_sync(int id, int n) { asm volatile("bar.sync %0, %1;" ::"r"(id), "r"(n) : "memory"); }
DEVI void fence_proxy_async() { asm volatile("fence.proxy.async.shared::cta;" ::: "memory"); }
DEVI void fence_proxy_async_global() { asm volatile("fence.proxy.async.global;" ::: "memory"); }
DEVI int clampi(int v, int lo, int hi) { return v < lo ? lo : (v > hi ? hi : v); }

template <int TA, int TB> DEVI void wgmma_m64n144k16_ss(float (&d)[72], uint64_t descA, uint64_t descB, int scaleD) {
  asm volatile("{\n.reg .pred p;\nsetp.ne.b32 p, %74, 0;\nwgmma.mma_async.sync.aligned.m64n144k16.f32.bf16.bf16 {%0, %1, %2, %3, %4, %5, %6, %7, %8, %9, %10, %11, %12, %13, %14, %15, %16, %17, %18, %19, %20, %21, %22, %23, %24, %25, %26, %27, %28, %29, %30, %31, %32, %33, %34, %35, %36, %37, %38, %39, %40, %41, %42, %43, %44, %45, %46, %47, %48, %49, %50, %51, %52, %53, %54, %55, %56, %57, %58, %59, %60, %61, %62, %63, %64, %65, %66, %67, %68, %69, %70, %71}, %72, %73, p, 1, 1, %75, %76;\n}\n"
    : "+f"(d[0]), "+f"(d[1]), "+f"(d[2]), "+f"(d[3]), "+f"(d[4]), "+f"(d[5]), "+f"(d[6]), "+f"(d[7]), "+f"(d[8]), "+f"(d[9]), "+f"(d[10]), "+f"(d[11]), "+f"(d[12]), "+f"(d[13]), "+f"(d[14]), "+f"(d[15]), "+f"(d[16]), "+f"(d[17]), "+f"(d[18]), "+f"(d[19]), "+f"(d[20]), "+f"(d[21]), "+f"(d[22]), "+f"(d[23]), "+f"(d[24]), "+f"(d[25]), "+f"(d[26]), "+f"(d[27]), "+f"(d[28]), "+f"(d[29]), "+f"(d[30]), "+f"(d[31]), "+f"(d[32]), "+f"(d[33]), "+f"(d[34]), "+f"(d[35]), "+f"(d[36]), "+f"(d[37]), "+f"(d[38]), "+f"(d[39]), "+f"(d[40]), "+f"(d[41]), "+f"(d[42]), "+f"(d[43]), "+f"(d[44]), "+f"(d[45]), "+f"(d[46]), "+f"(d[47]), "+f"(d[48]), "+f"(d[49]), "+f"(d[50]), "+f"(d[51]), "+f"(d[52]), "+f"(d[53]), "+f"(d[54]), "+f"(d[55]), "+f"(d[56]), "+f"(d[57]), "+f"(d[58]), "+f"(d[59]), "+f"(d[60]), "+f"(d[61]), "+f"(d[62]), "+f"(d[63]), "+f"(d[64]), "+f"(d[65]), "+f"(d[66]), "+f"(d[67]), "+f"(d[68]), "+f"(d[69]), "+f"(d[70]), "+f"(d[71])
    : "l"(descA), "l"(descB), "r"(scaleD), "n"(TA), "n"(TB));
}

template <int TB> DEVI void wgmma_m64n64k16_rs(float (&d)[32], uint32_t a0, uint32_t a1, uint32_t a2, uint32_t a3, uint64_t descB, int scaleD) {
  asm volatile("{\n.reg .pred p;\nsetp.ne.b32 p, %37, 0;\nwgmma.mma_async.sync.aligned.m64n64k16.f32.bf16.bf16 {%0, %1, %2, %3, %4, %5, %6, %7, %8, %9, %10, %11, %12, %13, %14, %15, %16, %17, %18, %19, %20, %21, %22, %23, %24, %25, %26, %27, %28, %29, %30, %31}, {%32, %33, %34, %35}, %36, p, 1, 1, %38;\n}\n"
    : "+f"(d[0]), "+f"(d[1]), "+f"(d[2]), "+f"(d[3]), "+f"(d[4]), "+f"(d[5]), "+f"(d[6]), "+f"(d[7]), "+f"(d[8]), "+f"(d[9]), "+f"(d[10]), "+f"(d[11]), "+f"(d[12]), "+f"(d[13]), "+f"(d[14]), "+f"(d[15]), "+f"(d[16]), "+f"(d[17]), "+f"(d[18]), "+f"(d[19]), "+f"(d[20]), "+f"(d[21]), "+f"(d[22]), "+f"(d[23]), "+f"(d[24]), "+f"(d[25]), "+f"(d[26]), "+f"(d[27]), "+f"(d[28]), "+f"(d[29]), "+f"(d[30]), "+f"(d[31])
    : "r"(a0), "r"(a1), "r"(a2), "r"(a3), "l"(descB), "r"(scaleD), "n"(TB));
}

template <int TA, int TB> DEVI void wgmma_m64n48k16_ss(float (&d)[24], uint64_t descA, uint64_t descB, int scaleD) {
  asm volatile("{\n.reg .pred p;\nsetp.ne.b32 p, %26, 0;\nwgmma.mma_async.sync.aligned.m64n48k16.f32.bf16.bf16 {%0, %1, %2, %3, %4, %5, %6, %7, %8, %9, %10, %11, %12, %13, %14, %15, %16, %17, %18, %19, %20, %21, %22, %23}, %24, %25, p, 1, 1, %27, %28;\n}\n"
    : "+f"(d[0]), "+f"(d[1]), "+f"(d[2]), "+f"(d[3]), "+f"(d[4]), "+f"(d[5]), "+f"(d[6]), "+f"(d[7]), "+f"(d[8]), "+f"(d[9]), "+f"(d[10]), "+f"(d[11]), "+f"(d[12]), "+f"(d[13]), "+f"(d[14]), "+f"(d[15]), "+f"(d[16]), "+f"(d[17]), "+f"(d[18]), "+f"(d[19]), "+f"(d[20]), "+f"(d[21]), "+f"(d[22]), "+f"(d[23])
    : "l"(descA), "l"(descB), "r"(scaleD), "n"(TA), "n"(TB));
}

template <int TA, int TB> DEVI void wgmma_m64n96k16_ss(float (&d)[48], uint64_t descA, uint64_t descB, int scaleD) {
  asm volatile("{\n.reg .pred p;\nsetp.ne.b32 p, %50, 0;\nwgmma.mma_async.sync.aligned.m64n96k16.f32.bf16.bf16 {%0, %1, %2, %3, %4, %5, %6, %7, %8, %9, %10, %11, %12, %13, %14, %15, %16, %17, %18, %19, %20, %21, %22, %23, %24, %25, %26, %27, %28, %29, %30, %31, %32, %33, %34, %35, %36, %37, %38, %39, %40, %41, %42, %43, %44, %45, %46, %47}, %48, %49, p, 1, 1, %51, %52;\n}\n"
    : "+f"(d[0]), "+f"(d[1]), "+f"(d[2]), "+f"(d[3]), "+f"(d[4]), "+f"(d[5]), "+f"(d[6]), "+f"(d[7]), "+f"(d[8]), "+f"(d[9]), "+f"(d[10]), "+f"(d[11]), "+f"(d[12]), "+f"(d[13]), "+f"(d[14]), "+f"(d[15]), "+f"(d[16]), "+f"(d[17]), "+f"(d[18]), "+f"(d[19]), "+f"(d[20]), "+f"(d[21]), "+f"(d[22]), "+f"(d[23]), "+f"(d[24]), "+f"(d[25]), "+f"(d[26]), "+f"(d[27]), "+f"(d[28]), "+f"(d[29]), "+f"(d[30]), "+f"(d[31]), "+f"(d[32]), "+f"(d[33]), "+f"(d[34]), "+f"(d[35]), "+f"(d[36]), "+f"(d[37]), "+f"(d[38]), "+f"(d[39]), "+f"(d[40]), "+f"(d[41]), "+f"(d[42]), "+f"(d[43]), "+f"(d[44]), "+f"(d[45]), "+f"(d[46]), "+f"(d[47])
    : "l"(descA), "l"(descB), "r"(scaleD), "n"(TA), "n"(TB));
}

#define DEV_NB 7
#define DEV_D 6
#define DEV_WTMA 2
#define DEV_WOD 2000
#define DEV_PB 7
#define DEV_SEND 0
#define DEV_NV 0
#define DEV_BE 0
#define DEV_ONORM 0
#define DEV_GF 1
#define X_NOV 0
#define X_NOK 0
#define X_NOSH 0
#define X_NOMV 0
#define X_NOST 0
#define X_NOH 0
#define X_NOSTSM 0
#define DEV_ORD 0
#define DEV_HSUM 2
#define DEV_DEPH 24
#define DEV_PS 200
#define PWAIT mbar_wait_sleep
#define DEV_TURN 1
#define DEV_WG 1
#define DEV_GATE 0
#define HPOLL ld_acquire
#define DEV_GG 27
#define DEV_GI 0
#define DEV_OMAJ 1
#define OIDX(g, ps) ((ps) * 28 + (g))
#define OSTEP 1
#define DEV_HMERGE 1
#define DEV_OE 0
#define DEV_F1 1
#define DEV_F2 1
#define DEV_F3 1
#define DEV_F4 1
#define DEV_QD 1
#define DEV_NS 200

constexpr int kS = 112;
constexpr int kStripCtas = 112;
constexpr int kProjCtas = 20;
constexpr int kThreads = 512;
constexpr int kArr = 29;
constexpr int kExch = 27;
constexpr int kSteps = 28;
constexpr int kTiles = kSteps * 28;
constexpr int kOTileBytes = 64 * 192 * 2;
constexpr int kTailBands = DEV_NB;
constexpr int kTail0 = kSteps - kTailBands;
constexpr int kProjTiles = (kSteps - kTailBands) * 28;
constexpr int kHaloBytes = 3 * 784 - 16, kHaloPitch = 2432;

__device__ __align__(1024) uint8_t g_o[(size_t)kTiles * kOTileBytes];
constexpr int kHaloBlock = (2 * kExch + 1) * kHaloPitch;
__device__ __align__(1024) uint8_t g_halo[(size_t)kStripCtas * kHaloBlock];
__device__ __align__(1024) uint8_t g_wop[4 * 3 * 192 * 32];
__device__ uint32_t g_hflag[kStripCtas * 32];
__device__ uint32_t g_oflag[28 * 32];
__device__ uint32_t g_wflag[4 * 32];
__device__ uint32_t g_epoch[132 * 32];

#define HFLAG(c) reinterpret_cast<uint32_t*>(g_halo + (size_t)(c) * kHaloBlock + 2 * kExch * kHaloPitch)
#define HEPOCH(c) (HFLAG(c) + 32)

namespace ka {
constexpr int kWAtom = 192 * 32;
constexpr int kWBytes = 9 * kWAtom;
constexpr int kXBytes = 64 * 384;
constexpr int kCol = 784;
constexpr int kQCol = 400;
constexpr int kSlot = 22 * kCol;
constexpr int kQSlot = 16 * kQCol;
constexpr int kQOff = 5 * kSlot + 32;
constexpr int kOffX = kWBytes;
constexpr int kOffRing = kOffX + 2 * kXBytes;
constexpr int kOffBar = kOffRing + kQOff + 6 * kQSlot;
constexpr int kOffStage = kOffX, kOffWo = kOffX + 2 * kWAtom;
constexpr int kOffDummy = kOffBar + 896;
DEVI uint32_t tail_buf(int i) { return i < 2 ? i * kOTileBytes : kOffRing + (i - 2) * 2 * kSlot; }
constexpr int kLastBytes = 3 * (16 + 2 * 15) * 128;
constexpr int kBarX = 0, kBarFull = 256, kBarO = 512, kBarT = 768, kBarJunk = 896;
constexpr int kSmemBytes = kOffBar + 896 + 704;
constexpr int kD = DEV_D;
static_assert(kD == 5 || kD == 6, "ring");
static_assert(kTailBands <= 8, "buffers");
constexpr int kNbInit = 0, kNbMisc = 1, kNbBurst = 2, kNbTile = 7, kNbFirst = 13, kNbX = 14;
}

namespace kb {
constexpr int kWoBlk = 192 * 128;
constexpr int kStages = 6;
constexpr int kOffA = 3 * kWoBlk;
constexpr int kOffBar = kOffA + kStages * kOTileBytes;
constexpr int kSmemBytes = kOffBar + 128;
}

constexpr int kSmemBytes = ka::kSmemBytes > kb::kSmemBytes ? ka::kSmemBytes : kb::kSmemBytes;
static_assert(kSmemBytes <= 232448, "smem");

#define TRACE(idx)
#define GT(i)
#define ATRACE(k)
#define TRBASE (sbase + kTraceOff)

DEVI void mbar_wait_sleep(uint32_t bar, uint32_t parity) {
  uint32_t it = 0;
  while (!mbar_test_wait(bar, parity)) {
    __nanosleep(DEV_NS);
    if (++it > LIMIT) { BAIL(bar & 0xfffff); break; }
  }
}

DEVI void publish_fence() {
  fence_proxy_async_global();
  fence_gpu();
}

DEVI uint32_t sched_fence() {
  uint32_t t;
  asm volatile("mov.u32 %0, %clock;" : "=r"(t)::"memory");
  return t;
}

struct AttnState {
  uint32_t kf[5][3][4];
  uint32_t vf[5][3][4];
  float bias[5][4];
  uint32_t p[5][2];
  uint32_t kaddr, vaddr, qaddr, bar, junk, fence;
  float sum0, sum1;
  uint32_t ones[4];
  bool rdy;
  uint32_t pm;
  uint32_t* optr;
};

DEVI void store_o(AttnState& s, float (&o)[3][4], float i0, float i1, bool on) {
#pragma unroll
  for (int mt = 0; mt < 3; mt++) {
    stg32_if(s.optr + (2 * mt) * 32, pack_bf16(o[mt][0] * i0, o[mt][1] * i1), on);
    stg32_if(s.optr + (2 * mt + 1) * 32, pack_bf16(o[mt][2] * i0, o[mt][3] * i1), on);
  }
  s.optr += OSTEP * kOTileBytes / 4;
}

template <int PH>
DEVI void attn_step(AttnState& s, int g, int warp, const __nv_bfloat16* __restrict__ rpb) {
  using namespace ka;
  constexpr int R = (2 * PH) % 5, N0 = (R + 3) % 5, N1 = (R + 4) % 5;
  constexpr int SL = ((PH + 1) % 5) * kSlot;
  if (PH == 0 && g == 0) {
    {
      const int lane = threadIdx.x & 31, qc0 = 16 * ((blockIdx.x >> 2) % 7) + 2 * warp;
      const int kc = clampi(qc0 - 3, 0, kS - 8) + (lane >> 2);
      const unsigned short* r = reinterpret_cast<const unsigned short*>(rpb) + (blockIdx.x & 3) * 169 + (3 - (lane & 3)) * 13 + kc - qc0 + 6;
      const int sw0 = clampi(qc0 - 3, 0, kS - 7), sw1 = clampi(qc0 - 2, 0, kS - 7);
      const bool ok0 = kc >= sw0 && kc < sw0 + 7, ok1 = kc >= sw1 && kc < sw1 + 7;
#pragma unroll
      for (int i = 0; i < 10; i++) {
        const uint32_t v0 = ok0 ? (uint32_t)__ldg(r + i * 13) : 0xFF80u;
        const uint32_t v1 = ok1 ? (uint32_t)__ldg(r + i * 13 - 1) : 0xFF80u;
        s.bias[i >> 1][2 * (i & 1)] = __uint_as_float(v0 << 16) * 6.928203230275509f;
        s.bias[i >> 1][2 * (i & 1) + 1] = __uint_as_float(v1 << 16) * 6.928203230275509f;
      }
    }
    named_bar_sync(kNbMisc, 384);
    mbar_wait(s.bar + kBarFull, 0);
#pragma unroll
    for (int k = 0; k < 3; k++) {
      ldmatrix_x4(s.kf[1][k], s.kaddr + k * 32);
      ldmatrix_x4(s.kf[2][k], s.kaddr + 384 + k * 32);
      ldmatrix_x4_t(s.vf[1][k], s.vaddr + k * 32);
      ldmatrix_x4_t(s.vf[2][k], s.vaddr + 384 + k * 32);
      s.vf[0][k][0] = s.vf[0][k][1] = s.vf[0][k][2] = s.vf[0][k][3] = 0u;
    }
    named_bar_arrive(kNbFirst, 384);
  }
  if (!s.rdy) mbar_wait(s.bar + kBarFull + 8 * (g + 1), 0);
  if (DEV_DEPH && PH == DEV_DEPH % 5 && g == DEV_DEPH && warp >= 4) named_bar_sync(kNbInit, 256);
  ATRACE(0);
  float t[5][4], o[3][4], z[4];
  uint32_t q[6];
  const uint32_t (&ones)[4] = s.ones;
#define LDV(n) if (!X_NOV) ldmatrix_x4_t(s.vf[(n) < 3 ? N0 : N1][(n) % 3], s.vaddr + SL + ((n) / 3) * 384 + ((n) % 3) * 32);
#define LDK(n) if (!X_NOK) ldmatrix_x4(s.kf[(n) & 1 ? N1 : N0][(n) >> 1], s.kaddr + SL + ((n) & 1) * 384 + ((n) >> 1) * 32);
#define PV(i) { _Pragma("unroll") for (int mt = 0; mt < 3; mt++) { \
                  if ((i) == 0) mma16816_z(o[mt], s.vf[N0][mt], s.p[0][0], s.p[0][1]); \
                  else mma16816(o[mt], s.vf[(R + 3 + (i)) % 5][mt], s.p[i][0], s.p[i][1]); } \
                if (DEV_HSUM == 1) { if ((i) == 0) mma16816_z(z, ones, s.p[0][0], s.p[0][1]); else mma16816(z, ones, s.p[i][0], s.p[i][1]); } \
                if (DEV_HSUM == 2) { if ((i) == 0) mma16816_z(z, ones, s.p[0][0] | s.p[4][0], s.p[0][1] | s.p[4][1]); \
                                     else if ((i) < 4) mma16816(z, ones, s.p[i][0], s.p[i][1]); } }
#define QK(i, ks) { if ((ks) == 0) mma16816_c(t[i], s.kf[(R + (i)) % 5][0], q[0], q[1], s.bias[i]); \
                    else mma16816(t[i], s.kf[(R + (i)) % 5][ks], q[2 * (ks)], q[2 * (ks) + 1]); }
#define REL named_bar_arrive(kNbBurst + (PH + kD) % 5, 384);
  ldmatrix_x4(q[0], q[1], q[2], q[3], s.qaddr);
  ldmatrix_x2(q[4], q[5], s.qaddr + 64);
  uint32_t f0 = 0, f1, f2, f3 = 0;
  LDK(0) LDK(1) LDK(2) LDK(3) LDK(4) LDK(5)
  PV(0) PV(1) PV(2) PV(3) PV(4)
  f1 = DEV_F1 ? sched_fence() : 0;
  s.junk ^= s.fence;
#pragma unroll
  for (int n = 5; n >= DEV_NV; n--) LDV(n)
#pragma unroll
  for (int n = 0; n < 15 - DEV_BE; n++) QK(n % 5, n / 5)
  f2 = DEV_F2 ? sched_fence() : 0;
  REL
#pragma unroll
  for (int n = 15 - DEV_BE; n < 15; n++) QK(n % 5, n / 5)
  s.fence = DEV_F3 ? sched_fence() : 0;
  if (DEV_DEPH && PH == DEV_DEPH % 5 && g == DEV_DEPH && warp < 4) named_bar_arrive(kNbInit, 256);
  ATRACE(1);
  uint32_t pm = s.pm;
  if (PH == 0 && g == 0) pm &= ~0x3Fu;
  if (PH == 2 && g == kSteps - 1) pm |= 0x3Fu;
  float x[7][2];
  sel2<1>(pm, x[0][0], x[0][1], t[0][0], t[0][1], t[3][2], t[3][3]);
  sel2<2>(pm, x[1][0], x[1][1], t[0][2], t[0][3], t[4][0], t[4][1]);
  sel2<4>(pm, x[2][0], x[2][1], t[1][0], t[1][1], t[4][2], t[4][3]);
#pragma unroll
  for (int e = 0; e < 2; e++) {
    x[3][e] = t[1][2 + e]; x[4][e] = t[2][e]; x[5][e] = t[2][2 + e]; x[6][e] = t[3][e];
  }
  float m0 = fmaxf(fmaxf(fmaxf(x[0][0], x[1][0]), fmaxf(x[2][0], x[3][0])), fmaxf(fmaxf(x[4][0], x[5][0]), x[6][0]));
  float m1 = fmaxf(fmaxf(fmaxf(x[0][1], x[1][1]), fmaxf(x[2][1], x[3][1])), fmaxf(fmaxf(x[4][1], x[5][1]), x[6][1]));
#pragma unroll
  for (int d = 4; d <= (X_NOSH ? 0 : 16); d <<= 1) {
    m0 = fmaxf(m0, __shfl_xor_sync(0xffffffffu, m0, d));
    m1 = fmaxf(m1, __shfl_xor_sync(0xffffffffu, m1, d));
    if (!DEV_HSUM) {
      s.sum0 += __shfl_xor_sync(0xffffffffu, s.sum0, d);
      s.sum1 += __shfl_xor_sync(0xffffffffu, s.sum1, d);
    }
  }
  if (!DEV_HSUM) { z[0] = s.sum0; z[1] = s.sum1; }
  if (DEV_OE) store_o(s, o, rcp_approx(z[0]), rcp_approx(z[1]), PH == 1 || PH == 2 || g > 0);
  uint32_t f4 = 0;
  if (DEV_NV > 0) {
    f4 = DEV_F4 ? sched_fence() : 0;
#pragma unroll
    for (int n = 0; n < DEV_NV; n++) LDV(n)
  }
  s.rdy = PH == 3 && g < 0;
  if (PH < 3 || g >= 0) s.rdy = mbar_test_wait(s.bar + kBarFull + 8 * (g + 2), 0);
  const float c = 0.14433756729740643f * 1.4426950408889634f;
  const float n0 = -m0 * c, n1 = -m1 * c;
  uint32_t pt[7];
#pragma unroll
  for (int i = 0; i < 7; i++) {
    const float e0 = ex2(fmaf(x[i][0], c, n0)), e1 = ex2(fmaf(x[i][1], c, n1));
    if (!DEV_HSUM) {
      s.sum0 = i ? s.sum0 + e0 : e0;
      s.sum1 = i ? s.sum1 + e1 : e1;
    }
    pt[i] = X_NOMV ? pack_bf16(e0, e1) : movmatrix_t(pack_bf16(e0, e1));
  }
  split2<8>(pm, s.p[0][0], s.p[3][1], pt[0]);
  split2<16>(pm, s.p[0][1], s.p[4][0], pt[1]);
  split2<32>(pm, s.p[1][0], s.p[4][1], pt[2]);
  s.p[1][1] = pt[3]; s.p[2][0] = pt[4]; s.p[2][1] = pt[5]; s.p[3][0] = pt[6];
#pragma unroll
  for (int i = 0; i < 5; i++) asm volatile("" : "+r"(s.p[i][0]), "+r"(s.p[i][1])::"memory");
  if (!DEV_HSUM) asm volatile("" : "+f"(s.sum0), "+f"(s.sum1)::"memory");
  if (!DEV_OE) store_o(s, o, rcp_approx(z[0]), rcp_approx(z[1]), PH == 1 || PH == 2 || g > 0);
  __syncwarp();
  if ((s.pm & 64) && (PH < 3 || g >= 0)) mbar_arrive(s.bar + kBarO + 8 * (g - 1));
  s.junk ^= f0 ^ f1 ^ f2 ^ f3;
  s.fence ^= f4;
  s.qaddr += kQSlot;
  if (s.qaddr >= s.bar) s.qaddr -= 6 * kQSlot;
  asm volatile("" : "+r"(s.junk)::"memory");
  ATRACE(2);
}

__global__ void __launch_bounds__(kThreads, 1)
nat_kernel(const __nv_bfloat16* __restrict__ wqkv, const __nv_bfloat16* __restrict__ rpb,
           const __grid_constant__ CUtensorMap tm_x, const __grid_constant__ CUtensorMap tm_w,
           const __grid_constant__ CUtensorMap tm_h, const __grid_constant__ CUtensorMap tm_r,
           const __grid_constant__ CUtensorMap tm_wo, const __grid_constant__ CUtensorMap tm_out,
           const __grid_constant__ CUtensorMap tm_wo2, const __grid_constant__ CUtensorMap tm_o2) {
  extern __shared__ __align__(1024) uint8_t smem_raw[];
  const uint32_t sbase = smem_u32(smem_raw);
  if (sbase & 1023u) __trap();
  const int warp = __shfl_sync(0xffffffffu, (int)(threadIdx.x >> 5), 0), lane = threadIdx.x & 31;
  const int wg = warp >> 2, wl = warp & 3;
  const int cta = blockIdx.x;
  const bool strip_cta = cta < kStripCtas;
  const int head = cta & 3, ps = cta >> 2, par = ps / 7, strip = ps - 7 * par;
  if (threadIdx.x == 0) TRACE(0);

  if (strip_cta && threadIdx.x == 384) {
    using namespace ka;
    const uint32_t bar = sbase + kOffBar;
    mbar_init(bar + kBarX, 1);
    mbar_expect_tx(bar + kBarX, kXBytes + DEV_WTMA * 3 * kWAtom);
    tma_load_5d(sbase + kOffX, &tm_x, bar + kBarX, 0, 16 * strip, -1, 3 * (par & 1), par >> 1);
#pragma unroll
    for (int i = 9 - 3 * DEV_WTMA; i < 9; i++)
      tma_load_2d(sbase + i * kWAtom, &tm_w, bar + kBarX, (i / 3) * 192 + head * 48 + (i % 3) * 16, 0);
    TRACE(10);
  }
  __syncwarp();
  if (DEV_WTMA < 3 && strip_cta && wg == 2 && threadIdx.x < 256 + 96) {
    using namespace ka;
    constexpr int kSec = DEV_WTMA < 3 ? 3 - DEV_WTMA : 1;
    uint4 v[12 * kSec];
    const int wk = ((int)threadIdx.x - 256) / 6, wu = (int)threadIdx.x - 256 - 6 * wk;
    const uint8_t* src = reinterpret_cast<const uint8_t*>(wqkv) + wk * 1152 + head * 96 + wu * 16;
#pragma unroll
    for (int i = 0; i < 12 * kSec; i++) v[i] = ldg128(src + (i / kSec) * 16 * 1152 + (i % kSec) * 384);
    const uint32_t dst = sbase + (wu >> 1) * kWAtom + wk * 32 + (((wu ^ (wk >> 2)) & 1) << 4);
#pragma unroll
    for (int i = 0; i < 12 * kSec; i++) sts128(dst + (i / kSec) * 16 * 32 + (i % kSec) * 3 * kWAtom, v[i]);
    if (warp == 8) TRACE(6);
    fence_proxy_async();
  }
  if (threadIdx.x == 480) GT(0);

  if (strip_cta) {
    using namespace ka;
    const uint32_t bar = sbase + kOffBar, ring = sbase + kOffRing;
    if (wg < 2) {
      if (DEV_WG == 0) named_bar_arrive(kNbX, 416);
      reg_inc<184>();
      AttnState s;
      const int qc0 = 16 * strip + 2 * warp;
      const int kc0 = clampi(qc0 - 3, 0, kS - 8);
      const uint32_t colb = ring + (kc0 - (16 * strip - 3) + (lane & 7)) * kCol;
      s.kaddr = colb + ((lane >> 3) & 1) * 192 + (lane >> 4) * 16;
      s.vaddr = colb + 96 + (lane >> 4) * 192 + ((lane >> 3) & 1) * 16;
      {
        const int qr = (lane & 7) >> 1;
        const uint32_t qa = ring + kQOff + (2 * warp + (lane & 1)) * kQCol + (lane >> 3) * 16;
        s.qaddr = qa + (qr == 3 ? 5 * kQSlot : 4 * kQSlot + (qr + 1) * 96);
      }
      s.bar = bar;
      s.optr = reinterpret_cast<uint32_t*>(g_o + (size_t)OIDX(0, ps) * kOTileBytes + head * 6144 + warp * 768) + lane - 3 * OSTEP * kOTileBytes / 4;
#pragma unroll
      for (int i = 0; i < 5; i++) {
        s.p[i][0] = s.p[i][1] = 0u;
        s.bias[i][0] = s.bias[i][1] = s.bias[i][2] = s.bias[i][3] = 0.f;
#pragma unroll
        for (int k = 0; k < 3; k++)
#pragma unroll
          for (int c = 0; c < 4; c++) s.kf[i][k][c] = s.vf[i][k][c] = 0u;
      }
      s.junk = s.fence = 0;
      s.rdy = true;
#pragma unroll
      for (int i = 0; i < 4; i++) s.ones[i] = __shfl_sync(0xffffffffu, 0x3F803F80u, i);
      s.sum0 = s.sum1 = 1.f;
      s.pm = (7u << (lane & 3) & 7u) | ((7u << (lane >> 3) & 7u) << 3) | (lane == 0 ? 64u : 0u);
      s.pm = __shfl_sync(0xffffffffu, s.pm, lane);
#pragma unroll 1
      for (int g = -2; g < kSteps; g += 5) {
        attn_step<3>(s, g, warp, rpb);
        attn_step<4>(s, g + 1, warp, rpb);
        attn_step<0>(s, g + 2, warp, rpb);
        attn_step<1>(s, g + 3, warp, rpb);
        attn_step<2>(s, g + 4, warp, rpb);
      }
      {
        float o[3][4], z[4];
        const uint32_t (&ones)[4] = s.ones;
#pragma unroll
        for (int mt = 0; mt < 3; mt++) mma16816_z(o[mt], s.vf[4][mt], s.p[0][0], s.p[0][1]);
        mma16816_z(z, ones, s.p[0][0], s.p[0][1]);
#pragma unroll
        for (int i = 1; i < 5; i++) {
#pragma unroll
          for (int mt = 0; mt < 3; mt++) mma16816(o[mt], s.vf[i - 1][mt], s.p[i][0], s.p[i][1]);
          mma16816(z, ones, s.p[i][0], s.p[i][1]);
        }
        store_o(s, o, rcp_approx(z[0]), rcp_approx(z[1]), true);
        __syncwarp();
        if (lane == 0) mbar_arrive(bar + kBarO + 8 * (kSteps - 1));
      }
      s.junk ^= s.fence;
      if (s.junk == 0x9e3779b9u) sts32(bar + kBarJunk, 0);
      if (warp == 0) TRACE(1);
      if (threadIdx.x == 128) GT(3);
    } else if (wg == 2) {
      reg_dec<104>();
      const int col = ((lane >> 3) & 1) * 8 + (lane & 7);
      uint32_t kva = ring + (3 + col) * kCol + wl * 192 + (lane >> 4) * 16;
      uint32_t qa = ring + kQOff + col * kQCol + wl * 96 + (lane >> 4) * 16;
      const uint32_t alo = (uint32_t)make_desc(sbase + kOffX, 16, 1024, 1), blo = (uint32_t)make_desc(sbase, kWAtom, 256, 3);
      constexpr uint32_t ahi = (1u << 30) | (1024 >> 4), bhi = (3u << 30) | (256 >> 4);
      if (wl == 0) TRACE(2);
      uint32_t gj = 0, qprev = 0, qk[12];
#pragma unroll
      for (int j = 0; j < 12; j++) qk[j] = 0;
      int bid = kNbBurst, tid = kNbTile;
      named_bar_arrive(kNbBurst + (kD - 2) % 5, 384);
      named_bar_arrive(kNbBurst + (kD - 1) % 5, 384);
      named_bar_sync(kNbX, DEV_WG ? 160 : 416);
      if (wl == 0) TRACE(7);
      mbar_wait(bar + kBarX, 0);
      if (wl == 0) TRACE(16 + 0);
#pragma unroll 1
      for (int a = 0; a < kArr; a++) {
        float acc[72];
        const uint32_t al = alo + (a & 1) * (kXBytes >> 4);
        if (a >= kD) named_bar_sync(bid, 384);
        if (wl == 0) TRACE(16 + a * 4 + 1);
        wg_fence();
#pragma unroll
        for (int k = 0; k < 12; k++)
          wgmma_m64n144k16_ss<0, 1>(acc, desc64(al + (((k >> 2) * 8192 + (k & 3) * 32) >> 4), ahi), desc64(blo + k * 32, bhi), k != 0);
        wg_commit();
        if (DEV_GF) gj ^= sched_fence();
        if (a > 0) {
#pragma unroll
          for (int j = 0; j < 3; j++) stmatrix_x4(qprev + j * 32, qk[4 * j], qk[4 * j + 1], qk[4 * j + 2], qk[4 * j + 3]);
          __syncwarp();
          if (lane == 0 && a - 1 < kExch) mbar_arrive(bar + kBarFull + 8 * (a - 1));
        }
        bid = bid == kNbBurst + 4 ? kNbBurst : bid + 1;
        if (a == 0) named_bar_sync(kNbInit, 256);
        const bool xok = mbar_test_wait(bar + kBarX + 8 * (a + 1), 0);
        if (a == kArr - 1 && wl != 0) {
          const int r = col / 3, c = col - 3 * r;
          qa = sbase + kOffDummy + lane * 16;
          kva = col < 15 && wl < 3 ? ring + ((kExch + (r >> 2)) % 5) * kSlot + ((wl - 1) * 19 + c) * kCol + (r & 3) * 192 + (lane >> 4) * 16
                                   : qa;
        }
        wg_wait<0>();
        fence_regs(acc);
        named_bar_arrive(kNbX + (a & 1), 160);
        if (kD == 6 && a == 5) named_bar_sync(kNbFirst, 384);
        if (DEV_NV && a >= 6) mbar_wait(bar + kBarO + 8 * (a - 7), 0);
        if (wl == 0) TRACE(16 + a * 4 + 2);
#pragma unroll
        for (int jp = 0; jp < (DEV_QD ? 6 : 9); jp++) {
          const int j = jp < 6 ? jp + 3 : jp - 6;
          if (!X_NOSTSM || acc[8 * j] == 123.f) stmatrix_x4(j < 3 ? qa + j * 32 : kva + (j - 3) * 32, pack_bf16(acc[8 * j + 0], acc[8 * j + 1]),
                      pack_bf16(acc[8 * j + 2], acc[8 * j + 3]), pack_bf16(acc[8 * j + 4], acc[8 * j + 5]),
                      pack_bf16(acc[8 * j + 6], acc[8 * j + 7]));
        }
#pragma unroll
        for (int j = 0; j < 12; j++) qk[j] = pack_bf16(acc[2 * j], acc[2 * j + 1]);
        qprev = qa;
        if (a < kExch) named_bar_arrive(tid, 160);
        tid = tid == kNbTile + 5 ? kNbTile : tid + 1;
        if (wl == 0) TRACE(16 + a * 4 + 3);
        if (!xok && a + 1 < kArr) mbar_wait(bar + kBarX + 8 * (a + 1), 0);
        if (wl == 0) TRACE(16 + (a + 1) * 4 + 0);
        kva += kSlot;
        if (kva >= ring + 5 * kSlot) kva -= 5 * kSlot;
        qa += kQSlot;
        if (qa >= bar) qa -= 6 * kQSlot;
      }
#pragma unroll
      for (int j = 0; j < 3; j++) stmatrix_x4(qprev + j * 32, qk[4 * j], qk[4 * j + 1], qk[4 * j + 2], qk[4 * j + 3]);
      __syncwarp();
      if (lane < kArr - kExch) mbar_arrive(bar + kBarFull + 8 * (kExch + lane));
      if (gj == 0x9e3779b9u) sts32(bar + kBarJunk, 0);
      if (kD == 5) named_bar_arrive(kNbFirst, 384);
#pragma unroll 1
      for (int g = kArr - kD; g < kSteps; g++) {
        if (g != DEV_GG) named_bar_arrive(bid, 384);
        bid = bid == kNbBurst + 4 ? kNbBurst : bid + 1;
      }
      {
        const uint32_t wlo = (uint32_t)make_desc(sbase + kOffWo, kWAtom, 256, 3);
        const int n = lane & 7, j = 2 * wl + ((lane >> 3) & 1);
        const uint32_t sta = sbase + kOffStage + ((2 * j + (n & 1)) * 4 + (n >> 1)) * 96 + (lane >> 4) * 16;
        mbar_wait(bar + kBarX + 8 * kArr, 0);
#pragma unroll 1
        for (int g = kTail0 + ((kTail0 ^ (head >> 1)) & 1), i = 0; g < kSteps; g += 2, i++) {
          float acc[48];
          if (DEV_GG && i == DEV_GI) named_bar_sync(kNbBurst + (DEV_GG + kD) % 5, 384);
          mbar_wait(bar + kBarT + 8 * i, 0);
          if (wl == 0) TRACE(144 + i * 2);
          const uint32_t tlo = (uint32_t)make_desc(sbase + tail_buf(i), 128, 768, 0);
          wg_fence();
#pragma unroll
          for (int k = 0; k < 12; k++)
            wgmma_m64n96k16_ss<1, 1>(acc, desc64(tlo + (((k / 3) * 6144 + (k % 3) * 256) >> 4), 768 >> 4), desc64(wlo + k * 32, bhi), k != 0);
          wg_commit();
          if (threadIdx.x == 256) bulk_wait_read();
          named_bar_sync(kNbMisc, 128);
          wg_wait<0>();
          fence_regs(acc);
#pragma unroll
          for (int jp = 0; jp < 6; jp++)
            stmatrix_x4(sta + (jp / 3) * kWAtom + (jp % 3) * 32, pack_bf16(acc[8 * jp + 0], acc[8 * jp + 1]),
                        pack_bf16(acc[8 * jp + 2], acc[8 * jp + 3]), pack_bf16(acc[8 * jp + 4], acc[8 * jp + 5]),
                        pack_bf16(acc[8 * jp + 6], acc[8 * jp + 7]));
          fence_proxy_async();
          named_bar_sync(kNbMisc, 128);
          if (threadIdx.x == 256) {
            tma_store_5d(&tm_out, sbase + kOffStage, (head & 1) * 96, 4 * g, 16 * strip, par & 1, par >> 1);
            tma_store_5d(&tm_out, sbase + kOffStage + kWAtom, (head & 1) * 96 + 48, 4 * g, 16 * strip, par & 1, par >> 1);
            bulk_commit();
          }
          __syncwarp();
          if (wl == 0) TRACE(145 + i * 2);
        }
        if (threadIdx.x == 256) {
          bulk_wait<0>();
          GT(2);
        }
      }
    } else {
      reg_dec<40>();
      if (wl == 0) named_bar_arrive(kNbX, DEV_WG ? 160 : 416);
      if (lane == 0) {
        const uint32_t b0 = bar + 64 * wl;
        if (wl == 1 && head == 1) tma_prefetch_5d(&tm_x, 0, 16 * strip, 3, 3 * (par & 1), par >> 1);
#pragma unroll
        for (int i = 0; i < 64; i += 8) {
          if (i || wl) mbar_init(b0 + kBarX + i, 1);
          mbar_init(b0 + kBarFull + i, wl < 3 || i < 8 * (kExch - 24) ? (DEV_QD ? 6 : 2) : (i == 56 ? 8 : 4));
          mbar_init(b0 + kBarO + i, 8);
          if (wl == 0 && i < 32) mbar_init(b0 + kBarT + i, 1);
        }
#pragma unroll
        for (int i = 0; i < 64; i += 8) {
          if (i || wl)
            mbar_expect_tx(b0 + kBarX + i, wl < 3 || i < 32 ? kXBytes : (i == 32 ? kLastBytes : 6 * kWAtom));
          if (wl == 0 && i < 32) mbar_expect_tx(bar + kBarT + i, kOTileBytes);
        }
        fence_mbar_init();
        if (wl == 0) {
          tma_load_5d(sbase + kOffX + kXBytes, &tm_x, bar + kBarX + 8, 0, 16 * strip, 3, 3 * (par & 1), par >> 1);
          tma_prefetch_5d(&tm_x, 0, 16 * strip, 4 * (2 + ((head - 2) & 3)) - 1, 3 * (par & 1), par >> 1);
          TRACE(5);
        }
      }
      __syncwarp();
      const uint32_t ep = ld_relaxed(HEPOCH(cta) + wl) * 32u;
      named_bar_arrive(kNbMisc, 384);
      named_bar_sync(kNbInit, 256);
      if (wl == 0) {
#pragma unroll 1
        for (int a = 2; a < kArr - 1; a++) {
          named_bar_sync(kNbX + (a & 1), 160);
          if (lane == 0) {
            tma_load_5d(sbase + kOffX + (a & 1) * kXBytes, &tm_x, bar + kBarX + 8 * a, 0, 16 * strip, 4 * a - 1,
                        3 * (par & 1), par >> 1);
            const int ap = a + 4;
            if (ap < kArr && (ap & 3) == head) tma_prefetch_5d(&tm_x, 0, 16 * strip, 4 * ap - 1, 3 * (par & 1), par >> 1);
          }
          __syncwarp();
        }
        named_bar_sync(kNbX, 160);
        if (lane < 9) {
          const int kb = lane / 3, w = lane - 3 * kb;
          tma_load_5d(sbase + kOffX + kb * 8192 + w * 2048, w == 0 ? &tm_r : &tm_h, bar + kBarX + 8 * (kArr - 1), 0,
                      16 * strip + (w == 0 ? 0 : (w == 1 ? -3 : 16)), w == 0 ? kS - 1 : 4 * kExch - 1, 3 * (par & 1) + kb, par >> 1);
        }
        {
          uint32_t it = 0;
          while (!__all_sync(0xffffffffu, (int)(ld_acquire(&g_wflag[(lane & 3) * 32]) - (ep + 1)) >= 0))
            if (++it > LIMIT) { BAIL(0x5000000); break; }
        }
        const uint8_t* wsrc = g_wop + (head & 1) * 6 * kWAtom;
        named_bar_sync(kNbX + 1, 160);
        if (lane == 0) bulk_load(sbase + kOffWo + 2 * kWAtom, wsrc + 2 * kWAtom, 4 * kWAtom, bar + kBarX + 8 * kArr);
        uint32_t seen = ld_acquire(&g_oflag[ps * 32 + (lane & 3)]);
        named_bar_sync(kNbX, 160);
        if (lane == 0) bulk_load(sbase + kOffWo, wsrc, 2 * kWAtom, bar + kBarX + 8 * kArr);
#pragma unroll 1
        for (int g = kTail0 + ((kTail0 ^ (head >> 1)) & 1), i = 0; g < kSteps; g += 2, i++) {
          uint32_t it = 0;
          while (!__all_sync(0xffffffffu, (int)(seen - (ep + g + 1)) >= 0)) {
            seen = ld_acquire(&g_oflag[ps * 32 + (lane & 3)]);
            if (++it > LIMIT) { BAIL(0x3000000 + g); break; }
          }
          if (lane == 0)
            bulk_load(sbase + tail_buf(i), g_o + (size_t)OIDX(g, ps) * kOTileBytes, kOTileBytes, bar + kBarT + 8 * i);
          __syncwarp();
        }
      } else {
        const int p = wl - 1;
        const bool on = !X_NOH && (lane == 0 ? strip > 0 : strip < 6);
        const int nb = on ? cta + (lane == 0 ? -4 : 4) : cta;
        const uint32_t bytes = X_NOH ? 0 : ((strip > 0 && strip < 6) ? 2 * kHaloBytes : kHaloBytes);
        int slot = p, g = 0;
#pragma unroll 1
        for (int a = p; a < kExch; a += 3) {
          named_bar_sync(kNbTile + a % 6, 160);
          const uint32_t sl = ring + slot * kSlot;
          if (lane < 2) {
            fence_proxy_async();
            if (on) bulk_store(g_halo + (size_t)cta * kHaloBlock + (lane * kExch + a) * kHaloPitch, sl + (3 + 13 * lane) * kCol, kHaloBytes);
            bulk_commit();
          }
          __syncwarp();
          g += __ffs(~__ballot_sync(0xffffffffu, lane < 4 && mbar_test_wait(bar + kBarO + 8 * (g + lane), 0))) - 1;
          __syncwarp();
          if (lane < 2) {
            bulk_wait<0>();
            if (lane == 0) mbar_expect_tx(bar + kBarFull + 8 * a, bytes);
            else mbar_arrive(bar + kBarFull + 8 * a);
            TRACE(160 + a * 4 + 0);
            publish_fence();
            st_relaxed(HFLAG(cta) + 4 * lane + p, ep + a + 1);
            if (lane == 0 && g) red_max(&g_oflag[ps * 32 + head], ep + g);
            TRACE(160 + a * 4 + 1);
            uint32_t it = 0;
            while (true) {
              const bool ok = !on || (int)(HPOLL(HFLAG(nb) + 4 * (lane ^ 1) + p) - (ep + a + 1)) >= 0;
              if (__all_sync(3u, ok)) break;
              if (++it > LIMIT) { BAIL(0x1000000 + a); break; }
            }
            TRACE(160 + a * 4 + 2);
            if (on) bulk_load(sl + lane * 19 * kCol, g_halo + (size_t)nb * kHaloBlock + ((lane ^ 1) * kExch + a) * kHaloPitch, kHaloBytes,
                              bar + kBarFull + 8 * a);
            TRACE(160 + a * 4 + 3);
          }
          __syncwarp();
          slot = slot >= 2 ? slot - 2 : slot + 3;
        }
        if (lane == 0) {
#pragma unroll 1
          for (g = kSteps - DEV_PB + p; g < kSteps; g += 3) {
            if (g < kSteps - 3) mbar_wait_sleep(bar + kBarO + 8 * g, 0);
            else mbar_wait(bar + kBarO + 8 * g, 0);
            TRACE(370 + g * 2);
            publish_fence();
            red_max(&g_oflag[ps * 32 + head], ep + g + 1);
            TRACE(371 + g * 2);
          }
          if (p == (DEV_PB - 1) % 3) GT(1);
        }
      }
      __syncwarp();
      if (lane == 0) st_relaxed(HEPOCH(cta) + wl, (ep >> 5) + 1);
    }
  } else {
    using namespace kb;
    const uint32_t bar = sbase + kOffBar, sA = sbase + kOffA;
    const int k = cta - kStripCtas;
    if (wg < 3) {
      reg_inc<160>();
      named_bar_sync(0, 512);
      uint32_t wf[12][4];
      mbar_wait(bar + 56, 0);
      {
        const int kr = (lane & 7) + ((lane >> 4) << 3);
        const uint32_t wa = sbase + wg * kWoBlk + kr * 128 + (((2 * wl + ((lane >> 3) & 1)) ^ (lane & 7)) << 4);
#pragma unroll
        for (int kk = 0; kk < 12; kk++) ldmatrix_x4_t(wf[kk], wa + kk * 2048);
      }
      named_bar_sync(3 + wg, 128);
      const int px = (2 * (lane >> 4) + (lane & 1)) * 4 + ((lane & 7) >> 1);
      const uint32_t sto = sbase + wg * kWoBlk + px * 128 + (((2 * wl + ((lane >> 3) & 1)) ^ (px & 7)) << 4);
      int st = 0, sb = 0;
      uint32_t ph = 0;
      uint32_t pk[16];
#pragma unroll
      for (int i = 0; i < 16; i++) pk[i] = 0u;
      auto store = [&](int tq) {
        const int g = tq / 28, tp = tq - 28 * g, tpar = tp / 7, tstrip = tp - 7 * tpar;
#pragma unroll
        for (int jp = 0; jp < 4; jp++)
          stmatrix_x4_t(sto + sb * 8192 + jp * 2048, pk[4 * jp], pk[4 * jp + 1], pk[4 * jp + 2], pk[4 * jp + 3]);
        fence_proxy_async();
        if (wl == 0 && lane == 0) bulk_wait_read1();
        named_bar_sync(3 + wg, 128);
        if (wl == 0 && lane == 0 && tq >= 0) {
          tma_store_5d(&tm_o2, sbase + wg * kWoBlk + sb * 8192, 0, 4 * g, 16 * tstrip, 3 * (tpar & 1) + wg, tpar >> 1);
          bulk_commit();
        }
        __syncwarp();
        sb = sb == 2 ? 0 : sb + 1;
      };
      int t = k;
#pragma unroll 1
      for (; t < kProjTiles; t += kProjCtas) {
        float acc[32];
        PWAIT(bar + 8 * st, ph);
        if (warp == 0) TRACE(16 + (t / kProjCtas) * 4 + 1);
        const uint32_t blo = (uint32_t)make_desc(sA + st * kOTileBytes, 128, 768, 0);
        if (DEV_TURN && (t > k || wg)) named_bar_sync(6 + wg, 256);
        wg_fence();
#pragma unroll
        for (int kk = 0; kk < 12; kk++)
          wgmma_m64n64k16_rs<1>(acc, wf[kk][0], wf[kk][1], wf[kk][2], wf[kk][3],
                                desc64(blo + (((kk / 3) * 6144 + (kk % 3) * 256) >> 4), 768 >> 4), kk != 0);
        wg_commit();
        if (DEV_TURN && (wg < 2 || t + kProjCtas < kProjTiles)) named_bar_arrive(6 + (wg == 2 ? 0 : wg + 1), 256);
        store(t - kProjCtas);
        if (warp == 0) TRACE(12 + (t / kProjCtas) * 4 + 3);
        wg_wait<0>();
        fence_regs(acc);
        if (lane == 0) mbar_arrive(bar + 64 + 8 * st);
        if (warp == 0) TRACE(16 + (t / kProjCtas) * 4 + 2);
#pragma unroll
        for (int i = 0; i < 16; i++) pk[i] = pack_bf16(acc[2 * i], acc[2 * i + 1]);
        if (++st == kStages) { st = 0; ph ^= 1; }
      }
      store(t - kProjCtas);
      if (warp == 0) TRACE(12 + (t / kProjCtas) * 4 + 3);
      if (wl == 0 && lane == 0) bulk_wait<0>();
      if (threadIdx.x == 0) GT(1);
    } else {
      reg_dec<32>();
      if (lane == 0) {
        mbar_init(bar + 16 * wl, 1);
        mbar_init(bar + 16 * wl + 8, 1);
        mbar_init(bar + 64 + 16 * wl, 12);
        mbar_init(bar + 64 + 16 * wl + 8, 12);
        fence_mbar_init();
      }
      __syncwarp();
      named_bar_sync(0, 512);
      if (wl == 3 && lane == 0) {
        if (DEV_WOD) __nanosleep(DEV_WOD);
        mbar_expect_tx(bar + 56, 3 * kWoBlk);
#pragma unroll 1
        for (int i = 0; i < 3; i++) tma_load_2d(sbase + i * kWoBlk, &tm_wo2, bar + 56, i * 64, 0);
      }
      __syncwarp();
      if (wl == 3 && k < 4) {
        if (lane == 0) {
          const uint32_t e0 = ld_relaxed(&g_epoch[cta * 32 + 3]);
          const uint32_t stg = sA + (kStages - 1) * kOTileBytes;
          mbar_expect_tx(bar + 48, 3 * ka::kWAtom);
#pragma unroll 1
          for (int i = 0; i < 3; i++) tma_load_2d(stg + i * ka::kWAtom, &tm_wo, bar + 48, k * 48 + i * 16, 0);
          mbar_wait(bar + 48, 0);
          bulk_store(g_wop + k * 3 * ka::kWAtom, stg, 3 * ka::kWAtom);
          bulk_commit();
          bulk_wait<0>();
          publish_fence();
          st_relaxed(&g_wflag[k * 32], e0 * 32u + 1);
          st_relaxed(&g_epoch[cta * 32 + 3], e0 + 1);
        }
        __syncwarp();
        named_bar_arrive(2, 64);
      }
      if (wl == 2 && k < 4) named_bar_sync(2, 64);
      if (wl < 3 && lane < 4) {
        const uint32_t e0 = ld_relaxed(&g_epoch[cta * 32 + wl]);
#pragma unroll 1
        for (int it = wl;; it += 3) {
          const int t = k + it * kProjCtas;
          if (t >= kProjTiles) break;
          const int st = it % kStages;
          const int g = t / 28, tp = t - 28 * g;
          uint32_t sp = 0;
          while (true) {
            const bool ok = (int)(ld_acquire(&g_oflag[tp * 32 + lane]) - (e0 * 32u + g + 1)) >= 0;
            if (__all_sync(15u, ok)) break;
            if (DEV_PS) __nanosleep(DEV_PS);
            if (++sp > LIMIT) { BAIL(0x2000000 + t); break; }
          }
          if (it >= kStages) mbar_wait(bar + 64 + 8 * st, ((it / kStages) & 1) ^ 1);
          TRACE(16 + it * 4 + 0);
          if (lane == 0) {
            mbar_expect_tx(bar + 8 * st, kOTileBytes);
            bulk_load(sA + st * kOTileBytes, g_o + (size_t)OIDX(g, tp) * kOTileBytes, kOTileBytes, bar + 8 * st);
          }
          __syncwarp(15u);
        }
        if (lane == 0) st_relaxed(&g_epoch[cta * 32 + wl], e0 + 1);
      }
    }
  }
}

}

namespace {

typedef CUresult (*EncodeTiledFn)(CUtensorMap*, CUtensorMapDataType, cuuint32_t, void*, const cuuint64_t*,
                                  const cuuint64_t*, const cuuint32_t*, const cuuint32_t*, CUtensorMapInterleave,
                                  CUtensorMapSwizzle, CUtensorMapL2promotion, CUtensorMapFloatOOBfill);

EncodeTiledFn get_encode_fn() {
  static EncodeTiledFn fn = nullptr;
  if (!fn) {
    void* p = nullptr;
    cudaDriverEntryPointQueryResult qres;
    if (cudaGetDriverEntryPoint("cuTensorMapEncodeTiled", &p, cudaEnableDefault, &qres) == cudaSuccess)
      fn = reinterpret_cast<EncodeTiledFn>(p);
  }
  return fn;
}

CUtensorMap make_map(void* base, int rank, const cuuint64_t* dims, const cuuint64_t* strides, const cuuint32_t* box,
                     CUtensorMapSwizzle swz) {
  CUtensorMap m;
  cuuint32_t es[5] = {1, 1, 1, 1, 1};
  get_encode_fn()(&m, CU_TENSOR_MAP_DATA_TYPE_BFLOAT16, (cuuint32_t)rank, base, dims, strides, box, es,
                  CU_TENSOR_MAP_INTERLEAVE_NONE, swz, CU_TENSOR_MAP_L2_PROMOTION_L2_128B,
                  CU_TENSOR_MAP_FLOAT_OOB_FILL_NONE);
  return m;
}

}

extern "C" void kernel_launch(void* const* d_in, const int* in_sizes, int n_in, void* d_out, int out_size) {
  using namespace nat;
  (void)in_sizes; (void)n_in; (void)out_size;
  const __nv_bfloat16* x = (const __nv_bfloat16*)d_in[0];
  const __nv_bfloat16* wqkv = (const __nv_bfloat16*)d_in[1];
  const __nv_bfloat16* wo = (const __nv_bfloat16*)d_in[2];
  const __nv_bfloat16* rpb = (const __nv_bfloat16*)d_in[3];
  __nv_bfloat16* out = (__nv_bfloat16*)d_out;

  CUtensorMap tm_x, tm_h, tm_r, tm_w, tm_wo, tm_out, tm_wo2, tm_o2;
  {
    cuuint64_t dims[5] = {64, 112, 112, 6, 2};
    cuuint64_t str[4] = {768, 2ull * 224 * 384, 128, 224ull * 384};
    cuuint32_t box[5] = {64, 16, 4, 3, 1};
    tm_x = make_map((void*)x, 5, dims, str, box, CU_TENSOR_MAP_SWIZZLE_128B);
    cuuint32_t boxh[5] = {64, 3, 5, 1, 1}, boxr[5] = {64, 16, 1, 1, 1};
    tm_h = make_map((void*)x, 5, dims, str, boxh, CU_TENSOR_MAP_SWIZZLE_128B);
    tm_r = make_map((void*)x, 5, dims, str, boxr, CU_TENSOR_MAP_SWIZZLE_128B);
  }
  {
    cuuint64_t dims[2] = {576, 192};
    cuuint64_t str[1] = {1152};
    cuuint32_t box[2] = {16, 192};
    tm_w = make_map((void*)wqkv, 2, dims, str, box, CU_TENSOR_MAP_SWIZZLE_32B);
  }
  {
    cuuint64_t dims[2] = {192, 192};
    cuuint64_t str[1] = {384};
    cuuint32_t box[2] = {16, 192};
    tm_wo = make_map((void*)wo, 2, dims, str, box, CU_TENSOR_MAP_SWIZZLE_32B);
    cuuint32_t box2[2] = {64, 192};
    tm_wo2 = make_map((void*)wo, 2, dims, str, box2, CU_TENSOR_MAP_SWIZZLE_128B);
  }
  {
    cuuint64_t dims[5] = {192, 112, 112, 2, 2};
    cuuint64_t str[4] = {2ull * 224 * 384, 768, 384, 224ull * 384};
    cuuint32_t box[5] = {48, 4, 16, 1, 1};
    tm_out = make_map((void*)out, 5, dims, str, box, CU_TENSOR_MAP_SWIZZLE_NONE);
  }
  {
    cuuint64_t dims[5] = {64, 112, 112, 6, 2};
    cuuint64_t str[4] = {2ull * 224 * 384, 768, 128, 224ull * 384};
    cuuint32_t box[5] = {64, 4, 16, 1, 1};
    tm_o2 = make_map((void*)out, 5, dims, str, box, CU_TENSOR_MAP_SWIZZLE_128B);
  }
  cudaFuncSetAttribute(nat_kernel, cudaFuncAttributeMaxDynamicSharedMemorySize, kSmemBytes);
  nat_kernel<<<kStripCtas + kProjCtas, kThreads, kSmemBytes>>>(wqkv, rpb, tm_x, tm_w, tm_h, tm_r, tm_wo, tm_out, tm_wo2, tm_o2);
}
```

```cpp
#include <cuda_runtime.h>
#include <cuda_bf16.h>
#include <cuda.h>
#include <stdint.h>

#define DEVI __device__ __forceinline__

namespace nat {

DEVI uint32_t smem_u32(const void* p) { return (uint32_t)__cvta_generic_to_shared(p); }

DEVI void mbar_init(uint32_t bar, uint32_t count) {
  asm volatile("mbarrier.init.shared::cta.b64 [%0], %1;" ::"r"(bar), "r"(count) : "memory");
}
DEVI void mbar_expect_tx(uint32_t bar, uint32_t bytes) {
  asm volatile("mbarrier.arrive.expect_tx.shared::cta.b64 _, [%0], %1;" ::"r"(bar), "r"(bytes) : "memory");
}
DEVI void mbar_arrive(uint32_t bar) {
  asm volatile("mbarrier.arrive.shared::cta.b64 _, [%0];" ::"r"(bar) : "memory");
}
DEVI bool mbar_try_wait(uint32_t bar, uint32_t parity) {
  uint32_t ok;
  asm volatile(
      "{\n.reg .pred p;\nmbarrier.try_wait.parity.shared::cta.b64 p, [%1], %2;\nselp.u32 %0, 1, 0, p;\n}\n"
      : "=r"(ok)
      : "r"(bar), "r"(parity)
      : "memory");
  return ok != 0;
}
DEVI bool mbar_test_wait(uint32_t bar, uint32_t parity) {
  uint32_t ok;
  asm volatile(
      "{\n.reg .pred p;\nmbarrier.test_wait.parity.shared::cta.b64 p, [%1], %2;\nselp.u32 %0, 1, 0, p;\n}\n"
      : "=r"(ok)
      : "r"(bar), "r"(parity)
      : "memory");
  return ok != 0;
}
#define BAIL(code) __trap()
#define LIMIT (1u << 20)
DEVI void mbar_wait(uint32_t bar, uint32_t parity) {
  uint32_t it = 0;
  while (!mbar_try_wait(bar, parity)) {
    if (++it > LIMIT) { BAIL(bar & 0xfffff); break; }
  }
}
DEVI void fence_mbar_init() { asm volatile("fence.mbarrier_init.release.cluster;" ::: "memory"); }

DEVI void tma_load_2d(uint32_t dst, const CUtensorMap* tm, uint32_t bar, int c0, int c1) {
  asm volatile(
      "cp.async.bulk.tensor.2d.shared::cluster.global.mbarrier::complete_tx::bytes [%0], [%1, {%3, %4}], [%2];"
      ::"r"(dst), "l"(tm), "r"(bar), "r"(c0), "r"(c1)
      : "memory");
}
DEVI void tma_store_5d(const CUtensorMap* tm, uint32_t src, int c0, int c1, int c2, int c3, int c4) {
  asm volatile("cp.async.bulk.tensor.5d.global.shared::cta.bulk_group [%0, {%2, %3, %4, %5, %6}], [%1];"
               ::"l"(tm), "r"(src), "r"(c0), "r"(c1), "r"(c2), "r"(c3), "r"(c4)
               : "memory");
}
DEVI void bulk_wait_read1() { asm volatile("cp.async.bulk.wait_group.read 1;" ::: "memory"); }
DEVI void bulk_wait_read() { asm volatile("cp.async.bulk.wait_group.read 0;" ::: "memory"); }
DEVI void tma_load_5d(uint32_t dst, const CUtensorMap* tm, uint32_t bar, int c0, int c1, int c2, int c3, int c4) {
  asm volatile(
      "cp.async.bulk.tensor.5d.shared::cluster.global.mbarrier::complete_tx::bytes [%0], [%1, {%3, %4, %5, %6, %7}], [%2];"
      ::"r"(dst), "l"(tm), "r"(bar), "r"(c0), "r"(c1), "r"(c2), "r"(c3), "r"(c4)
      : "memory");
}
DEVI void tma_prefetch_5d(const CUtensorMap* tm, int c0, int c1, int c2, int c3, int c4) {
  asm volatile("cp.async.bulk.prefetch.tensor.5d.L2.global [%0, {%1, %2, %3, %4, %5}];"
               ::"l"(tm), "r"(c0), "r"(c1), "r"(c2), "r"(c3), "r"(c4)
               : "memory");
}
DEVI void bulk_load(uint32_t dst, const void* src, uint32_t bytes, uint32_t bar) {
  asm volatile("cp.async.bulk.shared::cluster.global.mbarrier::complete_tx::bytes [%0], [%1], %2, [%3];"
               ::"r"(dst), "l"(src), "r"(bytes), "r"(bar) : "memory");
}
DEVI void bulk_store(void* dst, uint32_t src, uint32_t bytes) {
  asm volatile("cp.async.bulk.global.shared::cta.bulk_group [%0], [%1], %2;" ::"l"(dst), "r"(src), "r"(bytes) : "memory");
}
DEVI void bulk_commit() { asm volatile("cp.async.bulk.commit_group;" ::: "memory"); }
template <int N>
DEVI void bulk_wait() { asm volatile("cp.async.bulk.wait_group %0;" ::"n"(N) : "memory"); }

template <int N>
DEVI void reg_dec() { asm volatile("setmaxnreg.dec.sync.aligned.u32 %0;" ::"n"(N)); }
template <int N>
DEVI void reg_inc() { asm volatile("setmaxnreg.inc.sync.aligned.u32 %0;" ::"n"(N)); }

DEVI void wg_fence() { asm volatile("wgmma.fence.sync.aligned;" ::: "memory"); }
DEVI void wg_commit() { asm volatile("wgmma.commit_group.sync.aligned;" ::: "memory"); }
template <int N>
DEVI void wg_wait() { asm volatile("wgmma.wait_group.sync.aligned %0;" ::"n"(N) : "memory"); }
template <int N>
DEVI void fence_regs(float (&d)[N]) {
#pragma unroll
  for (int i = 0; i < N; i++) asm volatile("" : "+f"(d[i])::"memory");
}

DEVI uint64_t make_desc(uint32_t addr, uint32_t lbo, uint32_t sbo, uint32_t swz) {
  return (uint64_t)((addr & 0x3FFFFu) >> 4) | ((uint64_t)((lbo & 0x3FFFFu) >> 4) << 16) |
         ((uint64_t)((sbo & 0x3FFFFu) >> 4) << 32) | ((uint64_t)swz << 62);
}

DEVI uint64_t desc64(uint32_t lo, uint32_t hi) {
  uint64_t d;
  asm("mov.b64 %0, {%1, %2};" : "=l"(d) : "r"(lo), "r"(hi));
  return d;
}
DEVI uint32_t pack_bf16(float lo, float hi) {
  uint32_t r;
  asm("cvt.rn.bf16x2.f32 %0, %1, %2;" : "=r"(r) : "f"(hi), "f"(lo));
  return r;
}
DEVI float ex2(float x) {
  float r;
  asm("ex2.approx.ftz.f32 %0, %1;" : "=f"(r) : "f"(x));
  return r;
}
DEVI float rcp_approx(float x) {
  float r;
  asm("rcp.approx.ftz.f32 %0, %1;" : "=f"(r) : "f"(x));
  return r;
}
DEVI uint32_t movmatrix_t(uint32_t a) {
  uint32_t r;
  asm("movmatrix.sync.aligned.m8n8.trans.b16 %0, %1;" : "=r"(r) : "r"(a));
  return r;
}
DEVI void ldmatrix_x4(uint32_t (&r)[4], uint32_t addr) {
  asm volatile("ldmatrix.sync.aligned.m8n8.x4.shared.b16 {%0, %1, %2, %3}, [%4];"
               : "=r"(r[0]), "=r"(r[1]), "=r"(r[2]), "=r"(r[3]) : "r"(addr) : "memory");
}
DEVI void ldmatrix_x4(uint32_t& r0, uint32_t& r1, uint32_t& r2, uint32_t& r3, uint32_t addr) {
  asm volatile("ldmatrix.sync.aligned.m8n8.x4.shared.b16 {%0, %1, %2, %3}, [%4];"
               : "=r"(r0), "=r"(r1), "=r"(r2), "=r"(r3) : "r"(addr) : "memory");
}
DEVI void ldmatrix_x2(uint32_t& r0, uint32_t& r1, uint32_t addr) {
  asm volatile("ldmatrix.sync.aligned.m8n8.x2.shared.b16 {%0, %1}, [%2];"
               : "=r"(r0), "=r"(r1) : "r"(addr) : "memory");
}
DEVI void ldmatrix_x4_t(uint32_t (&r)[4], uint32_t addr) {
  asm volatile("ldmatrix.sync.aligned.m8n8.x4.trans.shared.b16 {%0, %1, %2, %3}, [%4];"
               : "=r"(r[0]), "=r"(r[1]), "=r"(r[2]), "=r"(r[3]) : "r"(addr) : "memory");
}
DEVI void stmatrix_x4(uint32_t addr, uint32_t r0, uint32_t r1, uint32_t r2, uint32_t r3) {
  asm volatile("stmatrix.sync.aligned.m8n8.x4.shared.b16 [%0], {%1, %2, %3, %4};"
               ::"r"(addr), "r"(r0), "r"(r1), "r"(r2), "r"(r3) : "memory");
}
DEVI void stmatrix_x4_t(uint32_t addr, uint32_t r0, uint32_t r1, uint32_t r2, uint32_t r3) {
  asm volatile("stmatrix.sync.aligned.m8n8.x4.trans.shared.b16 [%0], {%1, %2, %3, %4};"
               ::"r"(addr), "r"(r0), "r"(r1), "r"(r2), "r"(r3) : "memory");
}
DEVI void mma16816(float (&d)[4], const uint32_t (&a)[4], uint32_t b0, uint32_t b1) {
  asm volatile("mma.sync.aligned.m16n8k16.row.col.f32.bf16.bf16.f32 {%0, %1, %2, %3}, {%4, %5, %6, %7}, {%8, %9}, {%0, %1, %2, %3};"
               : "+f"(d[0]), "+f"(d[1]), "+f"(d[2]), "+f"(d[3])
               : "r"(a[0]), "r"(a[1]), "r"(a[2]), "r"(a[3]), "r"(b0), "r"(b1));
}
DEVI void mma16816_z(float (&d)[4], const uint32_t (&a)[4], uint32_t b0, uint32_t b1) {
  asm volatile("mma.sync.aligned.m16n8k16.row.col.f32.bf16.bf16.f32 {%0, %1, %2, %3}, {%4, %5, %6, %7}, {%8, %9}, {%10, %10, %10, %10};"
               : "=f"(d[0]), "=f"(d[1]), "=f"(d[2]), "=f"(d[3])
               : "r"(a[0]), "r"(a[1]), "r"(a[2]), "r"(a[3]), "r"(b0), "r"(b1), "f"(0.f));
}
DEVI void mma16816_c(float (&d)[4], const uint32_t (&a)[4], uint32_t b0, uint32_t b1, const float (&c)[4]) {
  asm volatile("mma.sync.aligned.m16n8k16.row.col.f32.bf16.bf16.f32 {%0, %1, %2, %3}, {%4, %5, %6, %7}, {%8, %9}, {%10, %11, %12, %13};"
               : "=f"(d[0]), "=f"(d[1]), "=f"(d[2]), "=f"(d[3])
               : "r"(a[0]), "r"(a[1]), "r"(a[2]), "r"(a[3]), "r"(b0), "r"(b1), "f"(c[0]), "f"(c[1]), "f"(c[2]), "f"(c[3]));
}
template <int BIT>
DEVI void sel2(uint32_t mask, float& r0, float& r1, float a0, float a1, float b0, float b1) {
  asm("{\n.reg .pred p;\n.reg .b32 t;\nand.b32 t, %2, %7;\nsetp.ne.b32 p, t, 0;\nselp.f32 %0, %3, %5, p;\nselp.f32 %1, %4, %6, p;\n}"
      : "=f"(r0), "=f"(r1) : "r"(mask), "f"(a0), "f"(a1), "f"(b0), "f"(b1), "n"(BIT));
}
template <int BIT>
DEVI void split2(uint32_t mask, uint32_t& r0, uint32_t& r1, uint32_t v) {
  asm("{\n.reg .pred p;\n.reg .b32 t;\nand.b32 t, %2, %4;\nsetp.ne.b32 p, t, 0;\nselp.b32 %0, %3, 0, p;\nselp.b32 %1, 0, %3, p;\n}"
      : "=r"(r0), "=r"(r1) : "r"(mask), "r"(v), "n"(BIT));
}
DEVI void stg32_if(uint32_t* p, uint32_t v, bool on) {
  asm volatile("{\n.reg .pred q;\nsetp.ne.u32 q, %2, 0;\n@q st.global.u32 [%0], %1;\n}" ::"l"(p), "r"(v), "r"((uint32_t)on) : "memory");
}
DEVI void red_max(uint32_t* p, uint32_t v) {
  asm volatile("red.relaxed.gpu.global.max.u32 [%0], %1;" ::"l"(p), "r"(v) : "memory");
}
DEVI uint4 ldg128(const void* p) {
  uint4 v;
  asm volatile("ld.global.nc.v4.u32 {%0, %1, %2, %3}, [%4];" : "=r"(v.x), "=r"(v.y), "=r"(v.z), "=r"(v.w) : "l"(p));
  return v;
}
DEVI uint32_t ld_acquire(const uint32_t* p) {
  uint32_t v;
  asm volatile("ld.acquire.gpu.global.u32 %0, [%1];" : "=r"(v) : "l"(p) : "memory");
  return v;
}
DEVI uint32_t ld_relaxed(const uint32_t* p) {
  uint32_t v;
  asm volatile("ld.relaxed.gpu.global.u32 %0, [%1];" : "=r"(v) : "l"(p) : "memory");
  return v;
}
DEVI void st_relaxed(uint32_t* p, uint32_t v) {
  asm volatile("st.relaxed.gpu.global.u32 [%0], %1;" ::"l"(p), "r"(v) : "memory");
}
DEVI void fence_gpu() { asm volatile("fence.acq_rel.gpu;" ::: "memory"); }
DEVI uint32_t lds32(uint32_t addr) {
  uint32_t v;
  asm volatile("ld.shared.u32 %0, [%1];" : "=r"(v) : "r"(addr) : "memory");
  return v;
}
DEVI uint32_t atom_inc_shared(uint32_t addr) {
  uint32_t v;
  asm volatile("atom.shared.add.u32 %0, [%1], 1;" : "=r"(v) : "r"(addr) : "memory");
  return v;
}
DEVI void sts32(uint32_t addr, uint32_t v) {
  asm volatile("st.shared.u32 [%0], %1;" ::"r"(addr), "r"(v) : "memory");
}
DEVI void sts128(uint32_t addr, uint4 v) {
  asm volatile("st.shared.v4.u32 [%0], {%1, %2, %3, %4};" ::"r"(addr), "r"(v.x), "r"(v.y), "r"(v.z), "r"(v.w) : "memory");
}
DEVI void named_bar_arrive(int id, int n) { asm volatile("bar.arrive %0, %1;" ::"r"(id), "r"(n) : "memory"); }
DEVI void named_bar_sync(int id, int n) { asm volatile("bar.sync %0, %1;" ::"r"(id), "r"(n) : "memory"); }
DEVI void fence_proxy_async() { asm volatile("fence.proxy.async.shared::cta;" ::: "memory"); }
DEVI void fence_proxy_async_global() { asm volatile("fence.proxy.async.global;" ::: "memory"); }
DEVI int clampi(int v, int lo, int hi) { return v < lo ? lo : (v > hi ? hi : v); }

template <int TA, int TB> DEVI void wgmma_m64n144k16_ss(float (&d)[72], uint64_t descA, uint64_t descB, int scaleD) {
  asm volatile("{\n.reg .pred p;\nsetp.ne.b32 p, %74, 0;\nwgmma.mma_async.sync.aligned.m64n144k16.f32.bf16.bf16 {%0, %1, %2, %3, %4, %5, %6, %7, %8, %9, %10, %11, %12, %13, %14, %15, %16, %17, %18, %19, %20, %21, %22, %23, %24, %25, %26, %27, %28, %29, %30, %31, %32, %33, %34, %35, %36, %37, %38, %39, %40, %41, %42, %43, %44, %45, %46, %47, %48, %49, %50, %51, %52, %53, %54, %55, %56, %57, %58, %59, %60, %61, %62, %63, %64, %65, %66, %67, %68, %69, %70, %71}, %72, %73, p, 1, 1, %75, %76;\n}\n"
    : "+f"(d[0]), "+f"(d[1]), "+f"(d[2]), "+f"(d[3]), "+f"(d[4]), "+f"(d[5]), "+f"(d[6]), "+f"(d[7]), "+f"(d[8]), "+f"(d[9]), "+f"(d[10]), "+f"(d[11]), "+f"(d[12]), "+f"(d[13]), "+f"(d[14]), "+f"(d[15]), "+f"(d[16]), "+f"(d[17]), "+f"(d[18]), "+f"(d[19]), "+f"(d[20]), "+f"(d[21]), "+f"(d[22]), "+f"(d[23]), "+f"(d[24]), "+f"(d[25]), "+f"(d[26]), "+f"(d[27]), "+f"(d[28]), "+f"(d[29]), "+f"(d[30]), "+f"(d[31]), "+f"(d[32]), "+f"(d[33]), "+f"(d[34]), "+f"(d[35]), "+f"(d[36]), "+f"(d[37]), "+f"(d[38]), "+f"(d[39]), "+f"(d[40]), "+f"(d[41]), "+f"(d[42]), "+f"(d[43]), "+f"(d[44]), "+f"(d[45]), "+f"(d[46]), "+f"(d[47]), "+f"(d[48]), "+f"(d[49]), "+f"(d[50]), "+f"(d[51]), "+f"(d[52]), "+f"(d[53]), "+f"(d[54]), "+f"(d[55]), "+f"(d[56]), "+f"(d[57]), "+f"(d[58]), "+f"(d[59]), "+f"(d[60]), "+f"(d[61]), "+f"(d[62]), "+f"(d[63]), "+f"(d[64]), "+f"(d[65]), "+f"(d[66]), "+f"(d[67]), "+f"(d[68]), "+f"(d[69]), "+f"(d[70]), "+f"(d[71])
    : "l"(descA), "l"(descB), "r"(scaleD), "n"(TA), "n"(TB));
}

template <int TB> DEVI void wgmma_m64n64k16_rs(float (&d)[32], uint32_t a0, uint32_t a1, uint32_t a2, uint32_t a3, uint64_t descB, int scaleD) {
  asm volatile("{\n.reg .pred p;\nsetp.ne.b32 p, %37, 0;\nwgmma.mma_async.sync.aligned.m64n64k16.f32.bf16.bf16 {%0, %1, %2, %3, %4, %5, %6, %7, %8, %9, %10, %11, %12, %13, %14, %15, %16, %17, %18, %19, %20, %21, %22, %23, %24, %25, %26, %27, %28, %29, %30, %31}, {%32, %33, %34, %35}, %36, p, 1, 1, %38;\n}\n"
    : "+f"(d[0]), "+f"(d[1]), "+f"(d[2]), "+f"(d[3]), "+f"(d[4]), "+f"(d[5]), "+f"(d[6]), "+f"(d[7]), "+f"(d[8]), "+f"(d[9]), "+f"(d[10]), "+f"(d[11]), "+f"(d[12]), "+f"(d[13]), "+f"(d[14]), "+f"(d[15]), "+f"(d[16]), "+f"(d[17]), "+f"(d[18]), "+f"(d[19]), "+f"(d[20]), "+f"(d[21]), "+f"(d[22]), "+f"(d[23]), "+f"(d[24]), "+f"(d[25]), "+f"(d[26]), "+f"(d[27]), "+f"(d[28]), "+f"(d[29]), "+f"(d[30]), "+f"(d[31])
    : "r"(a0), "r"(a1), "r"(a2), "r"(a3), "l"(descB), "r"(scaleD), "n"(TB));
}

template <int TA, int TB> DEVI void wgmma_m64n96k16_ss(float (&d)[48], uint64_t descA, uint64_t descB, int scaleD) {
  asm volatile("{\n.reg .pred p;\nsetp.ne.b32 p, %50, 0;\nwgmma.mma_async.sync.aligned.m64n96k16.f32.bf16.bf16 {%0, %1, %2, %3, %4, %5, %6, %7, %8, %9, %10, %11, %12, %13, %14, %15, %16, %17, %18, %19, %20, %21, %22, %23, %24, %25, %26, %27, %28, %29, %30, %31, %32, %33, %34, %35, %36, %37, %38, %39, %40, %41, %42, %43, %44, %45, %46, %47}, %48, %49, p, 1, 1, %51, %52;\n}\n"
    : "+f"(d[0]), "+f"(d[1]), "+f"(d[2]), "+f"(d[3]), "+f"(d[4]), "+f"(d[5]), "+f"(d[6]), "+f"(d[7]), "+f"(d[8]), "+f"(d[9]), "+f"(d[10]), "+f"(d[11]), "+f"(d[12]), "+f"(d[13]), "+f"(d[14]), "+f"(d[15]), "+f"(d[16]), "+f"(d[17]), "+f"(d[18]), "+f"(d[19]), "+f"(d[20]), "+f"(d[21]), "+f"(d[22]), "+f"(d[23]), "+f"(d[24]), "+f"(d[25]), "+f"(d[26]), "+f"(d[27]), "+f"(d[28]), "+f"(d[29]), "+f"(d[30]), "+f"(d[31]), "+f"(d[32]), "+f"(d[33]), "+f"(d[34]), "+f"(d[35]), "+f"(d[36]), "+f"(d[37]), "+f"(d[38]), "+f"(d[39]), "+f"(d[40]), "+f"(d[41]), "+f"(d[42]), "+f"(d[43]), "+f"(d[44]), "+f"(d[45]), "+f"(d[46]), "+f"(d[47])
    : "l"(descA), "l"(descB), "r"(scaleD), "n"(TA), "n"(TB));
}

constexpr int kS = 112;
constexpr int kStripCtas = 112;
constexpr int kProjCtas = 20;
constexpr int kThreads = 512;
constexpr int kArr = 29;
constexpr int kExch = 27;
constexpr int kSteps = 28;
constexpr int kTiles = kSteps * 28;
constexpr int kOTileBytes = 64 * 192 * 2;
constexpr int kTailBands = 7;
constexpr int kTail0 = kSteps - kTailBands;
constexpr int kProjTiles = (kSteps - kTailBands) * 28;
constexpr int kHaloBytes = 3 * 784 - 16, kHaloPitch = 2432;

__device__ __align__(1024) uint8_t g_o[(size_t)kTiles * kOTileBytes];
constexpr int kHaloBlock = (2 * kExch + 1) * kHaloPitch;
__device__ __align__(1024) uint8_t g_halo[(size_t)kStripCtas * kHaloBlock];
__device__ __align__(1024) uint8_t g_wop[4 * 3 * 192 * 32];
__device__ uint32_t g_oflag[28 * 32];
__device__ uint32_t g_wflag[4 * 32];
__device__ uint32_t g_epoch[kProjCtas * 32];

DEVI uint32_t* halo_flags(int cta) {
  return reinterpret_cast<uint32_t*>(g_halo + (size_t)cta * kHaloBlock + 2 * kExch * kHaloPitch);
}
DEVI const uint8_t* o_tile(int g, int ps) { return g_o + (size_t)(ps * kSteps + g) * kOTileBytes; }

namespace ka {
constexpr int kWAtom = 192 * 32;
constexpr int kWBytes = 9 * kWAtom;
constexpr int kXBytes = 64 * 384;
constexpr int kCol = 784;
constexpr int kQCol = 400;
constexpr int kSlot = 22 * kCol;
constexpr int kQSlot = 16 * kQCol;
constexpr int kQOff = 5 * kSlot + 32;
constexpr int kOffX = kWBytes;
constexpr int kOffRing = kOffX + 2 * kXBytes;
constexpr int kOffBar = kOffRing + kQOff + 6 * kQSlot;
constexpr int kOffStage = kOffX, kOffWo = kOffX + 2 * kWAtom;
constexpr int kOffDummy = kOffBar + 896;
DEVI uint32_t tail_buf(int i) { return i < 2 ? i * kOTileBytes : kOffRing + (i - 2) * 2 * kSlot; }
constexpr int kLastBytes = 3 * (16 + 2 * 15) * 128;
constexpr int kBarX = 0, kBarFull = 256, kBarO = 512, kBarT = 768, kBarJunk = 896;
constexpr int kSmemBytes = kOffBar + 896 + 704;
constexpr int kD = 6;
static_assert(kTailBands <= 8, "buffers");
constexpr int kShift = kArr - kD + 1;
constexpr int kNbInit = 0, kNbMisc = 1, kNbBurst = 2, kNbTile = 7, kNbFirst = 13, kNbX = 14;
}

namespace kb {
constexpr int kWoBlk = 192 * 128;
constexpr int kStages = 6;
constexpr int kOffA = 3 * kWoBlk;
constexpr int kOffBar = kOffA + kStages * kOTileBytes;
constexpr int kSmemBytes = kOffBar + 192;
}

constexpr int kSmemBytes = ka::kSmemBytes > kb::kSmemBytes ? ka::kSmemBytes : kb::kSmemBytes;
static_assert(kSmemBytes <= 232448, "smem");

#define TRACE(idx)
#define GT(i)
#define ATRACE(k)
#define TRBASE (sbase + kTraceOff)

DEVI void mbar_wait_sleep(uint32_t bar, uint32_t parity) {
  uint32_t it = 0;
  while (!mbar_test_wait(bar, parity)) {
    __nanosleep(200);
    if (++it > LIMIT) { BAIL(bar & 0xfffff); break; }
  }
}

DEVI void publish_fence() {
  fence_proxy_async_global();
  fence_gpu();
}

DEVI uint32_t sched_fence() {
  uint32_t t;
  asm volatile("mov.u32 %0, %clock;" : "=r"(t)::"memory");
  return t;
}

struct AttnState {
  uint32_t kf[5][3][4];
  uint32_t vf[5][3][4];
  float bias[5][4];
  uint32_t p[5][2];
  uint32_t kaddr, vaddr, qaddr, bar, junk, fence;
  uint32_t ones[4];
  bool rdy;
  uint32_t pm;
  uint32_t* optr;
};

DEVI void store_o(AttnState& s, float (&o)[3][4], float i0, float i1, bool on) {
#pragma unroll
  for (int mt = 0; mt < 3; mt++) {
    stg32_if(s.optr + (2 * mt) * 32, pack_bf16(o[mt][0] * i0, o[mt][1] * i1), on);
    stg32_if(s.optr + (2 * mt + 1) * 32, pack_bf16(o[mt][2] * i0, o[mt][3] * i1), on);
  }
  s.optr += kOTileBytes / 4;
}

template <int PH>
DEVI void attn_step(AttnState& s, int g, int warp, const __nv_bfloat16* __restrict__ rpb) {
  using namespace ka;
  constexpr int R = (2 * PH) % 5, N0 = (R + 3) % 5, N1 = (R + 4) % 5;
  constexpr int SL = ((PH + 1) % 5) * kSlot;
  if (PH == 0 && g == 0) {
    {
      const int lane = threadIdx.x & 31, qc0 = 16 * ((blockIdx.x >> 2) % 7) + 2 * warp;
      const int kc = clampi(qc0 - 3, 0, kS - 8) + (lane >> 2);
      const unsigned short* r = reinterpret_cast<const unsigned short*>(rpb) + (blockIdx.x & 3) * 169 + (3 - (lane & 3)) * 13 + kc - qc0 + 6;
      const int sw0 = clampi(qc0 - 3, 0, kS - 7), sw1 = clampi(qc0 - 2, 0, kS - 7);
      const bool ok0 = kc >= sw0 && kc < sw0 + 7, ok1 = kc >= sw1 && kc < sw1 + 7;
#pragma unroll
      for (int i = 0; i < 10; i++) {
        const uint32_t v0 = ok0 ? (uint32_t)__ldg(r + i * 13) : 0xFF80u;
        const uint32_t v1 = ok1 ? (uint32_t)__ldg(r + i * 13 - 1) : 0xFF80u;
        s.bias[i >> 1][2 * (i & 1)] = __uint_as_float(v0 << 16) * 6.928203230275509f;
        s.bias[i >> 1][2 * (i & 1) + 1] = __uint_as_float(v1 << 16) * 6.928203230275509f;
      }
    }
    named_bar_sync(kNbMisc, 384);
    mbar_wait(s.bar + kBarFull, 0);
#pragma unroll
    for (int k = 0; k < 3; k++) {
      ldmatrix_x4(s.kf[1][k], s.kaddr + k * 32);
      ldmatrix_x4(s.kf[2][k], s.kaddr + 384 + k * 32);
      ldmatrix_x4_t(s.vf[1][k], s.vaddr + k * 32);
      ldmatrix_x4_t(s.vf[2][k], s.vaddr + 384 + k * 32);
      s.vf[0][k][0] = s.vf[0][k][1] = s.vf[0][k][2] = s.vf[0][k][3] = 0u;
    }
    named_bar_arrive(kNbFirst, 384);
  }
  if (!s.rdy) mbar_wait(s.bar + kBarFull + 8 * (g + 1), 0);
  if (PH == kShift % 5 && g == kShift && warp >= 4) named_bar_sync(kNbInit, 256);
  ATRACE(0);
  float t[5][4], o[3][4], z[4];
  uint32_t q[6];
  ldmatrix_x4(q[0], q[1], q[2], q[3], s.qaddr);
  ldmatrix_x2(q[4], q[5], s.qaddr + 64);
#pragma unroll
  for (int ks = 0; ks < 3; ks++) {
    ldmatrix_x4(s.kf[N0][ks], s.kaddr + SL + ks * 32);
    ldmatrix_x4(s.kf[N1][ks], s.kaddr + SL + 384 + ks * 32);
  }
#pragma unroll
  for (int mt = 0; mt < 3; mt++) mma16816_z(o[mt], s.vf[N0][mt], s.p[0][0], s.p[0][1]);
  mma16816_z(z, s.ones, s.p[0][0] | s.p[4][0], s.p[0][1] | s.p[4][1]);
#pragma unroll
  for (int i = 1; i < 5; i++) {
#pragma unroll
    for (int mt = 0; mt < 3; mt++) mma16816(o[mt], s.vf[(R + 3 + i) % 5][mt], s.p[i][0], s.p[i][1]);
    if (i < 4) mma16816(z, s.ones, s.p[i][0], s.p[i][1]);
  }
  const uint32_t f1 = sched_fence();
  s.junk ^= s.fence;
#pragma unroll
  for (int n = 5; n >= 0; n--) ldmatrix_x4_t(s.vf[n < 3 ? N0 : N1][n % 3], s.vaddr + SL + (n / 3) * 384 + (n % 3) * 32);
#pragma unroll
  for (int i = 0; i < 5; i++) mma16816_c(t[i], s.kf[(R + i) % 5][0], q[0], q[1], s.bias[i]);
#pragma unroll
  for (int ks = 1; ks < 3; ks++) {
#pragma unroll
    for (int i = 0; i < 5; i++) mma16816(t[i], s.kf[(R + i) % 5][ks], q[2 * ks], q[2 * ks + 1]);
  }
  const uint32_t f2 = sched_fence();
  named_bar_arrive(kNbBurst + (PH + kD) % 5, 384);
  s.fence = sched_fence();
  if (PH == kShift % 5 && g == kShift && warp < 4) named_bar_arrive(kNbInit, 256);
  ATRACE(1);
  uint32_t pm = s.pm;
  if (PH == 0 && g == 0) pm &= ~0x3Fu;
  if (PH == 2 && g == kSteps - 1) pm |= 0x3Fu;
  float x[7][2];
  sel2<1>(pm, x[0][0], x[0][1], t[0][0], t[0][1], t[3][2], t[3][3]);
  sel2<2>(pm, x[1][0], x[1][1], t[0][2], t[0][3], t[4][0], t[4][1]);
  sel2<4>(pm, x[2][0], x[2][1], t[1][0], t[1][1], t[4][2], t[4][3]);
#pragma unroll
  for (int e = 0; e < 2; e++) {
    x[3][e] = t[1][2 + e]; x[4][e] = t[2][e]; x[5][e] = t[2][2 + e]; x[6][e] = t[3][e];
  }
  float m0 = fmaxf(fmaxf(fmaxf(x[0][0], x[1][0]), fmaxf(x[2][0], x[3][0])), fmaxf(fmaxf(x[4][0], x[5][0]), x[6][0]));
  float m1 = fmaxf(fmaxf(fmaxf(x[0][1], x[1][1]), fmaxf(x[2][1], x[3][1])), fmaxf(fmaxf(x[4][1], x[5][1]), x[6][1]));
#pragma unroll
  for (int d = 4; d <= 16; d <<= 1) {
    m0 = fmaxf(m0, __shfl_xor_sync(0xffffffffu, m0, d));
    m1 = fmaxf(m1, __shfl_xor_sync(0xffffffffu, m1, d));
  }
  s.rdy = PH == 3 && g < 0;
  if (PH < 3 || g >= 0) s.rdy = mbar_test_wait(s.bar + kBarFull + 8 * (g + 2), 0);
  const float c = 0.14433756729740643f * 1.4426950408889634f;
  const float n0 = -m0 * c, n1 = -m1 * c;
  uint32_t pt[7];
#pragma unroll
  for (int i = 0; i < 7; i++) {
    const float e0 = ex2(fmaf(x[i][0], c, n0)), e1 = ex2(fmaf(x[i][1], c, n1));
    pt[i] = movmatrix_t(pack_bf16(e0, e1));
  }
  split2<8>(pm, s.p[0][0], s.p[3][1], pt[0]);
  split2<16>(pm, s.p[0][1], s.p[4][0], pt[1]);
  split2<32>(pm, s.p[1][0], s.p[4][1], pt[2]);
  s.p[1][1] = pt[3]; s.p[2][0] = pt[4]; s.p[2][1] = pt[5]; s.p[3][0] = pt[6];
#pragma unroll
  for (int i = 0; i < 5; i++) asm volatile("" : "+r"(s.p[i][0]), "+r"(s.p[i][1])::"memory");
  const bool real = PH == 1 || PH == 2 || g > 0;
  store_o(s, o, rcp_approx(z[0]), rcp_approx(z[1]), real);
  __syncwarp();
  if ((s.pm & 64) && real) mbar_arrive(s.bar + kBarO + 8 * (g - 1));
  s.junk ^= f1 ^ f2;
  s.qaddr += kQSlot;
  if (s.qaddr >= s.bar) s.qaddr -= 6 * kQSlot;
  asm volatile("" : "+r"(s.junk)::"memory");
  ATRACE(2);
}

__global__ void __launch_bounds__(kThreads, 1)
nat_kernel(const __nv_bfloat16* __restrict__ wqkv, const __nv_bfloat16* __restrict__ rpb,
           const __grid_constant__ CUtensorMap tm_x, const __grid_constant__ CUtensorMap tm_w,
           const __grid_constant__ CUtensorMap tm_h, const __grid_constant__ CUtensorMap tm_r,
           const __grid_constant__ CUtensorMap tm_wo, const __grid_constant__ CUtensorMap tm_out,
           const __grid_constant__ CUtensorMap tm_wo2, const __grid_constant__ CUtensorMap tm_o2) {
  extern __shared__ __align__(1024) uint8_t smem_raw[];
  const uint32_t sbase = smem_u32(smem_raw);
  if (sbase & 1023u) __trap();
  const int warp = __shfl_sync(0xffffffffu, (int)(threadIdx.x >> 5), 0), lane = threadIdx.x & 31;
  const int wg = warp >> 2, wl = warp & 3;
  const int cta = blockIdx.x;
  const bool strip_cta = cta < kStripCtas;
  const int head = cta & 3, ps = cta >> 2, par = ps / 7, strip = ps - 7 * par;
  if (threadIdx.x == 0) TRACE(0);

  if (strip_cta && threadIdx.x == 384) {
    using namespace ka;
    const uint32_t bar = sbase + kOffBar;
    mbar_init(bar + kBarX, 1);
    mbar_expect_tx(bar + kBarX, kXBytes + 6 * kWAtom);
    tma_load_5d(sbase + kOffX, &tm_x, bar + kBarX, 0, 16 * strip, -1, 3 * (par & 1), par >> 1);
#pragma unroll
    for (int i = 3; i < 9; i++)
      tma_load_2d(sbase + i * kWAtom, &tm_w, bar + kBarX, (i / 3) * 192 + head * 48 + (i % 3) * 16, 0);
    TRACE(10);
  }
  __syncwarp();
  if (strip_cta && wg == 2 && threadIdx.x < 256 + 96) {
    using namespace ka;
    uint4 v[12];
    const int wk = ((int)threadIdx.x - 256) / 6, wu = (int)threadIdx.x - 256 - 6 * wk;
    const uint8_t* src = reinterpret_cast<const uint8_t*>(wqkv) + wk * 1152 + head * 96 + wu * 16;
#pragma unroll
    for (int i = 0; i < 12; i++) v[i] = ldg128(src + i * 16 * 1152);
    const uint32_t dst = sbase + (wu >> 1) * kWAtom + wk * 32 + (((wu ^ (wk >> 2)) & 1) << 4);
#pragma unroll
    for (int i = 0; i < 12; i++) sts128(dst + i * 16 * 32, v[i]);
    if (warp == 8) TRACE(6);
    fence_proxy_async();
  }
  if (threadIdx.x == 480) GT(0);

  if (strip_cta) {
    using namespace ka;
    const uint32_t bar = sbase + kOffBar, ring = sbase + kOffRing;
    if (wg < 2) {
      reg_inc<176>();
      AttnState s;
      const int qc0 = 16 * strip + 2 * warp;
      const int kc0 = clampi(qc0 - 3, 0, kS - 8);
      const uint32_t colb = ring + (kc0 - (16 * strip - 3) + (lane & 7)) * kCol;
      s.kaddr = colb + ((lane >> 3) & 1) * 192 + (lane >> 4) * 16;
      s.vaddr = colb + 96 + (lane >> 4) * 192 + ((lane >> 3) & 1) * 16;
      {
        const int qr = (lane & 7) >> 1;
        const uint32_t qa = ring + kQOff + (2 * warp + (lane & 1)) * kQCol + (lane >> 3) * 16;
        s.qaddr = qa + (qr == 3 ? 5 * kQSlot : 4 * kQSlot + (qr + 1) * 96);
      }
      s.bar = bar;
      s.optr = reinterpret_cast<uint32_t*>(g_o + (size_t)ps * kSteps * kOTileBytes + head * 6144 + warp * 768) + lane - 3 * kOTileBytes / 4;
#pragma unroll
      for (int i = 0; i < 5; i++) {
        s.p[i][0] = s.p[i][1] = 0u;
        s.bias[i][0] = s.bias[i][1] = s.bias[i][2] = s.bias[i][3] = 0.f;
#pragma unroll
        for (int k = 0; k < 3; k++)
#pragma unroll
          for (int c = 0; c < 4; c++) s.kf[i][k][c] = s.vf[i][k][c] = 0u;
      }
      s.junk = s.fence = 0;
      s.rdy = true;
#pragma unroll
      for (int i = 0; i < 4; i++) s.ones[i] = __shfl_sync(0xffffffffu, 0x3F803F80u, i);
      s.pm = (7u << (lane & 3) & 7u) | ((7u << (lane >> 3) & 7u) << 3) | (lane == 0 ? 64u : 0u);
      s.pm = __shfl_sync(0xffffffffu, s.pm, lane);
#pragma unroll 1
      for (int g = -2; g < kSteps; g += 5) {
        attn_step<3>(s, g, warp, rpb);
        attn_step<4>(s, g + 1, warp, rpb);
        attn_step<0>(s, g + 2, warp, rpb);
        attn_step<1>(s, g + 3, warp, rpb);
        attn_step<2>(s, g + 4, warp, rpb);
      }
      {
        float o[3][4], z[4];
#pragma unroll
        for (int mt = 0; mt < 3; mt++) mma16816_z(o[mt], s.vf[4][mt], s.p[0][0], s.p[0][1]);
        mma16816_z(z, s.ones, s.p[0][0], s.p[0][1]);
#pragma unroll
        for (int i = 1; i < 5; i++) {
#pragma unroll
          for (int mt = 0; mt < 3; mt++) mma16816(o[mt], s.vf[i - 1][mt], s.p[i][0], s.p[i][1]);
          mma16816(z, s.ones, s.p[i][0], s.p[i][1]);
        }
        store_o(s, o, rcp_approx(z[0]), rcp_approx(z[1]), true);
        __syncwarp();
        if (lane == 0) mbar_arrive(bar + kBarO + 8 * (kSteps - 1));
      }
      s.junk ^= s.fence;
      if (s.junk == 0x9e3779b9u) sts32(bar + kBarJunk, 0);
      if (warp == 0) TRACE(1);
      if (threadIdx.x == 128) GT(3);
    } else if (wg == 2) {
      reg_dec<120>();
      const int col = ((lane >> 3) & 1) * 8 + (lane & 7);
      uint32_t kva = ring + (3 + col) * kCol + wl * 192 + (lane >> 4) * 16;
      uint32_t qa = ring + kQOff + col * kQCol + wl * 96 + (lane >> 4) * 16;
      const uint32_t alo = (uint32_t)make_desc(sbase + kOffX, 16, 1024, 1), blo = (uint32_t)make_desc(sbase, kWAtom, 256, 3);
      constexpr uint32_t ahi = (1u << 30) | (1024 >> 4), bhi = (3u << 30) | (256 >> 4);
      if (wl == 0) TRACE(2);
      uint32_t gj = 0, qprev = 0, qk[12];
#pragma unroll
      for (int j = 0; j < 12; j++) qk[j] = 0;
      int bid = kNbBurst, tid = kNbTile;
      named_bar_arrive(kNbBurst + (kD - 2) % 5, 384);
      named_bar_arrive(kNbBurst + (kD - 1) % 5, 384);
      named_bar_sync(kNbX, 160);
      if (wl == 0) TRACE(7);
      mbar_wait(bar + kBarX, 0);
      if (wl == 0) TRACE(16 + 0);
#pragma unroll 1
      for (int a = 0; a < kArr; a++) {
        float acc[72];
        const uint32_t al = alo + (a & 1) * (kXBytes >> 4);
        if (a >= kD) named_bar_sync(bid, 384);
        if (wl == 0) TRACE(16 + a * 4 + 1);
        wg_fence();
#pragma unroll
        for (int k = 0; k < 12; k++)
          wgmma_m64n144k16_ss<0, 1>(acc, desc64(al + (((k >> 2) * 8192 + (k & 3) * 32) >> 4), ahi), desc64(blo + k * 32, bhi), k != 0);
        wg_commit();
        gj ^= sched_fence();
        if (a > 0) {
#pragma unroll
          for (int j = 0; j < 3; j++) stmatrix_x4(qprev + j * 32, qk[4 * j], qk[4 * j + 1], qk[4 * j + 2], qk[4 * j + 3]);
          __syncwarp();
          if (lane == 0 && a - 1 < kExch) mbar_arrive(bar + kBarFull + 8 * (a - 1));
        }
        bid = bid == kNbBurst + 4 ? kNbBurst : bid + 1;
        if (a == 0) named_bar_sync(kNbInit, 256);
        const bool xok = mbar_test_wait(bar + kBarX + 8 * (a + 1), 0);
        if (a == kArr - 1 && wl != 0) {
          const int r = col / 3, c = col - 3 * r;
          qa = sbase + kOffDummy + lane * 16;
          kva = col < 15 && wl < 3 ? ring + ((kExch + (r >> 2)) % 5) * kSlot + ((wl - 1) * 19 + c) * kCol + (r & 3) * 192 + (lane >> 4) * 16
                                   : qa;
        }
        wg_wait<0>();
        fence_regs(acc);
        named_bar_arrive(kNbX + (a & 1), 160);
        if (a == 5) named_bar_sync(kNbFirst, 384);
        if (wl == 0) TRACE(16 + a * 4 + 2);
#pragma unroll
        for (int j = 3; j < 9; j++)
          stmatrix_x4(kva + (j - 3) * 32, pack_bf16(acc[8 * j + 0], acc[8 * j + 1]), pack_bf16(acc[8 * j + 2], acc[8 * j + 3]),
                      pack_bf16(acc[8 * j + 4], acc[8 * j + 5]), pack_bf16(acc[8 * j + 6], acc[8 * j + 7]));
#pragma unroll
        for (int j = 0; j < 12; j++) qk[j] = pack_bf16(acc[2 * j], acc[2 * j + 1]);
        qprev = qa;
        if (a < kExch) named_bar_arrive(tid, 160);
        tid = tid == kNbTile + 5 ? kNbTile : tid + 1;
        if (wl == 0) TRACE(16 + a * 4 + 3);
        if (!xok && a + 1 < kArr) mbar_wait(bar + kBarX + 8 * (a + 1), 0);
        if (wl == 0) TRACE(16 + (a + 1) * 4 + 0);
        kva += kSlot;
        if (kva >= ring + 5 * kSlot) kva -= 5 * kSlot;
        qa += kQSlot;
        if (qa >= bar) qa -= 6 * kQSlot;
      }
#pragma unroll
      for (int j = 0; j < 3; j++) stmatrix_x4(qprev + j * 32, qk[4 * j], qk[4 * j + 1], qk[4 * j + 2], qk[4 * j + 3]);
      __syncwarp();
      if (lane < kArr - kExch) mbar_arrive(bar + kBarFull + 8 * (kExch + lane));
      if (gj == 0x9e3779b9u) sts32(bar + kBarJunk, 0);
#pragma unroll 1
      for (int g = kArr - kD; g < kSteps - 1; g++) {
        named_bar_arrive(bid, 384);
        bid = bid == kNbBurst + 4 ? kNbBurst : bid + 1;
      }
      {
        const uint32_t wlo = (uint32_t)make_desc(sbase + kOffWo, kWAtom, 256, 3);
        const int n = lane & 7, j = 2 * wl + ((lane >> 3) & 1);
        const uint32_t sta = sbase + kOffStage + ((2 * j + (n & 1)) * 4 + (n >> 1)) * 96 + (lane >> 4) * 16;
        mbar_wait(bar + kBarX + 8 * kArr, 0);
        named_bar_sync(bid, 384);
#pragma unroll 1
        for (int g = kTail0 + ((kTail0 ^ (head >> 1)) & 1), i = 0; g < kSteps; g += 2, i++) {
          float acc[48];
          mbar_wait(bar + kBarT + 8 * i, 0);
          if (wl == 0) TRACE(144 + i * 2);
          const uint32_t tlo = (uint32_t)make_desc(sbase + tail_buf(i), 128, 768, 0);
          wg_fence();
#pragma unroll
          for (int k = 0; k < 12; k++)
            wgmma_m64n96k16_ss<1, 1>(acc, desc64(tlo + (((k / 3) * 6144 + (k % 3) * 256) >> 4), 768 >> 4), desc64(wlo + k * 32, bhi), k != 0);
          wg_commit();
          if (threadIdx.x == 256) bulk_wait_read();
          named_bar_sync(kNbMisc, 128);
          wg_wait<0>();
          fence_regs(acc);
#pragma unroll
          for (int jp = 0; jp < 6; jp++)
            stmatrix_x4(sta + (jp / 3) * kWAtom + (jp % 3) * 32, pack_bf16(acc[8 * jp + 0], acc[8 * jp + 1]),
                        pack_bf16(acc[8 * jp + 2], acc[8 * jp + 3]), pack_bf16(acc[8 * jp + 4], acc[8 * jp + 5]),
                        pack_bf16(acc[8 * jp + 6], acc[8 * jp + 7]));
          fence_proxy_async();
          named_bar_sync(kNbMisc, 128);
          if (threadIdx.x == 256) {
            tma_store_5d(&tm_out, sbase + kOffStage, (head & 1) * 96, 4 * g, 16 * strip, par & 1, par >> 1);
            tma_store_5d(&tm_out, sbase + kOffStage + kWAtom, (head & 1) * 96 + 48, 4 * g, 16 * strip, par & 1, par >> 1);
            bulk_commit();
          }
          __syncwarp();
          if (wl == 0) TRACE(145 + i * 2);
        }
        if (threadIdx.x == 256) {
          bulk_wait<0>();
          GT(2);
        }
      }
    } else {
      reg_dec<40>();
      if (wl == 0) named_bar_arrive(kNbX, 160);
      if (lane == 0) {
        const uint32_t b0 = bar + 64 * wl;
        if (wl == 1 && head == 1) tma_prefetch_5d(&tm_x, 0, 16 * strip, 3, 3 * (par & 1), par >> 1);
#pragma unroll
        for (int i = 0; i < 64; i += 8) {
          if (i || wl) mbar_init(b0 + kBarX + i, 1);
          mbar_init(b0 + kBarFull + i, wl < 3 || i < 8 * (kExch - 24) ? 6 : 4);
          mbar_init(b0 + kBarO + i, 8);
          if (wl == 0 && i < 32) mbar_init(b0 + kBarT + i, 1);
        }
#pragma unroll
        for (int i = 0; i < 64; i += 8) {
          if (i || wl)
            mbar_expect_tx(b0 + kBarX + i, wl < 3 || i < 32 ? kXBytes : (i == 32 ? kLastBytes : 6 * kWAtom));
          if (wl == 0 && i < 32) mbar_expect_tx(bar + kBarT + i, kOTileBytes);
        }
        fence_mbar_init();
        if (wl == 0) {
          tma_load_5d(sbase + kOffX + kXBytes, &tm_x, bar + kBarX + 8, 0, 16 * strip, 3, 3 * (par & 1), par >> 1);
          tma_prefetch_5d(&tm_x, 0, 16 * strip, 4 * (2 + ((head - 2) & 3)) - 1, 3 * (par & 1), par >> 1);
          TRACE(5);
        }
      }
      __syncwarp();
      const uint32_t ep = ld_relaxed(halo_flags(cta) + 32 + wl) * 32u;
      named_bar_arrive(kNbMisc, 384);
      named_bar_sync(kNbInit, 256);
      if (wl == 0) {
#pragma unroll 1
        for (int a = 2; a < kArr - 1; a++) {
          named_bar_sync(kNbX + (a & 1), 160);
          if (lane == 0) {
            tma_load_5d(sbase + kOffX + (a & 1) * kXBytes, &tm_x, bar + kBarX + 8 * a, 0, 16 * strip, 4 * a - 1,
                        3 * (par & 1), par >> 1);
            const int ap = a + 4;
            if (ap < kArr && (ap & 3) == head) tma_prefetch_5d(&tm_x, 0, 16 * strip, 4 * ap - 1, 3 * (par & 1), par >> 1);
          }
          __syncwarp();
        }
        named_bar_sync(kNbX, 160);
        if (lane < 9) {
          const int kb = lane / 3, w = lane - 3 * kb;
          tma_load_5d(sbase + kOffX + kb * 8192 + w * 2048, w == 0 ? &tm_r : &tm_h, bar + kBarX + 8 * (kArr - 1), 0,
                      16 * strip + (w == 0 ? 0 : (w == 1 ? -3 : 16)), w == 0 ? kS - 1 : 4 * kExch - 1, 3 * (par & 1) + kb, par >> 1);
        }
        {
          uint32_t it = 0;
          while (!__all_sync(0xffffffffu, (int)(ld_acquire(&g_wflag[(lane & 3) * 32]) - (ep + 1)) >= 0))
            if (++it > LIMIT) { BAIL(0x5000000); break; }
        }
        const uint8_t* wsrc = g_wop + (head & 1) * 6 * kWAtom;
        named_bar_sync(kNbX + 1, 160);
        if (lane == 0) bulk_load(sbase + kOffWo + 2 * kWAtom, wsrc + 2 * kWAtom, 4 * kWAtom, bar + kBarX + 8 * kArr);
        uint32_t seen = ld_acquire(&g_oflag[ps * 32 + (lane & 3)]);
        named_bar_sync(kNbX, 160);
        if (lane == 0) bulk_load(sbase + kOffWo, wsrc, 2 * kWAtom, bar + kBarX + 8 * kArr);
#pragma unroll 1
        for (int g = kTail0 + ((kTail0 ^ (head >> 1)) & 1), i = 0; g < kSteps; g += 2, i++) {
          uint32_t it = 0;
          while (!__all_sync(0xffffffffu, (int)(seen - (ep + g + 1)) >= 0)) {
            seen = ld_acquire(&g_oflag[ps * 32 + (lane & 3)]);
            if (++it > LIMIT) { BAIL(0x3000000 + g); break; }
          }
          if (lane == 0)
            bulk_load(sbase + tail_buf(i), o_tile(g, ps), kOTileBytes, bar + kBarT + 8 * i);
          __syncwarp();
        }
      } else {
        const int p = wl - 1;
        const bool on = lane == 0 ? strip > 0 : strip < 6;
        const int nb = on ? cta + (lane == 0 ? -4 : 4) : cta;
        const uint32_t bytes = (strip > 0 && strip < 6) ? 2 * kHaloBytes : kHaloBytes;
        int slot = p, g = 0;
#pragma unroll 1
        for (int a = p; a < kExch; a += 3) {
          named_bar_sync(kNbTile + a % 6, 160);
          const uint32_t sl = ring + slot * kSlot;
          if (lane < 2) {
            fence_proxy_async();
            if (on) bulk_store(g_halo + (size_t)cta * kHaloBlock + (lane * kExch + a) * kHaloPitch, sl + (3 + 13 * lane) * kCol, kHaloBytes);
            bulk_commit();
          }
          __syncwarp();
          g += __ffs(~__ballot_sync(0xffffffffu, lane < 4 && mbar_test_wait(bar + kBarO + 8 * (g + lane), 0))) - 1;
          __syncwarp();
          if (lane < 2) {
            bulk_wait<0>();
            if (lane == 0) mbar_expect_tx(bar + kBarFull + 8 * a, bytes);
            else mbar_arrive(bar + kBarFull + 8 * a);
            TRACE(160 + a * 4 + 0);
            publish_fence();
            st_relaxed(halo_flags(cta) + 4 * lane + p, ep + a + 1);
            if (lane == 0 && g) red_max(&g_oflag[ps * 32 + head], ep + g);
            TRACE(160 + a * 4 + 1);
            uint32_t it = 0;
            while (true) {
              const bool ok = !on || (int)(ld_acquire(halo_flags(nb) + 4 * (lane ^ 1) + p) - (ep + a + 1)) >= 0;
              if (__all_sync(3u, ok)) break;
              if (++it > LIMIT) { BAIL(0x1000000 + a); break; }
            }
            TRACE(160 + a * 4 + 2);
            if (on) bulk_load(sl + lane * 19 * kCol, g_halo + (size_t)nb * kHaloBlock + ((lane ^ 1) * kExch + a) * kHaloPitch, kHaloBytes,
                              bar + kBarFull + 8 * a);
            TRACE(160 + a * 4 + 3);
          }
          __syncwarp();
          slot = slot >= 2 ? slot - 2 : slot + 3;
        }
        if (lane == 0) {
#pragma unroll 1
          for (g = kSteps - 7 + p; g < kSteps; g += 3) {
            if (g < kSteps - 3) mbar_wait_sleep(bar + kBarO + 8 * g, 0);
            else mbar_wait(bar + kBarO + 8 * g, 0);
            TRACE(370 + g * 2);
            publish_fence();
            red_max(&g_oflag[ps * 32 + head], ep + g + 1);
            TRACE(371 + g * 2);
          }
          if (p == 0) GT(1);
        }
      }
      __syncwarp();
      if (lane == 0) st_relaxed(halo_flags(cta) + 32 + wl, (ep >> 5) + 1);
    }
  } else {
    using namespace kb;
    const uint32_t bar = sbase + kOffBar, sA = sbase + kOffA;
    const int k = cta - kStripCtas;
    if (wg < 3) {
      named_bar_sync(0, 512);
      uint32_t wf[12][4];
      mbar_wait(bar + 56, 0);
      {
        const int kr = (lane & 7) + ((lane >> 4) << 3);
        const uint32_t wa = sbase + wg * kWoBlk + kr * 128 + (((2 * wl + ((lane >> 3) & 1)) ^ (lane & 7)) << 4);
#pragma unroll
        for (int kk = 0; kk < 12; kk++) ldmatrix_x4_t(wf[kk], wa + kk * 2048);
      }
      named_bar_sync(3 + wg, 128);
      const int px = (2 * (lane >> 4) + (lane & 1)) * 4 + ((lane & 7) >> 1);
      const uint32_t sto = sbase + wg * kWoBlk + px * 128 + (((2 * wl + ((lane >> 3) & 1)) ^ (px & 7)) << 4);
      int st = 0, sb = 0;
      uint32_t ph = 0;
      uint32_t pk[16];
#pragma unroll
      for (int i = 0; i < 16; i++) pk[i] = 0u;
      auto store = [&](int tq) {
        const int g = tq / 28, tp = tq - 28 * g, tpar = tp / 7, tstrip = tp - 7 * tpar;
#pragma unroll
        for (int jp = 0; jp < 4; jp++)
          stmatrix_x4_t(sto + sb * 8192 + jp * 2048, pk[4 * jp], pk[4 * jp + 1], pk[4 * jp + 2], pk[4 * jp + 3]);
        fence_proxy_async();
        if (wl == 0 && lane == 0) bulk_wait_read1();
        named_bar_sync(3 + wg, 128);
        if (wl == 0 && lane == 0 && tq >= 0) {
          tma_store_5d(&tm_o2, sbase + wg * kWoBlk + sb * 8192, 0, 4 * g, 16 * tstrip, 3 * (tpar & 1) + wg, tpar >> 1);
          bulk_commit();
        }
        __syncwarp();
        sb = sb == 2 ? 0 : sb + 1;
      };
      int t = k, cur = -1;
#pragma unroll 1
      for (; t < kProjTiles; t += kProjCtas) {
        float acc[32];
        mbar_wait(bar + 8 * st, ph);
        if (warp == 0) TRACE(16 + (t / kProjCtas) * 4 + 1);
        const uint32_t blo = (uint32_t)make_desc(sA + st * kOTileBytes, 128, 768, 0);
        if (t > k || wg) named_bar_sync(6 + wg, 256);
        wg_fence();
#pragma unroll
        for (int kk = 0; kk < 12; kk++)
          wgmma_m64n64k16_rs<1>(acc, wf[kk][0], wf[kk][1], wf[kk][2], wf[kk][3],
                                desc64(blo + (((kk / 3) * 6144 + (kk % 3) * 256) >> 4), 768 >> 4), kk != 0);
        wg_commit();
        if (wg < 2 || t + kProjCtas < kProjTiles) named_bar_arrive(6 + (wg == 2 ? 0 : wg + 1), 256);
        const int nxt = (int)lds32(bar + 128 + 4 * st);
        store(cur);
        cur = nxt;
        if (warp == 0) TRACE(12 + (t / kProjCtas) * 4 + 3);
        wg_wait<0>();
        fence_regs(acc);
        if (lane == 0) mbar_arrive(bar + 64 + 8 * st);
        if (warp == 0) TRACE(16 + (t / kProjCtas) * 4 + 2);
#pragma unroll
        for (int i = 0; i < 16; i++) pk[i] = pack_bf16(acc[2 * i], acc[2 * i + 1]);
        if (++st == kStages) { st = 0; ph ^= 1; }
      }
      store(cur);
      if (warp == 0) TRACE(12 + (t / kProjCtas) * 4 + 3);
      if (wl == 0 && lane == 0) bulk_wait<0>();
      if (threadIdx.x == 0) GT(1);
    } else {
      if (lane == 0) {
        mbar_init(bar + 16 * wl, 1);
        mbar_init(bar + 16 * wl + 8, 1);
        mbar_init(bar + 64 + 16 * wl, 12);
        mbar_init(bar + 64 + 16 * wl + 8, 12);
        sts32(bar + 160, 0);
        fence_mbar_init();
      }
      __syncwarp();
      named_bar_sync(0, 512);
      if (wl == 3 && lane == 0) {
        __nanosleep(2000);
        mbar_expect_tx(bar + 56, 3 * kWoBlk);
#pragma unroll 1
        for (int i = 0; i < 3; i++) tma_load_2d(sbase + i * kWoBlk, &tm_wo2, bar + 56, i * 64, 0);
      }
      __syncwarp();
      if (wl == 3 && k < 4) {
        if (lane == 0) {
          const uint32_t e0 = ld_relaxed(&g_epoch[k * 32 + 3]);
          const uint32_t stg = sA + (kStages - 1) * kOTileBytes;
          mbar_expect_tx(bar + 48, 3 * ka::kWAtom);
#pragma unroll 1
          for (int i = 0; i < 3; i++) tma_load_2d(stg + i * ka::kWAtom, &tm_wo, bar + 48, k * 48 + i * 16, 0);
          mbar_wait(bar + 48, 0);
          bulk_store(g_wop + k * 3 * ka::kWAtom, stg, 3 * ka::kWAtom);
          bulk_commit();
          bulk_wait<0>();
          publish_fence();
          st_relaxed(&g_wflag[k * 32], e0 * 32u + 1);
          st_relaxed(&g_epoch[k * 32 + 3], e0 + 1);
        }
        __syncwarp();
        named_bar_arrive(2, 128);
      }
      if (wl < 3 && k < 4) named_bar_sync(2, 128);
      if (wl < 3 && lane < 4) {
        const uint32_t e0 = ld_relaxed(&g_epoch[k * 32 + wl]);
#pragma unroll 1
        for (int it = wl;; it += 3) {
          const int t = k + it * kProjCtas;
          if (t >= kProjTiles) break;
          const int g = t / 28, tp = t - 28 * g;
          uint32_t sp = 0;
          while (true) {
            const bool ok = (int)(ld_acquire(&g_oflag[tp * 32 + lane]) - (e0 * 32u + g + 1)) >= 0;
            if (__all_sync(15u, ok)) break;
            if (++sp > LIMIT) { BAIL(0x2000000 + t); break; }
          }
          if (lane == 0) {
            const int n = (int)atom_inc_shared(bar + 160), st = n % kStages;
            if (n >= kStages) mbar_wait(bar + 64 + 8 * st, ((n / kStages) & 1) ^ 1);
            TRACE(16 + n * 4 + 0);
            sts32(bar + 128 + 4 * st, t);
            mbar_expect_tx(bar + 8 * st, kOTileBytes);
            bulk_load(sA + st * kOTileBytes, o_tile(g, tp), kOTileBytes, bar + 8 * st);
          }
          __syncwarp(15u);
        }
        if (lane == 0) st_relaxed(&g_epoch[k * 32 + wl], e0 + 1);
      }
    }
  }
}

}

namespace {

typedef CUresult (*EncodeTiledFn)(CUtensorMap*, CUtensorMapDataType, cuuint32_t, void*, const cuuint64_t*,
                                  const cuuint64_t*, const cuuint32_t*, const cuuint32_t*, CUtensorMapInterleave,
                                  CUtensorMapSwizzle, CUtensorMapL2promotion, CUtensorMapFloatOOBfill);

EncodeTiledFn get_encode_fn() {
  static EncodeTiledFn fn = nullptr;
  if (!fn) {
    void* p = nullptr;
    cudaDriverEntryPointQueryResult qres;
    if (cudaGetDriverEntryPoint("cuTensorMapEncodeTiled", &p, cudaEnableDefault, &qres) == cudaSuccess)
      fn = reinterpret_cast<EncodeTiledFn>(p);
  }
  return fn;
}

CUtensorMap make_map(void* base, int rank, const cuuint64_t* dims, const cuuint64_t* strides, const cuuint32_t* box,
                     CUtensorMapSwizzle swz) {
  CUtensorMap m;
  cuuint32_t es[5] = {1, 1, 1, 1, 1};
  get_encode_fn()(&m, CU_TENSOR_MAP_DATA_TYPE_BFLOAT16, (cuuint32_t)rank, base, dims, strides, box, es,
                  CU_TENSOR_MAP_INTERLEAVE_NONE, swz, CU_TENSOR_MAP_L2_PROMOTION_L2_128B,
                  CU_TENSOR_MAP_FLOAT_OOB_FILL_NONE);
  return m;
}

}

extern "C" void kernel_launch(void* const* d_in, const int* in_sizes, int n_in, void* d_out, int out_size) {
  using namespace nat;
  (void)in_sizes; (void)n_in; (void)out_size;
  const __nv_bfloat16* x = (const __nv_bfloat16*)d_in[0];
  const __nv_bfloat16* wqkv = (const __nv_bfloat16*)d_in[1];
  const __nv_bfloat16* wo = (const __nv_bfloat16*)d_in[2];
  const __nv_bfloat16* rpb = (const __nv_bfloat16*)d_in[3];
  __nv_bfloat16* out = (__nv_bfloat16*)d_out;

  CUtensorMap tm_x, tm_h, tm_r, tm_w, tm_wo, tm_out, tm_wo2, tm_o2;
  {
    cuuint64_t dims[5] = {64, 112, 112, 6, 2};
    cuuint64_t str[4] = {768, 2ull * 224 * 384, 128, 224ull * 384};
    cuuint32_t box[5] = {64, 16, 4, 3, 1};
    tm_x = make_map((void*)x, 5, dims, str, box, CU_TENSOR_MAP_SWIZZLE_128B);
    cuuint32_t boxh[5] = {64, 3, 5, 1, 1}, boxr[5] = {64, 16, 1, 1, 1};
    tm_h = make_map((void*)x, 5, dims, str, boxh, CU_TENSOR_MAP_SWIZZLE_128B);
    tm_r = make_map((void*)x, 5, dims, str, boxr, CU_TENSOR_MAP_SWIZZLE_128B);
  }
  {
    cuuint64_t dims[2] = {576, 192};
    cuuint64_t str[1] = {1152};
    cuuint32_t box[2] = {16, 192};
    tm_w = make_map((void*)wqkv, 2, dims, str, box, CU_TENSOR_MAP_SWIZZLE_32B);
  }
  {
    cuuint64_t dims[2] = {192, 192};
    cuuint64_t str[1] = {384};
    cuuint32_t box[2] = {16, 192};
    tm_wo = make_map((void*)wo, 2, dims, str, box, CU_TENSOR_MAP_SWIZZLE_32B);
    cuuint32_t box2[2] = {64, 192};
    tm_wo2 = make_map((void*)wo, 2, dims, str, box2, CU_TENSOR_MAP_SWIZZLE_128B);
  }
  {
    cuuint64_t dims[5] = {192, 112, 112, 2, 2};
    cuuint64_t str[4] = {2ull * 224 * 384, 768, 384, 224ull * 384};
    cuuint32_t box[5] = {48, 4, 16, 1, 1};
    tm_out = make_map((void*)out, 5, dims, str, box, CU_TENSOR_MAP_SWIZZLE_NONE);
  }
  {
    cuuint64_t dims[5] = {64, 112, 112, 6, 2};
    cuuint64_t str[4] = {2ull * 224 * 384, 768, 128, 224ull * 384};
    cuuint32_t box[5] = {64, 4, 16, 1, 1};
    tm_o2 = make_map((void*)out, 5, dims, str, box, CU_TENSOR_MAP_SWIZZLE_128B);
  }
  cudaFuncSetAttribute(nat_kernel, cudaFuncAttributeMaxDynamicSharedMemorySize, kSmemBytes);
  nat_kernel<<<kStripCtas + kProjCtas, kThreads, kSmemBytes>>>(wqkv, rpb, tm_x, tm_w, tm_h, tm_r, tm_wo, tm_out, tm_wo2, tm_o2);
}
```

```cpp
#include <cuda_runtime.h>
#include <cuda_bf16.h>
#include <cuda.h>
#include <stdint.h>

#define DEVI __device__ __forceinline__

namespace nat {

DEVI uint32_t smem_u32(const void* p) { return (uint32_t)__cvta_generic_to_shared(p); }

DEVI void mbar_init(uint32_t bar, uint32_t count) {
  asm volatile("mbarrier.init.shared::cta.b64 [%0], %1;" ::"r"(bar), "r"(count) : "memory");
}
DEVI void mbar_expect_tx(uint32_t bar, uint32_t bytes) {
  asm volatile("mbarrier.arrive.expect_tx.shared::cta.b64 _, [%0], %1;" ::"r"(bar), "r"(bytes) : "memory");
}
DEVI void mbar_arrive(uint32_t bar) {
  asm volatile("mbarrier.arrive.shared::cta.b64 _, [%0];" ::"r"(bar) : "memory");
}
DEVI bool mbar_try_wait(uint32_t bar, uint32_t parity) {
  uint32_t ok;
  asm volatile(
      "{\n.reg .pred p;\nmbarrier.try_wait.parity.shared::cta.b64 p, [%1], %2;\nselp.u32 %0, 1, 0, p;\n}\n"
      : "=r"(ok)
      : "r"(bar), "r"(parity)
      : "memory");
  return ok != 0;
}
DEVI bool mbar_test_wait(uint32_t bar, uint32_t parity) {
  uint32_t ok;
  asm volatile(
      "{\n.reg .pred p;\nmbarrier.test_wait.parity.shared::cta.b64 p, [%1], %2;\nselp.u32 %0, 1, 0, p;\n}\n"
      : "=r"(ok)
      : "r"(bar), "r"(parity)
      : "memory");
  return ok != 0;
}
#define BAIL(code) __trap()
#define LIMIT (1u << 20)
DEVI void mbar_wait(uint32_t bar, uint32_t parity) {
  uint32_t it = 0;
  while (!mbar_try_wait(bar, parity)) {
    if (++it > LIMIT) { BAIL(bar & 0xfffff); break; }
  }
}
DEVI void fence_mbar_init() { asm volatile("fence.mbarrier_init.release.cluster;" ::: "memory"); }

DEVI void tma_load_2d(uint32_t dst, const CUtensorMap* tm, uint32_t bar, int c0, int c1) {
  asm volatile(
      "cp.async.bulk.tensor.2d.shared::cluster.global.mbarrier::complete_tx::bytes [%0], [%1, {%3, %4}], [%2];"
      ::"r"(dst), "l"(tm), "r"(bar), "r"(c0), "r"(c1)
      : "memory");
}
DEVI void tma_store_5d(const CUtensorMap* tm, uint32_t src, int c0, int c1, int c2, int c3, int c4) {
  asm volatile("cp.async.bulk.tensor.5d.global.shared::cta.bulk_group [%0, {%2, %3, %4, %5, %6}], [%1];"
               ::"l"(tm), "r"(src), "r"(c0), "r"(c1), "r"(c2), "r"(c3), "r"(c4)
               : "memory");
}
DEVI void bulk_wait_read1() { asm volatile("cp.async.bulk.wait_group.read 1;" ::: "memory"); }
DEVI void bulk_wait_read() { asm volatile("cp.async.bulk.wait_group.read 0;" ::: "memory"); }
DEVI void tma_load_5d(uint32_t dst, const CUtensorMap* tm, uint32_t bar, int c0, int c1, int c2, int c3, int c4) {
  asm volatile(
      "cp.async.bulk.tensor.5d.shared::cluster.global.mbarrier::complete_tx::bytes [%0], [%1, {%3, %4, %5, %6, %7}], [%2];"
      ::"r"(dst), "l"(tm), "r"(bar), "r"(c0), "r"(c1), "r"(c2), "r"(c3), "r"(c4)
      : "memory");
}
DEVI uint64_t policy_evict_first() {
  uint64_t p;
  asm("createpolicy.fractional.L2::evict_first.b64 %0, 1.0;" : "=l"(p));
  return p;
}
DEVI void bulk_load_hint(uint32_t dst, const void* src, uint32_t bytes, uint32_t bar, uint64_t pol) {
  asm volatile("cp.async.bulk.shared::cluster.global.mbarrier::complete_tx::bytes.L2::cache_hint [%0], [%1], %2, [%3], %4;"
               ::"r"(dst), "l"(src), "r"(bytes), "r"(bar), "l"(pol) : "memory");
}
DEVI void prefetch_map(const CUtensorMap* tm) {
  asm volatile("prefetch.tensormap [%0];" ::"l"(tm) : "memory");
}
DEVI void tma_prefetch_5d(const CUtensorMap* tm, int c0, int c1, int c2, int c3, int c4) {
  asm volatile("cp.async.bulk.prefetch.tensor.5d.L2.global [%0, {%1, %2, %3, %4, %5}];"
               ::"l"(tm), "r"(c0), "r"(c1), "r"(c2), "r"(c3), "r"(c4)
               : "memory");
}
DEVI void bulk_load(uint32_t dst, const void* src, uint32_t bytes, uint32_t bar) {
  asm volatile("cp.async.bulk.shared::cluster.global.mbarrier::complete_tx::bytes [%0], [%1], %2, [%3];"
               ::"r"(dst), "l"(src), "r"(bytes), "r"(bar) : "memory");
}
DEVI void bulk_store(void* dst, uint32_t src, uint32_t bytes) {
  asm volatile("cp.async.bulk.global.shared::cta.bulk_group [%0], [%1], %2;" ::"l"(dst), "r"(src), "r"(bytes) : "memory");
}
DEVI void bulk_commit() { asm volatile("cp.async.bulk.commit_group;" ::: "memory"); }
template <int N>
DEVI void bulk_wait() { asm volatile("cp.async.bulk.wait_group %0;" ::"n"(N) : "memory"); }

template <int N>
DEVI void reg_dec() { asm volatile("setmaxnreg.dec.sync.aligned.u32 %0;" ::"n"(N)); }
template <int N>
DEVI void reg_inc() { asm volatile("setmaxnreg.inc.sync.aligned.u32 %0;" ::"n"(N)); }

DEVI void wg_fence() { asm volatile("wgmma.fence.sync.aligned;" ::: "memory"); }
DEVI void wg_commit() { asm volatile("wgmma.commit_group.sync.aligned;" ::: "memory"); }
template <int N>
DEVI void wg_wait() { asm volatile("wgmma.wait_group.sync.aligned %0;" ::"n"(N) : "memory"); }
template <int N>
DEVI void fence_regs(float (&d)[N]) {
#pragma unroll
  for (int i = 0; i < N; i++) asm volatile("" : "+f"(d[i])::"memory");
}

DEVI uint64_t make_desc(uint32_t addr, uint32_t lbo, uint32_t sbo, uint32_t swz) {
  return (uint64_t)((addr & 0x3FFFFu) >> 4) | ((uint64_t)((lbo & 0x3FFFFu) >> 4) << 16) |
         ((uint64_t)((sbo & 0x3FFFFu) >> 4) << 32) | ((uint64_t)swz << 62);
}

DEVI uint64_t desc64(uint32_t lo, uint32_t hi) {
  uint64_t d;
  asm("mov.b64 %0, {%1, %2};" : "=l"(d) : "r"(lo), "r"(hi));
  return d;
}
DEVI uint32_t pack_bf16(float lo, float hi) {
  uint32_t r;
  asm("cvt.rn.bf16x2.f32 %0, %1, %2;" : "=r"(r) : "f"(hi), "f"(lo));
  return r;
}
DEVI float ex2(float x) {
  float r;
  asm("ex2.approx.ftz.f32 %0, %1;" : "=f"(r) : "f"(x));
  return r;
}
DEVI float rcp_approx(float x) {
  float r;
  asm("rcp.approx.ftz.f32 %0, %1;" : "=f"(r) : "f"(x));
  return r;
}
DEVI uint32_t movmatrix_t(uint32_t a) {
  uint32_t r;
  asm("movmatrix.sync.aligned.m8n8.trans.b16 %0, %1;" : "=r"(r) : "r"(a));
  return r;
}
DEVI void ldmatrix_x4(uint32_t (&r)[4], uint32_t addr) {
  asm volatile("ldmatrix.sync.aligned.m8n8.x4.shared.b16 {%0, %1, %2, %3}, [%4];"
               : "=r"(r[0]), "=r"(r[1]), "=r"(r[2]), "=r"(r[3]) : "r"(addr) : "memory");
}
DEVI void ldmatrix_x4(uint32_t& r0, uint32_t& r1, uint32_t& r2, uint32_t& r3, uint32_t addr) {
  asm volatile("ldmatrix.sync.aligned.m8n8.x4.shared.b16 {%0, %1, %2, %3}, [%4];"
               : "=r"(r0), "=r"(r1), "=r"(r2), "=r"(r3) : "r"(addr) : "memory");
}
DEVI void ldmatrix_x2(uint32_t& r0, uint32_t& r1, uint32_t addr) {
  asm volatile("ldmatrix.sync.aligned.m8n8.x2.shared.b16 {%0, %1}, [%2];"
               : "=r"(r0), "=r"(r1) : "r"(addr) : "memory");
}
DEVI void ldmatrix_x4_t(uint32_t (&r)[4], uint32_t addr) {
  asm volatile("ldmatrix.sync.aligned.m8n8.x4.trans.shared.b16 {%0, %1, %2, %3}, [%4];"
               : "=r"(r[0]), "=r"(r[1]), "=r"(r[2]), "=r"(r[3]) : "r"(addr) : "memory");
}
DEVI void stmatrix_x4(uint32_t addr, uint32_t r0, uint32_t r1, uint32_t r2, uint32_t r3) {
  asm volatile("stmatrix.sync.aligned.m8n8.x4.shared.b16 [%0], {%1, %2, %3, %4};"
               ::"r"(addr), "r"(r0), "r"(r1), "r"(r2), "r"(r3) : "memory");
}
DEVI void stmatrix_x4_t(uint32_t addr, uint32_t r0, uint32_t r1, uint32_t r2, uint32_t r3) {
  asm volatile("stmatrix.sync.aligned.m8n8.x4.trans.shared.b16 [%0], {%1, %2, %3, %4};"
               ::"r"(addr), "r"(r0), "r"(r1), "r"(r2), "r"(r3) : "memory");
}
DEVI void mma16816(float (&d)[4], const uint32_t (&a)[4], uint32_t b0, uint32_t b1) {
  asm volatile("mma.sync.aligned.m16n8k16.row.col.f32.bf16.bf16.f32 {%0, %1, %2, %3}, {%4, %5, %6, %7}, {%8, %9}, {%0, %1, %2, %3};"
               : "+f"(d[0]), "+f"(d[1]), "+f"(d[2]), "+f"(d[3])
               : "r"(a[0]), "r"(a[1]), "r"(a[2]), "r"(a[3]), "r"(b0), "r"(b1));
}
DEVI void mma16816_z(float (&d)[4], const uint32_t (&a)[4], uint32_t b0, uint32_t b1) {
  asm volatile("mma.sync.aligned.m16n8k16.row.col.f32.bf16.bf16.f32 {%0, %1, %2, %3}, {%4, %5, %6, %7}, {%8, %9}, {%10, %10, %10, %10};"
               : "=f"(d[0]), "=f"(d[1]), "=f"(d[2]), "=f"(d[3])
               : "r"(a[0]), "r"(a[1]), "r"(a[2]), "r"(a[3]), "r"(b0), "r"(b1), "f"(0.f));
}
DEVI void mma16816_c(float (&d)[4], const uint32_t (&a)[4], uint32_t b0, uint32_t b1, const float (&c)[4]) {
  asm volatile("mma.sync.aligned.m16n8k16.row.col.f32.bf16.bf16.f32 {%0, %1, %2, %3}, {%4, %5, %6, %7}, {%8, %9}, {%10, %11, %12, %13};"
               : "=f"(d[0]), "=f"(d[1]), "=f"(d[2]), "=f"(d[3])
               : "r"(a[0]), "r"(a[1]), "r"(a[2]), "r"(a[3]), "r"(b0), "r"(b1), "f"(c[0]), "f"(c[1]), "f"(c[2]), "f"(c[3]));
}
template <int BIT>
DEVI void sel2(uint32_t mask, float& r0, float& r1, float a0, float a1, float b0, float b1) {
  asm("{\n.reg .pred p;\n.reg .b32 t;\nand.b32 t, %2, %7;\nsetp.ne.b32 p, t, 0;\nselp.f32 %0, %3, %5, p;\nselp.f32 %1, %4, %6, p;\n}"
      : "=f"(r0), "=f"(r1) : "r"(mask), "f"(a0), "f"(a1), "f"(b0), "f"(b1), "n"(BIT));
}
template <int BIT>
DEVI void split2(uint32_t mask, uint32_t& r0, uint32_t& r1, uint32_t v) {
  asm("{\n.reg .pred p;\n.reg .b32 t;\nand.b32 t, %2, %4;\nsetp.ne.b32 p, t, 0;\nselp.b32 %0, %3, 0, p;\nselp.b32 %1, 0, %3, p;\n}"
      : "=r"(r0), "=r"(r1) : "r"(mask), "r"(v), "n"(BIT));
}
DEVI void stg32_if(uint32_t* p, uint32_t v, bool on) {
  asm volatile("{\n.reg .pred q;\nsetp.ne.u32 q, %2, 0;\n@q st.global.u32 [%0], %1;\n}" ::"l"(p), "r"(v), "r"((uint32_t)on) : "memory");
}
DEVI void red_max(uint32_t* p, uint32_t v) {
  asm volatile("red.relaxed.gpu.global.max.u32 [%0], %1;" ::"l"(p), "r"(v) : "memory");
}
DEVI uint4 ldg128(const void* p) {
  uint4 v;
  asm volatile("ld.global.nc.v4.u32 {%0, %1, %2, %3}, [%4];" : "=r"(v.x), "=r"(v.y), "=r"(v.z), "=r"(v.w) : "l"(p));
  return v;
}
DEVI uint32_t ld_acquire(const uint32_t* p) {
  uint32_t v;
  asm volatile("ld.acquire.gpu.global.u32 %0, [%1];" : "=r"(v) : "l"(p) : "memory");
  return v;
}
DEVI uint32_t ld_relaxed(const uint32_t* p) {
  uint32_t v;
  asm volatile("ld.relaxed.gpu.global.u32 %0, [%1];" : "=r"(v) : "l"(p) : "memory");
  return v;
}
DEVI void st_relaxed(uint32_t* p, uint32_t v) {
  asm volatile("st.relaxed.gpu.global.u32 [%0], %1;" ::"l"(p), "r"(v) : "memory");
}
DEVI void fence_gpu() { asm volatile("fence.acq_rel.gpu;" ::: "memory"); }
DEVI uint32_t lds32(uint32_t addr) {
  uint32_t v;
  asm volatile("ld.shared.u32 %0, [%1];" : "=r"(v) : "r"(addr) : "memory");
  return v;
}
DEVI uint32_t atom_inc_shared(uint32_t addr) {
  uint32_t v;
  asm volatile("atom.shared.add.u32 %0, [%1], 1;" : "=r"(v) : "r"(addr) : "memory");
  return v;
}
DEVI void sts32(uint32_t addr, uint32_t v) {
  asm volatile("st.shared.u32 [%0], %1;" ::"r"(addr), "r"(v) : "memory");
}
DEVI void sts128(uint32_t addr, uint4 v) {
  asm volatile("st.shared.v4.u32 [%0], {%1, %2, %3, %4};" ::"r"(addr), "r"(v.x), "r"(v.y), "r"(v.z), "r"(v.w) : "memory");
}
DEVI void named_bar_arrive(int id, int n) { asm volatile("bar.arrive %0, %1;" ::"r"(id), "r"(n) : "memory"); }
DEVI void named_bar_sync(int id, int n) { asm volatile("bar.sync %0, %1;" ::"r"(id), "r"(n) : "memory"); }
DEVI void fence_proxy_async() { asm volatile("fence.proxy.async.shared::cta;" ::: "memory"); }
DEVI void fence_proxy_async_global() { asm volatile("fence.proxy.async.global;" ::: "memory"); }
DEVI int clampi(int v, int lo, int hi) { return v < lo ? lo : (v > hi ? hi : v); }

template <int TA, int TB> DEVI void wgmma_m64n144k16_ss(float (&d)[72], uint64_t descA, uint64_t descB, int scaleD) {
  asm volatile("{\n.reg .pred p;\nsetp.ne.b32 p, %74, 0;\nwgmma.mma_async.sync.aligned.m64n144k16.f32.bf16.bf16 {%0, %1, %2, %3, %4, %5, %6, %7, %8, %9, %10, %11, %12, %13, %14, %15, %16, %17, %18, %19, %20, %21, %22, %23, %24, %25, %26, %27, %28, %29, %30, %31, %32, %33, %34, %35, %36, %37, %38, %39, %40, %41, %42, %43, %44, %45, %46, %47, %48, %49, %50, %51, %52, %53, %54, %55, %56, %57, %58, %59, %60, %61, %62, %63, %64, %65, %66, %67, %68, %69, %70, %71}, %72, %73, p, 1, 1, %75, %76;\n}\n"
    : "+f"(d[0]), "+f"(d[1]), "+f"(d[2]), "+f"(d[3]), "+f"(d[4]), "+f"(d[5]), "+f"(d[6]), "+f"(d[7]), "+f"(d[8]), "+f"(d[9]), "+f"(d[10]), "+f"(d[11]), "+f"(d[12]), "+f"(d[13]), "+f"(d[14]), "+f"(d[15]), "+f"(d[16]), "+f"(d[17]), "+f"(d[18]), "+f"(d[19]), "+f"(d[20]), "+f"(d[21]), "+f"(d[22]), "+f"(d[23]), "+f"(d[24]), "+f"(d[25]), "+f"(d[26]), "+f"(d[27]), "+f"(d[28]), "+f"(d[29]), "+f"(d[30]), "+f"(d[31]), "+f"(d[32]), "+f"(d[33]), "+f"(d[34]), "+f"(d[35]), "+f"(d[36]), "+f"(d[37]), "+f"(d[38]), "+f"(d[39]), "+f"(d[40]), "+f"(d[41]), "+f"(d[42]), "+f"(d[43]), "+f"(d[44]), "+f"(d[45]), "+f"(d[46]), "+f"(d[47]), "+f"(d[48]), "+f"(d[49]), "+f"(d[50]), "+f"(d[51]), "+f"(d[52]), "+f"(d[53]), "+f"(d[54]), "+f"(d[55]), "+f"(d[56]), "+f"(d[57]), "+f"(d[58]), "+f"(d[59]), "+f"(d[60]), "+f"(d[61]), "+f"(d[62]), "+f"(d[63]), "+f"(d[64]), "+f"(d[65]), "+f"(d[66]), "+f"(d[67]), "+f"(d[68]), "+f"(d[69]), "+f"(d[70]), "+f"(d[71])
    : "l"(descA), "l"(descB), "r"(scaleD), "n"(TA), "n"(TB));
}

template <int TB> DEVI void wgmma_m64n64k16_rs(float (&d)[32], uint32_t a0, uint32_t a1, uint32_t a2, uint32_t a3, uint64_t descB, int scaleD) {
  asm volatile("{\n.reg .pred p;\nsetp.ne.b32 p, %37, 0;\nwgmma.mma_async.sync.aligned.m64n64k16.f32.bf16.bf16 {%0, %1, %2, %3, %4, %5, %6, %7, %8, %9, %10, %11, %12, %13, %14, %15, %16, %17, %18, %19, %20, %21, %22, %23, %24, %25, %26, %27, %28, %29, %30, %31}, {%32, %33, %34, %35}, %36, p, 1, 1, %38;\n}\n"
    : "+f"(d[0]), "+f"(d[1]), "+f"(d[2]), "+f"(d[3]), "+f"(d[4]), "+f"(d[5]), "+f"(d[6]), "+f"(d[7]), "+f"(d[8]), "+f"(d[9]), "+f"(d[10]), "+f"(d[11]), "+f"(d[12]), "+f"(d[13]), "+f"(d[14]), "+f"(d[15]), "+f"(d[16]), "+f"(d[17]), "+f"(d[18]), "+f"(d[19]), "+f"(d[20]), "+f"(d[21]), "+f"(d[22]), "+f"(d[23]), "+f"(d[24]), "+f"(d[25]), "+f"(d[26]), "+f"(d[27]), "+f"(d[28]), "+f"(d[29]), "+f"(d[30]), "+f"(d[31])
    : "r"(a0), "r"(a1), "r"(a2), "r"(a3), "l"(descB), "r"(scaleD), "n"(TB));
}

template <int TA, int TB> DEVI void wgmma_m64n96k16_ss(float (&d)[48], uint64_t descA, uint64_t descB, int scaleD) {
  asm volatile("{\n.reg .pred p;\nsetp.ne.b32 p, %50, 0;\nwgmma.mma_async.sync.aligned.m64n96k16.f32.bf16.bf16 {%0, %1, %2, %3, %4, %5, %6, %7, %8, %9, %10, %11, %12, %13, %14, %15, %16, %17, %18, %19, %20, %21, %22, %23, %24, %25, %26, %27, %28, %29, %30, %31, %32, %33, %34, %35, %36, %37, %38, %39, %40, %41, %42, %43, %44, %45, %46, %47}, %48, %49, p, 1, 1, %51, %52;\n}\n"
    : "+f"(d[0]), "+f"(d[1]), "+f"(d[2]), "+f"(d[3]), "+f"(d[4]), "+f"(d[5]), "+f"(d[6]), "+f"(d[7]), "+f"(d[8]), "+f"(d[9]), "+f"(d[10]), "+f"(d[11]), "+f"(d[12]), "+f"(d[13]), "+f"(d[14]), "+f"(d[15]), "+f"(d[16]), "+f"(d[17]), "+f"(d[18]), "+f"(d[19]), "+f"(d[20]), "+f"(d[21]), "+f"(d[22]), "+f"(d[23]), "+f"(d[24]), "+f"(d[25]), "+f"(d[26]), "+f"(d[27]), "+f"(d[28]), "+f"(d[29]), "+f"(d[30]), "+f"(d[31]), "+f"(d[32]), "+f"(d[33]), "+f"(d[34]), "+f"(d[35]), "+f"(d[36]), "+f"(d[37]), "+f"(d[38]), "+f"(d[39]), "+f"(d[40]), "+f"(d[41]), "+f"(d[42]), "+f"(d[43]), "+f"(d[44]), "+f"(d[45]), "+f"(d[46]), "+f"(d[47])
    : "l"(descA), "l"(descB), "r"(scaleD), "n"(TA), "n"(TB));
}

constexpr int kS = 112;
constexpr int kStripCtas = 112;
constexpr int kProjCtas = 20;
constexpr int kThreads = 512;
constexpr int kArr = 29;
constexpr int kExch = 27;
constexpr int kSteps = 28;
constexpr int kTiles = kSteps * 28;
constexpr int kOTileBytes = 64 * 192 * 2;
constexpr int kTailBands = 7;
constexpr int kTail0 = kSteps - kTailBands;
constexpr int kProjTiles = (kSteps - kTailBands) * 28;
constexpr int kHaloBytes = 3 * 784 - 16, kHaloPitch = 2432;

__device__ __align__(1024) uint8_t g_o[(size_t)kTiles * kOTileBytes];
constexpr int kHaloRing = 10;
constexpr int kHaloBlock = (2 * kHaloRing + 1) * kHaloPitch;
__device__ __align__(1024) uint8_t g_halo[(size_t)kStripCtas * kHaloBlock];
__device__ __align__(1024) uint8_t g_wop[4 * 3 * 192 * 32];
__device__ uint32_t g_oflag[28 * 32];
__device__ uint32_t g_wflag[4 * 32];
__device__ uint32_t g_epoch[kProjCtas * 32];

DEVI uint32_t* halo_flags(int cta) {
  return reinterpret_cast<uint32_t*>(g_halo + (size_t)cta * kHaloBlock + 2 * kHaloRing * kHaloPitch);
}
DEVI const uint8_t* o_tile(int g, int ps) { return g_o + (size_t)(ps * kSteps + g) * kOTileBytes; }

namespace ka {
constexpr int kWAtom = 192 * 32;
constexpr int kWBytes = 9 * kWAtom;
constexpr int kXBytes = 64 * 384;
constexpr int kCol = 784;
constexpr int kQCol = 400;
constexpr int kSlot = 22 * kCol;
constexpr int kQSlot = 16 * kQCol;
constexpr int kQOff = 5 * kSlot + 32;
constexpr int kOffX = kWBytes;
constexpr int kOffRing = kOffX + 2 * kXBytes;
constexpr int kOffBar = kOffRing + kQOff + 6 * kQSlot;
constexpr int kOffStage = kOffX, kOffWo = kOffX + 2 * kWAtom;
constexpr int kOffDummy = kOffBar + 896;
DEVI uint32_t tail_buf(int i) { return i < 2 ? i * kOTileBytes : kOffRing + (i - 2) * 2 * kSlot; }
constexpr int kLastBytes = 3 * (16 + 2 * 15) * 128;
constexpr int kBarX = 0, kBarFull = 256, kBarO = 512, kBarT = 768, kBarJunk = 896;
constexpr int kSmemBytes = kOffBar + 896 + 704;
constexpr int kD = 6;
static_assert(kTailBands <= 8, "buffers");
constexpr int kShift = kArr - kD + 1;
constexpr int kNbInit = 0, kNbMisc = 1, kNbBurst = 2, kNbTile = 7, kNbFirst = 13, kNbX = 14;
}

namespace kb {
constexpr int kWoBlk = 192 * 128;
constexpr int kStages = 6;
constexpr int kOffA = 3 * kWoBlk;
constexpr int kOffBar = kOffA + kStages * kOTileBytes;
constexpr int kSmemBytes = kOffBar + 192;
}

constexpr int kSmemBytes = ka::kSmemBytes > kb::kSmemBytes ? ka::kSmemBytes : kb::kSmemBytes;
static_assert(kSmemBytes <= 232448, "smem");

#define TRACE(idx)
#define GT(i)
#define ATRACE(k)
#define TRBASE (sbase + kTraceOff)

DEVI void mbar_wait_sleep(uint32_t bar, uint32_t parity) {
  uint32_t it = 0;
  while (!mbar_test_wait(bar, parity)) {
    __nanosleep(200);
    if (++it > LIMIT) { BAIL(bar & 0xfffff); break; }
  }
}

DEVI void publish_fence() {
  fence_proxy_async_global();
  fence_gpu();
}

DEVI uint32_t sched_fence() {
  uint32_t t;
  asm volatile("mov.u32 %0, %clock;" : "=r"(t)::"memory");
  return t;
}

struct AttnState {
  uint32_t kf[5][3][4];
  uint32_t vf[5][3][4];
  float bias[5][4];
  uint32_t p[5][2];
  uint32_t kaddr, vaddr, qaddr, bar, junk, fence;
  uint32_t ones[4];
  bool rdy;
  uint32_t pm;
  uint32_t* optr;
};

DEVI void store_o(AttnState& s, float (&o)[3][4], float i0, float i1, bool on) {
#pragma unroll
  for (int mt = 0; mt < 3; mt++) {
    stg32_if(s.optr + (2 * mt) * 32, pack_bf16(o[mt][0] * i0, o[mt][1] * i1), on);
    stg32_if(s.optr + (2 * mt + 1) * 32, pack_bf16(o[mt][2] * i0, o[mt][3] * i1), on);
  }
  s.optr += kOTileBytes / 4;
}

template <int PH>
DEVI void attn_step(AttnState& s, int g, int warp, const __nv_bfloat16* __restrict__ rpb) {
  using namespace ka;
  constexpr int R = (2 * PH) % 5, N0 = (R + 3) % 5, N1 = (R + 4) % 5;
  constexpr int SL = ((PH + 1) % 5) * kSlot;
  if (PH == 0 && g == 0) {
    {
      const int lane = threadIdx.x & 31, qc0 = 16 * ((blockIdx.x >> 2) % 7) + 2 * warp;
      const int kc = clampi(qc0 - 3, 0, kS - 8) + (lane >> 2);
      const unsigned short* r = reinterpret_cast<const unsigned short*>(rpb) + (blockIdx.x & 3) * 169 + (3 - (lane & 3)) * 13 + kc - qc0 + 6;
      const int sw0 = clampi(qc0 - 3, 0, kS - 7), sw1 = clampi(qc0 - 2, 0, kS - 7);
      const bool ok0 = kc >= sw0 && kc < sw0 + 7, ok1 = kc >= sw1 && kc < sw1 + 7;
#pragma unroll
      for (int i = 0; i < 10; i++) {
        const uint32_t v0 = ok0 ? (uint32_t)__ldg(r + i * 13) : 0xFF80u;
        const uint32_t v1 = ok1 ? (uint32_t)__ldg(r + i * 13 - 1) : 0xFF80u;
        s.bias[i >> 1][2 * (i & 1)] = __uint_as_float(v0 << 16) * 6.928203230275509f;
        s.bias[i >> 1][2 * (i & 1) + 1] = __uint_as_float(v1 << 16) * 6.928203230275509f;
      }
    }
    named_bar_sync(kNbMisc, 384);
    mbar_wait(s.bar + kBarFull, 0);
#pragma unroll
    for (int k = 0; k < 3; k++) {
      ldmatrix_x4(s.kf[1][k], s.kaddr + k * 32);
      ldmatrix_x4(s.kf[2][k], s.kaddr + 384 + k * 32);
      ldmatrix_x4_t(s.vf[1][k], s.vaddr + k * 32);
      ldmatrix_x4_t(s.vf[2][k], s.vaddr + 384 + k * 32);
      s.vf[0][k][0] = s.vf[0][k][1] = s.vf[0][k][2] = s.vf[0][k][3] = 0u;
    }
    named_bar_arrive(kNbFirst, 384);
  }
  if (!s.rdy) mbar_wait(s.bar + kBarFull + 8 * (g + 1), 0);
  if (PH == kShift % 5 && g == kShift && warp >= 4) named_bar_sync(kNbInit, 256);
  ATRACE(0);
  float t[5][4], o[3][4], z[4];
  uint32_t q[6];
  ldmatrix_x4(q[0], q[1], q[2], q[3], s.qaddr);
  ldmatrix_x2(q[4], q[5], s.qaddr + 64);
#pragma unroll
  for (int ks = 0; ks < 3; ks++) {
    ldmatrix_x4(s.kf[N0][ks], s.kaddr + SL + ks * 32);
    ldmatrix_x4(s.kf[N1][ks], s.kaddr + SL + 384 + ks * 32);
  }
#pragma unroll
  for (int mt = 0; mt < 3; mt++) mma16816_z(o[mt], s.vf[N0][mt], s.p[0][0], s.p[0][1]);
  mma16816_z(z, s.ones, s.p[0][0] | s.p[4][0], s.p[0][1] | s.p[4][1]);
#pragma unroll
  for (int i = 1; i < 5; i++) {
#pragma unroll
    for (int mt = 0; mt < 3; mt++) mma16816(o[mt], s.vf[(R + 3 + i) % 5][mt], s.p[i][0], s.p[i][1]);
    if (i < 4) mma16816(z, s.ones, s.p[i][0], s.p[i][1]);
  }
  const uint32_t f1 = sched_fence();
  s.junk ^= s.fence;
#pragma unroll
  for (int n = 5; n >= 0; n--) ldmatrix_x4_t(s.vf[n < 3 ? N0 : N1][n % 3], s.vaddr + SL + (n / 3) * 384 + (n % 3) * 32);
#pragma unroll
  for (int i = 0; i < 5; i++) mma16816_c(t[i], s.kf[(R + i) % 5][0], q[0], q[1], s.bias[i]);
#pragma unroll
  for (int ks = 1; ks < 3; ks++) {
#pragma unroll
    for (int i = 0; i < 5; i++) mma16816(t[i], s.kf[(R + i) % 5][ks], q[2 * ks], q[2 * ks + 1]);
  }
  const uint32_t f2 = sched_fence();
  named_bar_arrive(kNbBurst + (PH + kD) % 5, 384);
  s.fence = sched_fence();
  if (PH == kShift % 5 && g == kShift && warp < 4) named_bar_arrive(kNbInit, 256);
  ATRACE(1);
  uint32_t pm = s.pm;
  if (PH == 0 && g == 0) pm &= ~0x3Fu;
  if (PH == 2 && g == kSteps - 1) pm |= 0x3Fu;
  float x[7][2];
  sel2<1>(pm, x[0][0], x[0][1], t[0][0], t[0][1], t[3][2], t[3][3]);
  sel2<2>(pm, x[1][0], x[1][1], t[0][2], t[0][3], t[4][0], t[4][1]);
  sel2<4>(pm, x[2][0], x[2][1], t[1][0], t[1][1], t[4][2], t[4][3]);
#pragma unroll
  for (int e = 0; e < 2; e++) {
    x[3][e] = t[1][2 + e]; x[4][e] = t[2][e]; x[5][e] = t[2][2 + e]; x[6][e] = t[3][e];
  }
  float m0 = fmaxf(fmaxf(fmaxf(x[0][0], x[1][0]), fmaxf(x[2][0], x[3][0])), fmaxf(fmaxf(x[4][0], x[5][0]), x[6][0]));
  float m1 = fmaxf(fmaxf(fmaxf(x[0][1], x[1][1]), fmaxf(x[2][1], x[3][1])), fmaxf(fmaxf(x[4][1], x[5][1]), x[6][1]));
#pragma unroll
  for (int d = 4; d <= 16; d <<= 1) {
    m0 = fmaxf(m0, __shfl_xor_sync(0xffffffffu, m0, d));
    m1 = fmaxf(m1, __shfl_xor_sync(0xffffffffu, m1, d));
  }
  s.rdy = PH == 3 && g < 0;
  if (PH < 3 || g >= 0) s.rdy = mbar_test_wait(s.bar + kBarFull + 8 * (g + 2), 0);
  const float c = 0.14433756729740643f * 1.4426950408889634f;
  const float n0 = -m0 * c, n1 = -m1 * c;
  uint32_t pt[7];
#pragma unroll
  for (int i = 0; i < 7; i++) {
    const float e0 = ex2(fmaf(x[i][0], c, n0)), e1 = ex2(fmaf(x[i][1], c, n1));
    pt[i] = movmatrix_t(pack_bf16(e0, e1));
  }
  split2<8>(pm, s.p[0][0], s.p[3][1], pt[0]);
  split2<16>(pm, s.p[0][1], s.p[4][0], pt[1]);
  split2<32>(pm, s.p[1][0], s.p[4][1], pt[2]);
  s.p[1][1] = pt[3]; s.p[2][0] = pt[4]; s.p[2][1] = pt[5]; s.p[3][0] = pt[6];
#pragma unroll
  for (int i = 0; i < 5; i++) asm volatile("" : "+r"(s.p[i][0]), "+r"(s.p[i][1])::"memory");
  const bool real = PH == 1 || PH == 2 || g > 0;
  store_o(s, o, rcp_approx(z[0]), rcp_approx(z[1]), real);
  __syncwarp();
  if ((s.pm & 64) && real) mbar_arrive(s.bar + kBarO + 8 * (g - 1));
  s.junk ^= f1 ^ f2;
  s.qaddr += kQSlot;
  if (s.qaddr >= s.bar) s.qaddr -= 6 * kQSlot;
  asm volatile("" : "+r"(s.junk)::"memory");
  ATRACE(2);
}

__global__ void __launch_bounds__(kThreads, 1)
nat_kernel(const __nv_bfloat16* __restrict__ wqkv, const __nv_bfloat16* __restrict__ rpb,
           const __grid_constant__ CUtensorMap tm_x, const __grid_constant__ CUtensorMap tm_w,
           const __grid_constant__ CUtensorMap tm_h, const __grid_constant__ CUtensorMap tm_r,
           const __grid_constant__ CUtensorMap tm_wo, const __grid_constant__ CUtensorMap tm_out,
           const __grid_constant__ CUtensorMap tm_wo2, const __grid_constant__ CUtensorMap tm_o2) {
  extern __shared__ __align__(1024) uint8_t smem_raw[];
  const uint32_t sbase = smem_u32(smem_raw);
  if (sbase & 1023u) __trap();
  const int warp = __shfl_sync(0xffffffffu, (int)(threadIdx.x >> 5), 0), lane = threadIdx.x & 31;
  const int wg = warp >> 2, wl = warp & 3;
  const int cta = blockIdx.x;
  const bool strip_cta = cta < kStripCtas;
  const int head = cta & 3, ps = cta >> 2, par = ps / 7, strip = ps - 7 * par;
  if (threadIdx.x == 0) TRACE(0);

  if (threadIdx.x == 416) prefetch_map(strip_cta ? &tm_w : &tm_wo2);
  if (strip_cta && threadIdx.x == 384) {
    using namespace ka;
    const uint32_t bar = sbase + kOffBar;
    mbar_init(bar + kBarX, 1);
    mbar_expect_tx(bar + kBarX, kXBytes + 6 * kWAtom);
    tma_load_5d(sbase + kOffX, &tm_x, bar + kBarX, 0, 16 * strip, -1, 3 * (par & 1), par >> 1);
#pragma unroll
    for (int i = 3; i < 9; i++)
      tma_load_2d(sbase + i * kWAtom, &tm_w, bar + kBarX, (i / 3) * 192 + head * 48 + (i % 3) * 16, 0);
    TRACE(10);
  }
  __syncwarp();
  if (strip_cta && wg == 2 && threadIdx.x < 256 + 96) {
    using namespace ka;
    uint4 v[12];
    const int wk = ((int)threadIdx.x - 256) / 6, wu = (int)threadIdx.x - 256 - 6 * wk;
    const uint8_t* src = reinterpret_cast<const uint8_t*>(wqkv) + wk * 1152 + head * 96 + wu * 16;
#pragma unroll
    for (int i = 0; i < 12; i++) v[i] = ldg128(src + i * 16 * 1152);
    const uint32_t dst = sbase + (wu >> 1) * kWAtom + wk * 32 + (((wu ^ (wk >> 2)) & 1) << 4);
#pragma unroll
    for (int i = 0; i < 12; i++) sts128(dst + i * 16 * 32, v[i]);
    if (warp == 8) TRACE(6);
    fence_proxy_async();
  }
  if (threadIdx.x == 480) GT(0);

  if (strip_cta) {
    using namespace ka;
    const uint32_t bar = sbase + kOffBar, ring = sbase + kOffRing;
    const int tskip = (head ^ (head >> 1)) & 1, thalf = head >> 1;
    if (wg < 2) {
      reg_inc<176>();
      AttnState s;
      const int qc0 = 16 * strip + 2 * warp;
      const int kc0 = clampi(qc0 - 3, 0, kS - 8);
      const uint32_t colb = ring + (kc0 - (16 * strip - 3) + (lane & 7)) * kCol;
      s.kaddr = colb + ((lane >> 3) & 1) * 192 + (lane >> 4) * 16;
      s.vaddr = colb + 96 + (lane >> 4) * 192 + ((lane >> 3) & 1) * 16;
      {
        const int qr = (lane & 7) >> 1;
        const uint32_t qa = ring + kQOff + (2 * warp + (lane & 1)) * kQCol + (lane >> 3) * 16;
        s.qaddr = qa + (qr == 3 ? 5 * kQSlot : 4 * kQSlot + (qr + 1) * 96);
      }
      s.bar = bar;
      s.optr = reinterpret_cast<uint32_t*>(g_o + (size_t)ps * kSteps * kOTileBytes + head * 6144 + warp * 768) + lane - 3 * kOTileBytes / 4;
#pragma unroll
      for (int i = 0; i < 5; i++) {
        s.p[i][0] = s.p[i][1] = 0u;
        s.bias[i][0] = s.bias[i][1] = s.bias[i][2] = s.bias[i][3] = 0.f;
#pragma unroll
        for (int k = 0; k < 3; k++)
#pragma unroll
          for (int c = 0; c < 4; c++) s.kf[i][k][c] = s.vf[i][k][c] = 0u;
      }
      s.junk = s.fence = 0;
      s.rdy = true;
#pragma unroll
      for (int i = 0; i < 4; i++) s.ones[i] = __shfl_sync(0xffffffffu, 0x3F803F80u, i);
      s.pm = (7u << (lane & 3) & 7u) | ((7u << (lane >> 3) & 7u) << 3) | (lane == 0 ? 64u : 0u);
      s.pm = __shfl_sync(0xffffffffu, s.pm, lane);
#pragma unroll 1
      for (int g = -2; g < kSteps; g += 5) {
        attn_step<3>(s, g, warp, rpb);
        attn_step<4>(s, g + 1, warp, rpb);
        attn_step<0>(s, g + 2, warp, rpb);
        attn_step<1>(s, g + 3, warp, rpb);
        attn_step<2>(s, g + 4, warp, rpb);
      }
      {
        float o[3][4], z[4];
#pragma unroll
        for (int mt = 0; mt < 3; mt++) mma16816_z(o[mt], s.vf[4][mt], s.p[0][0], s.p[0][1]);
        mma16816_z(z, s.ones, s.p[0][0], s.p[0][1]);
#pragma unroll
        for (int i = 1; i < 5; i++) {
#pragma unroll
          for (int mt = 0; mt < 3; mt++) mma16816(o[mt], s.vf[i - 1][mt], s.p[i][0], s.p[i][1]);
          mma16816(z, s.ones, s.p[i][0], s.p[i][1]);
        }
        store_o(s, o, rcp_approx(z[0]), rcp_approx(z[1]), true);
        __syncwarp();
        if (lane == 0) mbar_arrive(bar + kBarO + 8 * (kSteps - 1));
      }
      s.junk ^= s.fence;
      if (s.junk == 0x9e3779b9u) sts32(bar + kBarJunk, 0);
      if (warp == 0) TRACE(1);
      if (threadIdx.x == 128) GT(3);
    } else if (wg == 2) {
      reg_dec<120>();
      const int col = ((lane >> 3) & 1) * 8 + (lane & 7);
      uint32_t kva = ring + (3 + col) * kCol + wl * 192 + (lane >> 4) * 16;
      uint32_t qa = ring + kQOff + col * kQCol + wl * 96 + (lane >> 4) * 16;
      const uint32_t alo = (uint32_t)make_desc(sbase + kOffX, 16, 1024, 1), blo = (uint32_t)make_desc(sbase, kWAtom, 256, 3);
      constexpr uint32_t ahi = (1u << 30) | (1024 >> 4), bhi = (3u << 30) | (256 >> 4);
      if (wl == 0) TRACE(2);
      uint32_t gj = 0, qprev = 0, qk[12];
#pragma unroll
      for (int j = 0; j < 12; j++) qk[j] = 0;
      int bid = kNbBurst, tid = kNbTile;
      named_bar_arrive(kNbBurst + (kD - 2) % 5, 384);
      named_bar_arrive(kNbBurst + (kD - 1) % 5, 384);
      named_bar_sync(kNbX, 160);
      if (wl == 0) TRACE(7);
      mbar_wait(bar + kBarX, 0);
      if (wl == 0) TRACE(16 + 0);
#pragma unroll 1
      for (int a = 0; a < kArr; a++) {
        float acc[72];
        const uint32_t al = alo + (a & 1) * (kXBytes >> 4);
        if (a >= kD) named_bar_sync(bid, 384);
        if (wl == 0) TRACE(16 + a * 4 + 1);
        wg_fence();
#pragma unroll
        for (int k = 0; k < 12; k++)
          wgmma_m64n144k16_ss<0, 1>(acc, desc64(al + (((k >> 2) * 8192 + (k & 3) * 32) >> 4), ahi), desc64(blo + k * 32, bhi), k != 0);
        wg_commit();
        gj ^= sched_fence();
        if (a > 0) {
#pragma unroll
          for (int j = 0; j < 3; j++) stmatrix_x4(qprev + j * 32, qk[4 * j], qk[4 * j + 1], qk[4 * j + 2], qk[4 * j + 3]);
          __syncwarp();
          if (lane == 0 && a - 1 < kExch) mbar_arrive(bar + kBarFull + 8 * (a - 1));
        }
        bid = bid == kNbBurst + 4 ? kNbBurst : bid + 1;
        if (a == 0) named_bar_sync(kNbInit, 256);
        const bool xok = mbar_test_wait(bar + kBarX + 8 * (a + 1), 0);
        if (a == kArr - 1 && wl != 0) {
          const int r = col / 3, c = col - 3 * r;
          qa = sbase + kOffDummy + lane * 16;
          kva = col < 15 && wl < 3 ? ring + ((kExch + (r >> 2)) % 5) * kSlot + ((wl - 1) * 19 + c) * kCol + (r & 3) * 192 + (lane >> 4) * 16
                                   : qa;
        }
        wg_wait<0>();
        fence_regs(acc);
        named_bar_arrive(kNbX + (a & 1), 160);
        if (a == 5) named_bar_sync(kNbFirst, 384);
        if (wl == 0) TRACE(16 + a * 4 + 2);
#pragma unroll
        for (int j = 3; j < 9; j++)
          stmatrix_x4(kva + (j - 3) * 32, pack_bf16(acc[8 * j + 0], acc[8 * j + 1]), pack_bf16(acc[8 * j + 2], acc[8 * j + 3]),
                      pack_bf16(acc[8 * j + 4], acc[8 * j + 5]), pack_bf16(acc[8 * j + 6], acc[8 * j + 7]));
#pragma unroll
        for (int j = 0; j < 12; j++) qk[j] = pack_bf16(acc[2 * j], acc[2 * j + 1]);
        qprev = qa;
        if (a < kExch) named_bar_arrive(tid, 160);
        tid = tid == kNbTile + 5 ? kNbTile : tid + 1;
        if (wl == 0) TRACE(16 + a * 4 + 3);
        if (!xok && a + 1 < kArr) mbar_wait(bar + kBarX + 8 * (a + 1), 0);
        if (wl == 0) TRACE(16 + (a + 1) * 4 + 0);
        kva += kSlot;
        if (kva >= ring + 5 * kSlot) kva -= 5 * kSlot;
        qa += kQSlot;
        if (qa >= bar) qa -= 6 * kQSlot;
      }
#pragma unroll
      for (int j = 0; j < 3; j++) stmatrix_x4(qprev + j * 32, qk[4 * j], qk[4 * j + 1], qk[4 * j + 2], qk[4 * j + 3]);
      __syncwarp();
      if (lane < kArr - kExch) mbar_arrive(bar + kBarFull + 8 * (kExch + lane));
      if (gj == 0x9e3779b9u) sts32(bar + kBarJunk, 0);
#pragma unroll 1
      for (int g = kArr - kD; g < kSteps - 1; g++) {
        named_bar_arrive(bid, 384);
        bid = bid == kNbBurst + 4 ? kNbBurst : bid + 1;
      }
      {
        const uint32_t wlo = (uint32_t)make_desc(sbase + kOffWo, kWAtom, 256, 3);
        const int n = lane & 7, j = 2 * wl + ((lane >> 3) & 1);
        const uint32_t sta = sbase + kOffStage + ((2 * j + (n & 1)) * 4 + (n >> 1)) * 96 + (lane >> 4) * 16;
        mbar_wait(bar + kBarX + 8 * kArr, 0);
        named_bar_sync(bid, 384);
        if (tskip) mbar_wait(bar + kBarO + 8 * (kSteps - 1), 0);
#pragma unroll 1
        for (int g = kTail0 + tskip, i = 0; g < kSteps; g += 2, i++) {
          float acc[48];
          mbar_wait(bar + kBarT + 8 * i, 0);
          if (wl == 0) TRACE(144 + i * 2);
          const uint32_t tlo = (uint32_t)make_desc(sbase + tail_buf(i), 128, 768, 0);
          wg_fence();
#pragma unroll
          for (int k = 0; k < 12; k++)
            wgmma_m64n96k16_ss<1, 1>(acc, desc64(tlo + (((k / 3) * 6144 + (k % 3) * 256) >> 4), 768 >> 4), desc64(wlo + k * 32, bhi), k != 0);
          wg_commit();
          if (threadIdx.x == 256) bulk_wait_read();
          named_bar_sync(kNbMisc, 128);
          wg_wait<0>();
          fence_regs(acc);
#pragma unroll
          for (int jp = 0; jp < 6; jp++)
            stmatrix_x4(sta + (jp / 3) * kWAtom + (jp % 3) * 32, pack_bf16(acc[8 * jp + 0], acc[8 * jp + 1]),
                        pack_bf16(acc[8 * jp + 2], acc[8 * jp + 3]), pack_bf16(acc[8 * jp + 4], acc[8 * jp + 5]),
                        pack_bf16(acc[8 * jp + 6], acc[8 * jp + 7]));
          fence_proxy_async();
          named_bar_sync(kNbMisc, 128);
          if (threadIdx.x == 256) {
            tma_store_5d(&tm_out, sbase + kOffStage, thalf * 96, 4 * g, 16 * strip, par & 1, par >> 1);
            tma_store_5d(&tm_out, sbase + kOffStage + kWAtom, thalf * 96 + 48, 4 * g, 16 * strip, par & 1, par >> 1);
            bulk_commit();
          }
          __syncwarp();
          if (wl == 0) TRACE(145 + i * 2);
        }
        if (threadIdx.x == 256) {
          bulk_wait<0>();
          GT(2);
        }
      }
    } else {
      reg_dec<40>();
      if (wl == 0) named_bar_arrive(kNbX, 160);
      if (lane == 0) {
        const uint32_t b0 = bar + 64 * wl;
        if (wl == 1 && head == 1) tma_prefetch_5d(&tm_x, 0, 16 * strip, 3, 3 * (par & 1), par >> 1);
#pragma unroll
        for (int i = 0; i < 64; i += 8) {
          if (i || wl) mbar_init(b0 + kBarX + i, 1);
          mbar_init(b0 + kBarFull + i, wl < 3 || i < 8 * (kExch - 24) ? 6 : 4);
          mbar_init(b0 + kBarO + i, 8);
          if (wl == 0 && i < 32) mbar_init(b0 + kBarT + i, 1);
        }
#pragma unroll
        for (int i = 0; i < 64; i += 8) {
          if (i || wl)
            mbar_expect_tx(b0 + kBarX + i, wl < 3 || i < 32 ? kXBytes : (i == 32 ? kLastBytes : 6 * kWAtom));
          if (wl == 0 && i < 32) mbar_expect_tx(bar + kBarT + i, kOTileBytes);
        }
        fence_mbar_init();
        if (wl == 0) {
          tma_load_5d(sbase + kOffX + kXBytes, &tm_x, bar + kBarX + 8, 0, 16 * strip, 3, 3 * (par & 1), par >> 1);
          tma_prefetch_5d(&tm_x, 0, 16 * strip, 4 * (2 + ((head - 2) & 3)) - 1, 3 * (par & 1), par >> 1);
          TRACE(5);
        }
      }
      __syncwarp();
      const uint32_t ep = ld_relaxed(halo_flags(cta) + 32 + wl) * 32u;
      named_bar_arrive(kNbMisc, 384);
      named_bar_sync(kNbInit, 256);
      if (wl == 0) {
#pragma unroll 1
        for (int a = 2; a < kArr - 1; a++) {
          named_bar_sync(kNbX + (a & 1), 160);
          if (lane == 0) {
            tma_load_5d(sbase + kOffX + (a & 1) * kXBytes, &tm_x, bar + kBarX + 8 * a, 0, 16 * strip, 4 * a - 1,
                        3 * (par & 1), par >> 1);
            if (a == 20) {
              prefetch_map(&tm_h);
              prefetch_map(&tm_r);
              prefetch_map(&tm_out);
            }
            const int ap = a + 4;
            if (ap < kArr && (ap & 3) == head) tma_prefetch_5d(&tm_x, 0, 16 * strip, 4 * ap - 1, 3 * (par & 1), par >> 1);
          }
          __syncwarp();
        }
        named_bar_sync(kNbX, 160);
        if (lane < 9) {
          const int kb = lane / 3, w = lane - 3 * kb;
          tma_load_5d(sbase + kOffX + kb * 8192 + w * 2048, w == 0 ? &tm_r : &tm_h, bar + kBarX + 8 * (kArr - 1), 0,
                      16 * strip + (w == 0 ? 0 : (w == 1 ? -3 : 16)), w == 0 ? kS - 1 : 4 * kExch - 1, 3 * (par & 1) + kb, par >> 1);
        }
        {
          uint32_t it = 0;
          while (!__all_sync(0xffffffffu, (int)(ld_acquire(&g_wflag[(lane & 3) * 32]) - (ep + 1)) >= 0))
            if (++it > LIMIT) { BAIL(0x5000000); break; }
        }
        const uint8_t* wsrc = g_wop + thalf * 6 * kWAtom;
        named_bar_sync(kNbX + 1, 160);
        if (lane == 0) bulk_load(sbase + kOffWo + 2 * kWAtom, wsrc + 2 * kWAtom, 4 * kWAtom, bar + kBarX + 8 * kArr);
        uint32_t seen = ld_acquire(&g_oflag[ps * 32 + (lane & 3)]);
        named_bar_sync(kNbX, 160);
        if (lane == 0) bulk_load(sbase + kOffWo, wsrc, 2 * kWAtom, bar + kBarX + 8 * kArr);
#pragma unroll 1
        for (int g = kTail0 + tskip, i = 0; g < kSteps; g += 2, i++) {
          uint32_t it = 0;
          while (!__all_sync(0xffffffffu, (int)(seen - (ep + g + 1)) >= 0)) {
            seen = ld_acquire(&g_oflag[ps * 32 + (lane & 3)]);
            if (++it > LIMIT) { BAIL(0x3000000 + g); break; }
          }
          if (lane == 0)
            bulk_load(sbase + tail_buf(i), o_tile(g, ps), kOTileBytes, bar + kBarT + 8 * i);
          __syncwarp();
        }
      } else {
        const int p = wl - 1;
        const bool on = lane == 0 ? strip > 0 : strip < 6;
        const int nb = on ? cta + (lane == 0 ? -4 : 4) : cta;
        const uint32_t bytes = (strip > 0 && strip < 6) ? 2 * kHaloBytes : kHaloBytes;
        int slot = p, g = 0;
#pragma unroll 1
        for (int a = p; a < kExch; a += 3) {
          named_bar_sync(kNbTile + a % 6, 160);
          const uint32_t sl = ring + slot * kSlot;
          if (lane < 2) {
            fence_proxy_async();
            if (on) bulk_store(g_halo + (size_t)cta * kHaloBlock + (lane * kHaloRing + a % kHaloRing) * kHaloPitch, sl + (3 + 13 * lane) * kCol, kHaloBytes);
            bulk_commit();
          }
          __syncwarp();
          g += __ffs(~__ballot_sync(0xffffffffu, lane < 4 && mbar_test_wait(bar + kBarO + 8 * (g + lane), 0))) - 1;
          __syncwarp();
          if (lane < 2) {
            bulk_wait<0>();
            if (lane == 0) mbar_expect_tx(bar + kBarFull + 8 * a, bytes);
            else mbar_arrive(bar + kBarFull + 8 * a);
            TRACE(160 + a * 4 + 0);
            publish_fence();
            st_relaxed(halo_flags(cta) + 4 * lane + p, ep + a + 1);
            if (lane == 0 && g) red_max(&g_oflag[ps * 32 + head], ep + g);
            TRACE(160 + a * 4 + 1);
          }
          __syncwarp();
          {
            const uint32_t* fl = halo_flags(nb) + 4 * ((lane & 1) ^ 1) + p;
            uint32_t it = 0;
            while (!__all_sync(0xffffffffu, !(lane < 2 && on) || (int)(ld_acquire(fl) - (ep + a + 1)) >= 0))
              if (++it > LIMIT) { BAIL(0x1000000 + a); break; }
          }
          TRACE(160 + a * 4 + 2);
          if (lane < 2 && on)
            bulk_load(sl + lane * 19 * kCol, g_halo + (size_t)nb * kHaloBlock + ((lane ^ 1) * kHaloRing + a % kHaloRing) * kHaloPitch,
                      kHaloBytes, bar + kBarFull + 8 * a);
          TRACE(160 + a * 4 + 3);
          __syncwarp();
          slot = slot >= 2 ? slot - 2 : slot + 3;
        }
        if (lane == 0) {
#pragma unroll 1
          for (g = kSteps - 7 + p; g < kSteps; g += 3) {
            if (g < kSteps - 3) mbar_wait_sleep(bar + kBarO + 8 * g, 0);
            else mbar_wait(bar + kBarO + 8 * g, 0);
            TRACE(370 + g * 2);
            publish_fence();
            red_max(&g_oflag[ps * 32 + head], ep + g + 1);
            TRACE(371 + g * 2);
          }
          if (p == 0) GT(1);
        }
      }
      __syncwarp();
      if (lane == 0) st_relaxed(halo_flags(cta) + 32 + wl, (ep >> 5) + 1);
    }
  } else {
    using namespace kb;
    const uint32_t bar = sbase + kOffBar, sA = sbase + kOffA;
    const int k = cta - kStripCtas;
    if (wg < 3) {
      named_bar_sync(0, 512);
      uint32_t wf[12][4];
      mbar_wait(bar + 56, 0);
      {
        const int kr = (lane & 7) + ((lane >> 4) << 3);
        const uint32_t wa = sbase + wg * kWoBlk + kr * 128 + (((2 * wl + ((lane >> 3) & 1)) ^ (lane & 7)) << 4);
#pragma unroll
        for (int kk = 0; kk < 12; kk++) ldmatrix_x4_t(wf[kk], wa + kk * 2048);
      }
      named_bar_sync(3 + wg, 128);
      const int px = (2 * (lane >> 4) + (lane & 1)) * 4 + ((lane & 7) >> 1);
      const uint32_t sto = sbase + wg * kWoBlk + px * 128 + (((2 * wl + ((lane >> 3) & 1)) ^ (px & 7)) << 4);
      int st = 0, sb = 0;
      uint32_t ph = 0;
      uint32_t pk[16];
#pragma unroll
      for (int i = 0; i < 16; i++) pk[i] = 0u;
      auto store = [&](int tq) {
        const int g = tq / 28, tp = tq - 28 * g, tpar = tp / 7, tstrip = tp - 7 * tpar;
#pragma unroll
        for (int jp = 0; jp < 4; jp++)
          stmatrix_x4_t(sto + sb * 8192 + jp * 2048, pk[4 * jp], pk[4 * jp + 1], pk[4 * jp + 2], pk[4 * jp + 3]);
        fence_proxy_async();
        if (wl == 0 && lane == 0) bulk_wait_read1();
        named_bar_sync(3 + wg, 128);
        if (wl == 0 && lane == 0 && tq >= 0) {
          tma_store_5d(&tm_o2, sbase + wg * kWoBlk + sb * 8192, 0, 4 * g, 16 * tstrip, 3 * (tpar & 1) + wg, tpar >> 1);
          bulk_commit();
        }
        __syncwarp();
        sb = sb == 2 ? 0 : sb + 1;
      };
      int t = k, cur = -1;
#pragma unroll 1
      for (; t < kProjTiles; t += kProjCtas) {
        float acc[32];
        mbar_wait(bar + 8 * st, ph);
        if (warp == 0) TRACE(16 + (t / kProjCtas) * 4 + 1);
        const uint32_t blo = (uint32_t)make_desc(sA + st * kOTileBytes, 128, 768, 0);
        if (t > k || wg) named_bar_sync(6 + wg, 256);
        wg_fence();
#pragma unroll
        for (int kk = 0; kk < 12; kk++)
          wgmma_m64n64k16_rs<1>(acc, wf[kk][0], wf[kk][1], wf[kk][2], wf[kk][3],
                                desc64(blo + (((kk / 3) * 6144 + (kk % 3) * 256) >> 4), 768 >> 4), kk != 0);
        wg_commit();
        if (wg < 2 || t + kProjCtas < kProjTiles) named_bar_arrive(6 + (wg == 2 ? 0 : wg + 1), 256);
        const int nxt = (int)lds32(bar + 128 + 4 * st);
        store(cur);
        cur = nxt;
        if (warp == 0) TRACE(12 + (t / kProjCtas) * 4 + 3);
        wg_wait<0>();
        fence_regs(acc);
        if (lane == 0) mbar_arrive(bar + 64 + 8 * st);
        if (warp == 0) TRACE(16 + (t / kProjCtas) * 4 + 2);
#pragma unroll
        for (int i = 0; i < 16; i++) pk[i] = pack_bf16(acc[2 * i], acc[2 * i + 1]);
        if (++st == kStages) { st = 0; ph ^= 1; }
      }
      store(cur);
      if (warp == 0) TRACE(12 + (t / kProjCtas) * 4 + 3);
      if (wl == 0 && lane == 0) bulk_wait<0>();
      if (threadIdx.x == 0) GT(1);
    } else {
      if (lane == 0) {
        mbar_init(bar + 16 * wl, 1);
        mbar_init(bar + 16 * wl + 8, 1);
        mbar_init(bar + 64 + 16 * wl, 12);
        mbar_init(bar + 64 + 16 * wl + 8, 12);
        sts32(bar + 160, 0);
        fence_mbar_init();
      }
      __syncwarp();
      named_bar_sync(0, 512);
      if (wl == 3 && lane == 0) {
        prefetch_map(&tm_o2);
        __nanosleep(2000);
        mbar_expect_tx(bar + 56, 3 * kWoBlk);
#pragma unroll 1
        for (int i = 0; i < 3; i++) tma_load_2d(sbase + i * kWoBlk, &tm_wo2, bar + 56, i * 64, 0);
      }
      __syncwarp();
      if (wl == 3 && k < 4) {
        if (lane == 0) {
          const uint32_t e0 = ld_relaxed(&g_epoch[k * 32 + 3]);
          const uint32_t stg = sA + (kStages - 1) * kOTileBytes;
          mbar_expect_tx(bar + 48, 3 * ka::kWAtom);
#pragma unroll 1
          for (int i = 0; i < 3; i++) tma_load_2d(stg + i * ka::kWAtom, &tm_wo, bar + 48, k * 48 + i * 16, 0);
          mbar_wait(bar + 48, 0);
          bulk_store(g_wop + k * 3 * ka::kWAtom, stg, 3 * ka::kWAtom);
          bulk_commit();
          bulk_wait<0>();
          publish_fence();
          st_relaxed(&g_wflag[k * 32], e0 * 32u + 1);
          st_relaxed(&g_epoch[k * 32 + 3], e0 + 1);
        }
        __syncwarp();
        named_bar_arrive(2, 128);
      }
      if (wl < 3 && k < 4) named_bar_sync(2, 128);
      if (wl < 3 && lane < 4) {
        const uint32_t e0 = ld_relaxed(&g_epoch[k * 32 + wl]);
#pragma unroll 1
        for (int it = wl;; it += 3) {
          const int t = k + it * kProjCtas;
          if (t >= kProjTiles) break;
          const int g = t / 28, tp = t - 28 * g;
          uint32_t sp = 0;
          while (true) {
            const bool ok = (int)(ld_acquire(&g_oflag[tp * 32 + lane]) - (e0 * 32u + g + 1)) >= 0;
            if (__all_sync(15u, ok)) break;
            if (++sp > LIMIT) { BAIL(0x2000000 + t); break; }
          }
          if (lane == 0) {
            const int n = (int)atom_inc_shared(bar + 160), st = n % kStages;
            if (n >= kStages) mbar_wait(bar + 64 + 8 * st, ((n / kStages) & 1) ^ 1);
            TRACE(16 + n * 4 + 0);
            sts32(bar + 128 + 4 * st, t);
            mbar_expect_tx(bar + 8 * st, kOTileBytes);
            bulk_load_hint(sA + st * kOTileBytes, o_tile(g, tp), kOTileBytes, bar + 8 * st, policy_evict_first());
          }
          __syncwarp(15u);
        }
        if (lane == 0) st_relaxed(&g_epoch[k * 32 + wl], e0 + 1);
      }
    }
  }
}

}

namespace {

typedef CUresult (*EncodeTiledFn)(CUtensorMap*, CUtensorMapDataType, cuuint32_t, void*, const cuuint64_t*,
                                  const cuuint64_t*, const cuuint32_t*, const cuuint32_t*, CUtensorMapInterleave,
                                  CUtensorMapSwizzle, CUtensorMapL2promotion, CUtensorMapFloatOOBfill);

EncodeTiledFn get_encode_fn() {
  static EncodeTiledFn fn = nullptr;
  if (!fn) {
    void* p = nullptr;
    cudaDriverEntryPointQueryResult qres;
    if (cudaGetDriverEntryPoint("cuTensorMapEncodeTiled", &p, cudaEnableDefault, &qres) == cudaSuccess)
      fn = reinterpret_cast<EncodeTiledFn>(p);
  }
  return fn;
}

CUtensorMap make_map(void* base, int rank, const cuuint64_t* dims, const cuuint64_t* strides, const cuuint32_t* box,
                     CUtensorMapSwizzle swz) {
  CUtensorMap m;
  cuuint32_t es[5] = {1, 1, 1, 1, 1};
  get_encode_fn()(&m, CU_TENSOR_MAP_DATA_TYPE_BFLOAT16, (cuuint32_t)rank, base, dims, strides, box, es,
                  CU_TENSOR_MAP_INTERLEAVE_NONE, swz, CU_TENSOR_MAP_L2_PROMOTION_L2_128B,
                  CU_TENSOR_MAP_FLOAT_OOB_FILL_NONE);
  return m;
}

}

extern "C" void kernel_launch(void* const* d_in, const int* in_sizes, int n_in, void* d_out, int out_size) {
  using namespace nat;
  (void)in_sizes; (void)n_in; (void)out_size;
  const __nv_bfloat16* x = (const __nv_bfloat16*)d_in[0];
  const __nv_bfloat16* wqkv = (const __nv_bfloat16*)d_in[1];
  const __nv_bfloat16* wo = (const __nv_bfloat16*)d_in[2];
  const __nv_bfloat16* rpb = (const __nv_bfloat16*)d_in[3];
  __nv_bfloat16* out = (__nv_bfloat16*)d_out;

  CUtensorMap tm_x, tm_h, tm_r, tm_w, tm_wo, tm_out, tm_wo2, tm_o2;
  {
    cuuint64_t dims[5] = {64, 112, 112, 6, 2};
    cuuint64_t str[4] = {768, 2ull * 224 * 384, 128, 224ull * 384};
    cuuint32_t box[5] = {64, 16, 4, 3, 1};
    tm_x = make_map((void*)x, 5, dims, str, box, CU_TENSOR_MAP_SWIZZLE_128B);
    cuuint32_t boxh[5] = {64, 3, 5, 1, 1}, boxr[5] = {64, 16, 1, 1, 1};
    tm_h = make_map((void*)x, 5, dims, str, boxh, CU_TENSOR_MAP_SWIZZLE_128B);
    tm_r = make_map((void*)x, 5, dims, str, boxr, CU_TENSOR_MAP_SWIZZLE_128B);
  }
  {
    cuuint64_t dims[2] = {576, 192};
    cuuint64_t str[1] = {1152};
    cuuint32_t box[2] = {16, 192};
    tm_w = make_map((void*)wqkv, 2, dims, str, box, CU_TENSOR_MAP_SWIZZLE_32B);
  }
  {
    cuuint64_t dims[2] = {192, 192};
    cuuint64_t str[1] = {384};
    cuuint32_t box[2] = {16, 192};
    tm_wo = make_map((void*)wo, 2, dims, str, box, CU_TENSOR_MAP_SWIZZLE_32B);
    cuuint32_t box2[2] = {64, 192};
    tm_wo2 = make_map((void*)wo, 2, dims, str, box2, CU_TENSOR_MAP_SWIZZLE_128B);
  }
  {
    cuuint64_t dims[5] = {192, 112, 112, 2, 2};
    cuuint64_t str[4] = {2ull * 224 * 384, 768, 384, 224ull * 384};
    cuuint32_t box[5] = {48, 4, 16, 1, 1};
    tm_out = make_map((void*)out, 5, dims, str, box, CU_TENSOR_MAP_SWIZZLE_NONE);
  }
  {
    cuuint64_t dims[5] = {64, 112, 112, 6, 2};
    cuuint64_t str[4] = {2ull * 224 * 384, 768, 128, 224ull * 384};
    cuuint32_t box[5] = {64, 4, 16, 1, 1};
    tm_o2 = make_map((void*)out, 5, dims, str, box, CU_TENSOR_MAP_SWIZZLE_128B);
  }
  cudaFuncSetAttribute(nat_kernel, cudaFuncAttributeMaxDynamicSharedMemorySize, kSmemBytes);
  nat_kernel<<<kStripCtas + kProjCtas, kThreads, kSmemBytes>>>(wqkv, rpb, tm_x, tm_w, tm_h, tm_r, tm_wo, tm_out, tm_wo2, tm_o2);
}
```

```cpp
#include <cuda_runtime.h>
#include <cuda_bf16.h>
#include <cuda.h>
#include <stdint.h>

#define DEVI __device__ __forceinline__

namespace nat {

DEVI uint32_t smem_u32(const void* p) { return (uint32_t)__cvta_generic_to_shared(p); }

DEVI void mbar_init(uint32_t bar, uint32_t count) {
  asm volatile("mbarrier.init.shared::cta.b64 [%0], %1;" ::"r"(bar), "r"(count) : "memory");
}
DEVI void mbar_expect_tx(uint32_t bar, uint32_t bytes) {
  asm volatile("mbarrier.arrive.expect_tx.shared::cta.b64 _, [%0], %1;" ::"r"(bar), "r"(bytes) : "memory");
}
DEVI void mbar_arrive(uint32_t bar) {
  asm volatile("mbarrier.arrive.shared::cta.b64 _, [%0];" ::"r"(bar) : "memory");
}
DEVI bool mbar_try_wait(uint32_t bar, uint32_t parity) {
  uint32_t ok;
  asm volatile(
      "{\n.reg .pred p;\nmbarrier.try_wait.parity.shared::cta.b64 p, [%1], %2;\nselp.u32 %0, 1, 0, p;\n}\n"
      : "=r"(ok)
      : "r"(bar), "r"(parity)
      : "memory");
  return ok != 0;
}
DEVI bool mbar_test_wait(uint32_t bar, uint32_t parity) {
  uint32_t ok;
  asm volatile(
      "{\n.reg .pred p;\nmbarrier.test_wait.parity.shared::cta.b64 p, [%1], %2;\nselp.u32 %0, 1, 0, p;\n}\n"
      : "=r"(ok)
      : "r"(bar), "r"(parity)
      : "memory");
  return ok != 0;
}
#define BAIL(code) __trap()
#define LIMIT (1u << 20)
DEVI void mbar_wait(uint32_t bar, uint32_t parity) {
  uint32_t it = 0;
  while (!mbar_try_wait(bar, parity)) {
    if (++it > LIMIT) { BAIL(bar & 0xfffff); break; }
  }
}
DEVI void fence_mbar_init() { asm volatile("fence.mbarrier_init.release.cluster;" ::: "memory"); }

DEVI void tma_load_2d(uint32_t dst, const CUtensorMap* tm, uint32_t bar, int c0, int c1) {
  asm volatile(
      "cp.async.bulk.tensor.2d.shared::cluster.global.mbarrier::complete_tx::bytes [%0], [%1, {%3, %4}], [%2];"
      ::"r"(dst), "l"(tm), "r"(bar), "r"(c0), "r"(c1)
      : "memory");
}
DEVI void tma_store_5d(const CUtensorMap* tm, uint32_t src, int c0, int c1, int c2, int c3, int c4) {
  asm volatile("cp.async.bulk.tensor.5d.global.shared::cta.bulk_group [%0, {%2, %3, %4, %5, %6}], [%1];"
               ::"l"(tm), "r"(src), "r"(c0), "r"(c1), "r"(c2), "r"(c3), "r"(c4)
               : "memory");
}
DEVI void bulk_wait_read1() { asm volatile("cp.async.bulk.wait_group.read 1;" ::: "memory"); }
DEVI void bulk_wait_read() { asm volatile("cp.async.bulk.wait_group.read 0;" ::: "memory"); }
DEVI void tma_load_5d(uint32_t dst, const CUtensorMap* tm, uint32_t bar, int c0, int c1, int c2, int c3, int c4) {
  asm volatile(
      "cp.async.bulk.tensor.5d.shared::cluster.global.mbarrier::complete_tx::bytes [%0], [%1, {%3, %4, %5, %6, %7}], [%2];"
      ::"r"(dst), "l"(tm), "r"(bar), "r"(c0), "r"(c1), "r"(c2), "r"(c3), "r"(c4)
      : "memory");
}
DEVI uint64_t policy_evict_first() {
  uint64_t p;
  asm("createpolicy.fractional.L2::evict_first.b64 %0, 1.0;" : "=l"(p));
  return p;
}
DEVI void bulk_load_hint(uint32_t dst, const void* src, uint32_t bytes, uint32_t bar, uint64_t pol) {
  asm volatile("cp.async.bulk.shared::cluster.global.mbarrier::complete_tx::bytes.L2::cache_hint [%0], [%1], %2, [%3], %4;"
               ::"r"(dst), "l"(src), "r"(bytes), "r"(bar), "l"(pol) : "memory");
}
DEVI void prefetch_map(const CUtensorMap* tm) {
  asm volatile("prefetch.tensormap [%0];" ::"l"(tm) : "memory");
}
DEVI void tma_prefetch_5d(const CUtensorMap* tm, int c0, int c1, int c2, int c3, int c4) {
  asm volatile("cp.async.bulk.prefetch.tensor.5d.L2.global [%0, {%1, %2, %3, %4, %5}];"
               ::"l"(tm), "r"(c0), "r"(c1), "r"(c2), "r"(c3), "r"(c4)
               : "memory");
}
DEVI void bulk_load(uint32_t dst, const void* src, uint32_t bytes, uint32_t bar) {
  asm volatile("cp.async.bulk.shared::cluster.global.mbarrier::complete_tx::bytes [%0], [%1], %2, [%3];"
               ::"r"(dst), "l"(src), "r"(bytes), "r"(bar) : "memory");
}
DEVI void bulk_store(void* dst, uint32_t src, uint32_t bytes) {
  asm volatile("cp.async.bulk.global.shared::cta.bulk_group [%0], [%1], %2;" ::"l"(dst), "r"(src), "r"(bytes) : "memory");
}
DEVI void bulk_commit() { asm volatile("cp.async.bulk.commit_group;" ::: "memory"); }
template <int N>
DEVI void bulk_wait() { asm volatile("cp.async.bulk.wait_group %0;" ::"n"(N) : "memory"); }

template <int N>
DEVI void reg_dec() { asm volatile("setmaxnreg.dec.sync.aligned.u32 %0;" ::"n"(N)); }
template <int N>
DEVI void reg_inc() { asm volatile("setmaxnreg.inc.sync.aligned.u32 %0;" ::"n"(N)); }

DEVI void wg_fence() { asm volatile("wgmma.fence.sync.aligned;" ::: "memory"); }
DEVI void wg_commit() { asm volatile("wgmma.commit_group.sync.aligned;" ::: "memory"); }
template <int N>
DEVI void wg_wait() { asm volatile("wgmma.wait_group.sync.aligned %0;" ::"n"(N) : "memory"); }
template <int N>
DEVI void fence_regs(float (&d)[N]) {
#pragma unroll
  for (int i = 0; i < N; i++) asm volatile("" : "+f"(d[i])::"memory");
}

DEVI uint64_t make_desc(uint32_t addr, uint32_t lbo, uint32_t sbo, uint32_t swz) {
  return (uint64_t)((addr & 0x3FFFFu) >> 4) | ((uint64_t)((lbo & 0x3FFFFu) >> 4) << 16) |
         ((uint64_t)((sbo & 0x3FFFFu) >> 4) << 32) | ((uint64_t)swz << 62);
}

DEVI uint64_t desc64(uint32_t lo, uint32_t hi) {
  uint64_t d;
  asm("mov.b64 %0, {%1, %2};" : "=l"(d) : "r"(lo), "r"(hi));
  return d;
}
DEVI uint32_t pack_bf16(float lo, float hi) {
  uint32_t r;
  asm("cvt.rn.bf16x2.f32 %0, %1, %2;" : "=r"(r) : "f"(hi), "f"(lo));
  return r;
}
DEVI float ex2(float x) {
  float r;
  asm("ex2.approx.ftz.f32 %0, %1;" : "=f"(r) : "f"(x));
  return r;
}
DEVI float rcp_approx(float x) {
  float r;
  asm("rcp.approx.ftz.f32 %0, %1;" : "=f"(r) : "f"(x));
  return r;
}
DEVI uint32_t movmatrix_t(uint32_t a) {
  uint32_t r;
  asm("movmatrix.sync.aligned.m8n8.trans.b16 %0, %1;" : "=r"(r) : "r"(a));
  return r;
}
DEVI void ldmatrix_x4(uint32_t (&r)[4], uint32_t addr) {
  asm volatile("ldmatrix.sync.aligned.m8n8.x4.shared.b16 {%0, %1, %2, %3}, [%4];"
               : "=r"(r[0]), "=r"(r[1]), "=r"(r[2]), "=r"(r[3]) : "r"(addr) : "memory");
}
DEVI void ldmatrix_x4(uint32_t& r0, uint32_t& r1, uint32_t& r2, uint32_t& r3, uint32_t addr) {
  asm volatile("ldmatrix.sync.aligned.m8n8.x4.shared.b16 {%0, %1, %2, %3}, [%4];"
               : "=r"(r0), "=r"(r1), "=r"(r2), "=r"(r3) : "r"(addr) : "memory");
}
DEVI void ldmatrix_x2(uint32_t& r0, uint32_t& r1, uint32_t addr) {
  asm volatile("ldmatrix.sync.aligned.m8n8.x2.shared.b16 {%0, %1}, [%2];"
               : "=r"(r0), "=r"(r1) : "r"(addr) : "memory");
}
DEVI void ldmatrix_x4_t(uint32_t (&r)[4], uint32_t addr) {
  asm volatile("ldmatrix.sync.aligned.m8n8.x4.trans.shared.b16 {%0, %1, %2, %3}, [%4];"
               : "=r"(r[0]), "=r"(r[1]), "=r"(r[2]), "=r"(r[3]) : "r"(addr) : "memory");
}
DEVI void stmatrix_x4(uint32_t addr, uint32_t r0, uint32_t r1, uint32_t r2, uint32_t r3) {
  asm volatile("stmatrix.sync.aligned.m8n8.x4.shared.b16 [%0], {%1, %2, %3, %4};"
               ::"r"(addr), "r"(r0), "r"(r1), "r"(r2), "r"(r3) : "memory");
}
DEVI void stmatrix_x4_t(uint32_t addr, uint32_t r0, uint32_t r1, uint32_t r2, uint32_t r3) {
  asm volatile("stmatrix.sync.aligned.m8n8.x4.trans.shared.b16 [%0], {%1, %2, %3, %4};"
               ::"r"(addr), "r"(r0), "r"(r1), "r"(r2), "r"(r3) : "memory");
}
DEVI void mma16816(float (&d)[4], const uint32_t (&a)[4], uint32_t b0, uint32_t b1) {
  asm volatile("mma.sync.aligned.m16n8k16.row.col.f32.bf16.bf16.f32 {%0, %1, %2, %3}, {%4, %5, %6, %7}, {%8, %9}, {%0, %1, %2, %3};"
               : "+f"(d[0]), "+f"(d[1]), "+f"(d[2]), "+f"(d[3])
               : "r"(a[0]), "r"(a[1]), "r"(a[2]), "r"(a[3]), "r"(b0), "r"(b1));
}
DEVI void mma16816_z(float (&d)[4], const uint32_t (&a)[4], uint32_t b0, uint32_t b1) {
  asm volatile("mma.sync.aligned.m16n8k16.row.col.f32.bf16.bf16.f32 {%0, %1, %2, %3}, {%4, %5, %6, %7}, {%8, %9}, {%10, %10, %10, %10};"
               : "=f"(d[0]), "=f"(d[1]), "=f"(d[2]), "=f"(d[3])
               : "r"(a[0]), "r"(a[1]), "r"(a[2]), "r"(a[3]), "r"(b0), "r"(b1), "f"(0.f));
}
DEVI void mma16816_c(float (&d)[4], const uint32_t (&a)[4], uint32_t b0, uint32_t b1, const float (&c)[4]) {
  asm volatile("mma.sync.aligned.m16n8k16.row.col.f32.bf16.bf16.f32 {%0, %1, %2, %3}, {%4, %5, %6, %7}, {%8, %9}, {%10, %11, %12, %13};"
               : "=f"(d[0]), "=f"(d[1]), "=f"(d[2]), "=f"(d[3])
               : "r"(a[0]), "r"(a[1]), "r"(a[2]), "r"(a[3]), "r"(b0), "r"(b1), "f"(c[0]), "f"(c[1]), "f"(c[2]), "f"(c[3]));
}
template <int BIT>
DEVI void sel2(uint32_t mask, float& r0, float& r1, float a0, float a1, float b0, float b1) {
  asm("{\n.reg .pred p;\n.reg .b32 t;\nand.b32 t, %2, %7;\nsetp.ne.b32 p, t, 0;\nselp.f32 %0, %3, %5, p;\nselp.f32 %1, %4, %6, p;\n}"
      : "=f"(r0), "=f"(r1) : "r"(mask), "f"(a0), "f"(a1), "f"(b0), "f"(b1), "n"(BIT));
}
template <int BIT>
DEVI void split2(uint32_t mask, uint32_t& r0, uint32_t& r1, uint32_t v) {
  asm("{\n.reg .pred p;\n.reg .b32 t;\nand.b32 t, %2, %4;\nsetp.ne.b32 p, t, 0;\nselp.b32 %0, %3, 0, p;\nselp.b32 %1, 0, %3, p;\n}"
      : "=r"(r0), "=r"(r1) : "r"(mask), "r"(v), "n"(BIT));
}
DEVI void stg32_if(uint32_t* p, uint32_t v, bool on) {
  asm volatile("{\n.reg .pred q;\nsetp.ne.u32 q, %2, 0;\n@q st.global.u32 [%0], %1;\n}" ::"l"(p), "r"(v), "r"((uint32_t)on) : "memory");
}
DEVI uint4 ldg128(const void* p) {
  uint4 v;
  asm volatile("ld.global.nc.v4.u32 {%0, %1, %2, %3}, [%4];" : "=r"(v.x), "=r"(v.y), "=r"(v.z), "=r"(v.w) : "l"(p));
  return v;
}
DEVI uint32_t ld_acquire(const uint32_t* p) {
  uint32_t v;
  asm volatile("ld.acquire.gpu.global.u32 %0, [%1];" : "=r"(v) : "l"(p) : "memory");
  return v;
}
DEVI uint32_t ld_relaxed(const uint32_t* p) {
  uint32_t v;
  asm volatile("ld.relaxed.gpu.global.u32 %0, [%1];" : "=r"(v) : "l"(p) : "memory");
  return v;
}
DEVI void st_relaxed(uint32_t* p, uint32_t v) {
  asm volatile("st.relaxed.gpu.global.u32 [%0], %1;" ::"l"(p), "r"(v) : "memory");
}
DEVI void red_max_release(uint32_t* p, uint32_t v) {
  asm volatile("red.release.gpu.global.max.u32 [%0], %1;" ::"l"(p), "r"(v) : "memory");
}
DEVI void fence_gpu() { asm volatile("fence.acq_rel.gpu;" ::: "memory"); }
DEVI uint32_t lds32(uint32_t addr) {
  uint32_t v;
  asm volatile("ld.shared.u32 %0, [%1];" : "=r"(v) : "r"(addr) : "memory");
  return v;
}
DEVI uint32_t atom_inc_shared(uint32_t addr) {
  uint32_t v;
  asm volatile("atom.shared.add.u32 %0, [%1], 1;" : "=r"(v) : "r"(addr) : "memory");
  return v;
}
DEVI void sts32(uint32_t addr, uint32_t v) {
  asm volatile("st.shared.u32 [%0], %1;" ::"r"(addr), "r"(v) : "memory");
}
DEVI void sts128(uint32_t addr, uint4 v) {
  asm volatile("st.shared.v4.u32 [%0], {%1, %2, %3, %4};" ::"r"(addr), "r"(v.x), "r"(v.y), "r"(v.z), "r"(v.w) : "memory");
}
DEVI void named_bar_arrive(int id, int n) { asm volatile("bar.arrive %0, %1;" ::"r"(id), "r"(n) : "memory"); }
DEVI void named_bar_sync(int id, int n) { asm volatile("bar.sync %0, %1;" ::"r"(id), "r"(n) : "memory"); }
DEVI void fence_proxy_async() { asm volatile("fence.proxy.async.shared::cta;" ::: "memory"); }
DEVI void fence_proxy_async_global() { asm volatile("fence.proxy.async.global;" ::: "memory"); }
DEVI int clampi(int v, int lo, int hi) { return v < lo ? lo : (v > hi ? hi : v); }

template <int TA, int TB> DEVI void wgmma_m64n144k16_ss(float (&d)[72], uint64_t descA, uint64_t descB, int scaleD) {
  asm volatile("{\n.reg .pred p;\nsetp.ne.b32 p, %74, 0;\nwgmma.mma_async.sync.aligned.m64n144k16.f32.bf16.bf16 {%0, %1, %2, %3, %4, %5, %6, %7, %8, %9, %10, %11, %12, %13, %14, %15, %16, %17, %18, %19, %20, %21, %22, %23, %24, %25, %26, %27, %28, %29, %30, %31, %32, %33, %34, %35, %36, %37, %38, %39, %40, %41, %42, %43, %44, %45, %46, %47, %48, %49, %50, %51, %52, %53, %54, %55, %56, %57, %58, %59, %60, %61, %62, %63, %64, %65, %66, %67, %68, %69, %70, %71}, %72, %73, p, 1, 1, %75, %76;\n}\n"
    : "+f"(d[0]), "+f"(d[1]), "+f"(d[2]), "+f"(d[3]), "+f"(d[4]), "+f"(d[5]), "+f"(d[6]), "+f"(d[7]), "+f"(d[8]), "+f"(d[9]), "+f"(d[10]), "+f"(d[11]), "+f"(d[12]), "+f"(d[13]), "+f"(d[14]), "+f"(d[15]), "+f"(d[16]), "+f"(d[17]), "+f"(d[18]), "+f"(d[19]), "+f"(d[20]), "+f"(d[21]), "+f"(d[22]), "+f"(d[23]), "+f"(d[24]), "+f"(d[25]), "+f"(d[26]), "+f"(d[27]), "+f"(d[28]), "+f"(d[29]), "+f"(d[30]), "+f"(d[31]), "+f"(d[32]), "+f"(d[33]), "+f"(d[34]), "+f"(d[35]), "+f"(d[36]), "+f"(d[37]), "+f"(d[38]), "+f"(d[39]), "+f"(d[40]), "+f"(d[41]), "+f"(d[42]), "+f"(d[43]), "+f"(d[44]), "+f"(d[45]), "+f"(d[46]), "+f"(d[47]), "+f"(d[48]), "+f"(d[49]), "+f"(d[50]), "+f"(d[51]), "+f"(d[52]), "+f"(d[53]), "+f"(d[54]), "+f"(d[55]), "+f"(d[56]), "+f"(d[57]), "+f"(d[58]), "+f"(d[59]), "+f"(d[60]), "+f"(d[61]), "+f"(d[62]), "+f"(d[63]), "+f"(d[64]), "+f"(d[65]), "+f"(d[66]), "+f"(d[67]), "+f"(d[68]), "+f"(d[69]), "+f"(d[70]), "+f"(d[71])
    : "l"(descA), "l"(descB), "r"(scaleD), "n"(TA), "n"(TB));
}

template <int TB> DEVI void wgmma_m64n64k16_rs(float (&d)[32], uint32_t a0, uint32_t a1, uint32_t a2, uint32_t a3, uint64_t descB, int scaleD) {
  asm volatile("{\n.reg .pred p;\nsetp.ne.b32 p, %37, 0;\nwgmma.mma_async.sync.aligned.m64n64k16.f32.bf16.bf16 {%0, %1, %2, %3, %4, %5, %6, %7, %8, %9, %10, %11, %12, %13, %14, %15, %16, %17, %18, %19, %20, %21, %22, %23, %24, %25, %26, %27, %28, %29, %30, %31}, {%32, %33, %34, %35}, %36, p, 1, 1, %38;\n}\n"
    : "+f"(d[0]), "+f"(d[1]), "+f"(d[2]), "+f"(d[3]), "+f"(d[4]), "+f"(d[5]), "+f"(d[6]), "+f"(d[7]), "+f"(d[8]), "+f"(d[9]), "+f"(d[10]), "+f"(d[11]), "+f"(d[12]), "+f"(d[13]), "+f"(d[14]), "+f"(d[15]), "+f"(d[16]), "+f"(d[17]), "+f"(d[18]), "+f"(d[19]), "+f"(d[20]), "+f"(d[21]), "+f"(d[22]), "+f"(d[23]), "+f"(d[24]), "+f"(d[25]), "+f"(d[26]), "+f"(d[27]), "+f"(d[28]), "+f"(d[29]), "+f"(d[30]), "+f"(d[31])
    : "r"(a0), "r"(a1), "r"(a2), "r"(a3), "l"(descB), "r"(scaleD), "n"(TB));
}

template <int TA, int TB> DEVI void wgmma_m64n96k16_ss(float (&d)[48], uint64_t descA, uint64_t descB, int scaleD) {
  asm volatile("{\n.reg .pred p;\nsetp.ne.b32 p, %50, 0;\nwgmma.mma_async.sync.aligned.m64n96k16.f32.bf16.bf16 {%0, %1, %2, %3, %4, %5, %6, %7, %8, %9, %10, %11, %12, %13, %14, %15, %16, %17, %18, %19, %20, %21, %22, %23, %24, %25, %26, %27, %28, %29, %30, %31, %32, %33, %34, %35, %36, %37, %38, %39, %40, %41, %42, %43, %44, %45, %46, %47}, %48, %49, p, 1, 1, %51, %52;\n}\n"
    : "+f"(d[0]), "+f"(d[1]), "+f"(d[2]), "+f"(d[3]), "+f"(d[4]), "+f"(d[5]), "+f"(d[6]), "+f"(d[7]), "+f"(d[8]), "+f"(d[9]), "+f"(d[10]), "+f"(d[11]), "+f"(d[12]), "+f"(d[13]), "+f"(d[14]), "+f"(d[15]), "+f"(d[16]), "+f"(d[17]), "+f"(d[18]), "+f"(d[19]), "+f"(d[20]), "+f"(d[21]), "+f"(d[22]), "+f"(d[23]), "+f"(d[24]), "+f"(d[25]), "+f"(d[26]), "+f"(d[27]), "+f"(d[28]), "+f"(d[29]), "+f"(d[30]), "+f"(d[31]), "+f"(d[32]), "+f"(d[33]), "+f"(d[34]), "+f"(d[35]), "+f"(d[36]), "+f"(d[37]), "+f"(d[38]), "+f"(d[39]), "+f"(d[40]), "+f"(d[41]), "+f"(d[42]), "+f"(d[43]), "+f"(d[44]), "+f"(d[45]), "+f"(d[46]), "+f"(d[47])
    : "l"(descA), "l"(descB), "r"(scaleD), "n"(TA), "n"(TB));
}

constexpr int kS = 112;
constexpr int kStripCtas = 112;
constexpr int kProjCtas = 20;
constexpr int kThreads = 512;
constexpr int kArr = 29;
constexpr int kExch = 27;
constexpr int kSteps = 28;
constexpr int kTiles = kSteps * 28;
constexpr int kOTileBytes = 64 * 192 * 2;
constexpr int kTailBands = 7;
constexpr int kTail0 = kSteps - kTailBands;
constexpr int kProjTiles = (kSteps - kTailBands) * 28;
constexpr int kHaloBytes = 3 * 784 - 16, kHaloPitch = 2432;

__device__ __align__(1024) uint8_t g_o[(size_t)kTiles * kOTileBytes];
constexpr int kHaloRing = 10;
constexpr int kHaloBlock = (2 * kHaloRing + 1) * kHaloPitch;
__device__ __align__(1024) uint8_t g_halo[(size_t)kStripCtas * kHaloBlock];
__device__ __align__(1024) uint8_t g_wop[4 * 3 * 192 * 32];
__device__ uint32_t g_oflag[28 * 32];
__device__ uint32_t g_wflag[4 * 32];
__device__ uint32_t g_epoch[kProjCtas * 32];

DEVI uint32_t* halo_flags(int cta) {
  return reinterpret_cast<uint32_t*>(g_halo + (size_t)cta * kHaloBlock + 2 * kHaloRing * kHaloPitch);
}
DEVI const uint8_t* o_tile(int g, int ps) { return g_o + (size_t)(ps * kSteps + g) * kOTileBytes; }

namespace ka {
constexpr int kWAtom = 192 * 32;
constexpr int kWBytes = 9 * kWAtom;
constexpr int kXBytes = 64 * 384;
constexpr int kCol = 784;
constexpr int kQCol = 400;
constexpr int kSlot = 22 * kCol;
constexpr int kQSlot = 16 * kQCol;
constexpr int kQOff = 5 * kSlot + 32;
constexpr int kOffX = kWBytes;
constexpr int kOffRing = kOffX + 2 * kXBytes;
constexpr int kOffBar = kOffRing + kQOff + 6 * kQSlot;
constexpr int kOffStage = kOffX, kOffWo = kOffX + 2 * kWAtom;
constexpr int kOffDummy = kOffBar + 896;
DEVI uint32_t tail_buf(int i) { return i < 2 ? i * kOTileBytes : kOffRing + (i - 2) * 2 * kSlot; }
constexpr int kLastBytes = 3 * (16 + 2 * 15) * 128;
constexpr int kBarX = 0, kBarFull = 256, kBarO = 512, kBarT = 768, kBarOwn = 832, kBarJunk = 896;
constexpr int kSmemBytes = kOffBar + 896 + 704;
constexpr int kD = 6;
static_assert(kTailBands <= 8, "buffers");
constexpr int kShift = kArr - kD + 1;
constexpr int kNbInit = 0, kNbMisc = 1, kNbBurst = 2, kNbTile = 7, kNbFirst = 13, kNbX = 14;
}

namespace kb {
constexpr int kWoBlk = 192 * 128;
constexpr int kStages = 6;
constexpr int kOffA = 3 * kWoBlk;
constexpr int kOffBar = kOffA + kStages * kOTileBytes;
constexpr int kSmemBytes = kOffBar + 192;
}

constexpr int kSmemBytes = ka::kSmemBytes > kb::kSmemBytes ? ka::kSmemBytes : kb::kSmemBytes;
static_assert(kSmemBytes <= 232448, "smem");

#define TRACE(idx)
#define GT(i)
#define ATRACE(k)
#define TRBASE (sbase + kTraceOff)

DEVI void mbar_wait_sleep(uint32_t bar, uint32_t parity) {
  uint32_t it = 0;
  while (!mbar_test_wait(bar, parity)) {
    __nanosleep(200);
    if (++it > LIMIT) { BAIL(bar & 0xfffff); break; }
  }
}

DEVI void publish_fence() {
  fence_proxy_async_global();
  fence_gpu();
}

DEVI uint32_t sched_fence() {
  uint32_t t;
  asm volatile("mov.u32 %0, %clock;" : "=r"(t)::"memory");
  return t;
}

struct AttnState {
  uint32_t kf[5][3][4];
  uint32_t vf[5][3][4];
  float bias[5][4];
  uint32_t p[5][2];
  uint32_t kaddr, vaddr, qaddr, bar, junk, fence;
  uint32_t ones[4];
  bool rdy;
  uint32_t pm;
  uint32_t* optr;
};

DEVI void store_o(AttnState& s, float (&o)[3][4], float i0, float i1, bool on) {
#pragma unroll
  for (int mt = 0; mt < 3; mt++) {
    stg32_if(s.optr + (2 * mt) * 32, pack_bf16(o[mt][0] * i0, o[mt][1] * i1), on);
    stg32_if(s.optr + (2 * mt + 1) * 32, pack_bf16(o[mt][2] * i0, o[mt][3] * i1), on);
  }
  s.optr += kOTileBytes / 4;
}

template <int PH>
DEVI void attn_step(AttnState& s, int g, int warp, const __nv_bfloat16* __restrict__ rpb) {
  using namespace ka;
  constexpr int R = (2 * PH) % 5, N0 = (R + 3) % 5, N1 = (R + 4) % 5;
  constexpr int SL = ((PH + 1) % 5) * kSlot;
  if (PH == 0 && g == 0) {
    {
      const int lane = threadIdx.x & 31, qc0 = 16 * ((blockIdx.x >> 2) % 7) + 2 * warp;
      const int kc = clampi(qc0 - 3, 0, kS - 8) + (lane >> 2);
      const unsigned short* r = reinterpret_cast<const unsigned short*>(rpb) + (blockIdx.x & 3) * 169 + (3 - (lane & 3)) * 13 + kc - qc0 + 6;
      const int sw0 = clampi(qc0 - 3, 0, kS - 7), sw1 = clampi(qc0 - 2, 0, kS - 7);
      const bool ok0 = kc >= sw0 && kc < sw0 + 7, ok1 = kc >= sw1 && kc < sw1 + 7;
#pragma unroll
      for (int i = 0; i < 10; i++) {
        const uint32_t v0 = ok0 ? (uint32_t)__ldg(r + i * 13) : 0xFF80u;
        const uint32_t v1 = ok1 ? (uint32_t)__ldg(r + i * 13 - 1) : 0xFF80u;
        s.bias[i >> 1][2 * (i & 1)] = __uint_as_float(v0 << 16) * 6.928203230275509f;
        s.bias[i >> 1][2 * (i & 1) + 1] = __uint_as_float(v1 << 16) * 6.928203230275509f;
      }
    }
    named_bar_sync(kNbMisc, 384);
    mbar_wait(s.bar + kBarFull, 0);
#pragma unroll
    for (int k = 0; k < 3; k++) {
      ldmatrix_x4(s.kf[1][k], s.kaddr + k * 32);
      ldmatrix_x4(s.kf[2][k], s.kaddr + 384 + k * 32);
      ldmatrix_x4_t(s.vf[1][k], s.vaddr + k * 32);
      ldmatrix_x4_t(s.vf[2][k], s.vaddr + 384 + k * 32);
      s.vf[0][k][0] = s.vf[0][k][1] = s.vf[0][k][2] = s.vf[0][k][3] = 0u;
    }
    named_bar_arrive(kNbFirst, 384);
    s.rdy = false;
    s.pm = (s.pm << 8) | (s.pm & 64);
  }
  if (!s.rdy) {
    mbar_wait(s.bar + kBarFull + 8 * (g + 1), 0);
    if (PH == 1 && g == 1) s.pm >>= 8;
    if (PH == 2 && g == kSteps - 1) s.pm |= 0x3Fu;
    if (PH == kShift % 5 && g == kShift && warp >= 4) {
      const uint32_t t0 = sched_fence();
      while (sched_fence() - t0 < 200) {}
    }
  }
  ATRACE(0);
  float t[5][4], o[3][4], z[4];
  uint32_t q[6];
  ldmatrix_x4(q[0], q[1], q[2], q[3], s.qaddr);
  ldmatrix_x2(q[4], q[5], s.qaddr + 64);
#define LDK(ks) { ldmatrix_x4(s.kf[N0][ks], s.kaddr + SL + (ks) * 32); ldmatrix_x4(s.kf[N1][ks], s.kaddr + SL + 384 + (ks) * 32); }
#define LDV(n) ldmatrix_x4_t(s.vf[(n) < 3 ? N0 : N1][(n) % 3], s.vaddr + SL + ((n) / 3) * 384 + ((n) % 3) * 32);
#define PV(i) { _Pragma("unroll") for (int mt = 0; mt < 3; mt++) { \
                  if ((i) == 0) mma16816_z(o[mt], s.vf[N0][mt], s.p[0][0], s.p[0][1]); \
                  else mma16816(o[mt], s.vf[(R + 3 + (i)) % 5][mt], s.p[i][0], s.p[i][1]); } \
                if ((i) == 0) mma16816_z(z, s.ones, s.p[0][0] | s.p[4][0], s.p[0][1] | s.p[4][1]); \
                else if ((i) < 4) mma16816(z, s.ones, s.p[i][0], s.p[i][1]); }
#define QK(ks) { _Pragma("unroll") for (int i = 0; i < 5; i++) { \
                   if ((ks) == 0) mma16816_c(t[i], s.kf[(R + i) % 5][0], q[0], q[1], s.bias[i]); \
                   else mma16816(t[i], s.kf[(R + i) % 5][ks], q[2 * (ks)], q[2 * (ks) + 1]); } }
#define FN(x) x = sched_fence();
  uint32_t f0 = 0, f1;
  if (PH == 1) {
    LDK(0) PV(0) PV(1) PV(2) FN(f0) LDK(1) LDK(2) PV(3) PV(4) FN(f1)
    LDV(5) LDV(4) LDV(3) LDV(2) LDV(1) LDV(0) QK(0) QK(1) QK(2)
  } else if (PH == 2) {
    LDK(0) LDK(1) LDK(2) PV(0) PV(1) PV(2) FN(f1)
    LDV(5) LDV(4) LDV(3) PV(3) PV(4) FN(f0) LDV(2) LDV(1) LDV(0) QK(0) QK(1) QK(2)
  } else {
    LDK(0) LDK(1) LDK(2) PV(0) PV(1) PV(2) PV(3) PV(4) FN(f1)
    LDV(5) LDV(4) LDV(3) LDV(2) LDV(1) LDV(0) QK(0) QK(1) QK(2)
  }
#undef LDK
#undef LDV
#undef PV
#undef QK
#undef FN
  const uint32_t f2 = sched_fence();
  named_bar_arrive(kNbBurst + (PH + kD) % 5, 384);
  const uint32_t fo = s.fence;
  s.fence = sched_fence();
  ATRACE(1);
  const uint32_t pm = s.pm;
  float x[7][2];
  sel2<1>(pm, x[0][0], x[0][1], t[0][0], t[0][1], t[3][2], t[3][3]);
  sel2<2>(pm, x[1][0], x[1][1], t[0][2], t[0][3], t[4][0], t[4][1]);
  sel2<4>(pm, x[2][0], x[2][1], t[1][0], t[1][1], t[4][2], t[4][3]);
#pragma unroll
  for (int e = 0; e < 2; e++) {
    x[3][e] = t[1][2 + e]; x[4][e] = t[2][e]; x[5][e] = t[2][2 + e]; x[6][e] = t[3][e];
  }
  float m0 = fmaxf(fmaxf(fmaxf(x[0][0], x[1][0]), fmaxf(x[2][0], x[3][0])), fmaxf(fmaxf(x[4][0], x[5][0]), x[6][0]));
  float m1 = fmaxf(fmaxf(fmaxf(x[0][1], x[1][1]), fmaxf(x[2][1], x[3][1])), fmaxf(fmaxf(x[4][1], x[5][1]), x[6][1]));
#pragma unroll
  for (int d = 4; d <= 16; d <<= 1) {
    m0 = fmaxf(m0, __shfl_xor_sync(0xffffffffu, m0, d));
    m1 = fmaxf(m1, __shfl_xor_sync(0xffffffffu, m1, d));
  }
  {
    int nx = kBarFull + 8 * (g + 2);
    if (PH >= 3 && g < 0) nx = kBarOwn + 8 * warp;
    if ((PH == (kShift - 1) % 5 && g == kShift - 1) || (PH == 0 && g == 0) || (PH == 1 && g == kSteps - 2)) nx = kBarFull + 8 * 31;
    s.rdy = mbar_test_wait(s.bar + nx, 0);
  }
  const float c = 0.14433756729740643f * 1.4426950408889634f;
  const float n0 = -m0 * c, n1 = -m1 * c;
  uint32_t pt[7];
#pragma unroll
  for (int i = 0; i < 7; i++) {
    const float e0 = ex2(fmaf(x[i][0], c, n0)), e1 = ex2(fmaf(x[i][1], c, n1));
    pt[i] = movmatrix_t(pack_bf16(e0, e1));
  }
  split2<8>(pm, s.p[0][0], s.p[3][1], pt[0]);
  split2<16>(pm, s.p[0][1], s.p[4][0], pt[1]);
  split2<32>(pm, s.p[1][0], s.p[4][1], pt[2]);
  s.p[1][1] = pt[3]; s.p[2][0] = pt[4]; s.p[2][1] = pt[5]; s.p[3][0] = pt[6];
#pragma unroll
  for (int i = 0; i < 5; i++) asm volatile("" : "+r"(s.p[i][0]), "+r"(s.p[i][1])::"memory");
  const bool real = PH == 1 || PH == 2 || g > 0;
  store_o(s, o, rcp_approx(z[0]), rcp_approx(z[1]), real);
  __syncwarp();
  if ((s.pm & 64) && real) mbar_arrive(s.bar + kBarO + 8 * (g - 1));
  s.junk ^= fo ^ f0 ^ f1 ^ f2;
  s.qaddr += kQSlot;
  if (s.qaddr >= s.bar) s.qaddr -= 6 * kQSlot;
  asm volatile("" : "+r"(s.junk)::"memory");
  ATRACE(2);
}

__global__ void __launch_bounds__(kThreads, 1)
nat_kernel(const __nv_bfloat16* __restrict__ wqkv, const __nv_bfloat16* __restrict__ rpb,
           const __grid_constant__ CUtensorMap tm_x, const __grid_constant__ CUtensorMap tm_w,
           const __grid_constant__ CUtensorMap tm_h, const __grid_constant__ CUtensorMap tm_r,
           const __grid_constant__ CUtensorMap tm_wo, const __grid_constant__ CUtensorMap tm_out,
           const __grid_constant__ CUtensorMap tm_wo2, const __grid_constant__ CUtensorMap tm_o2) {
  extern __shared__ __align__(1024) uint8_t smem_raw[];
  const uint32_t sbase = smem_u32(smem_raw);
  if (sbase & 1023u) __trap();
  const int warp = __shfl_sync(0xffffffffu, (int)(threadIdx.x >> 5), 0), lane = threadIdx.x & 31;
  const int wg = warp >> 2, wl = warp & 3;
  const int cta = blockIdx.x;
  const bool strip_cta = cta < kStripCtas;
  const int head = cta & 3, ps = cta >> 2, par = ps / 7, strip = ps - 7 * par;
  if (threadIdx.x == 0) TRACE(0);

  if (threadIdx.x == 416) prefetch_map(strip_cta ? &tm_w : &tm_wo2);
  if (strip_cta && threadIdx.x == 384) {
    using namespace ka;
    const uint32_t bar = sbase + kOffBar;
    mbar_init(bar + kBarX, 1);
    mbar_expect_tx(bar + kBarX, kXBytes + 6 * kWAtom);
    tma_load_5d(sbase + kOffX, &tm_x, bar + kBarX, 0, 16 * strip, -1, 3 * (par & 1), par >> 1);
#pragma unroll
    for (int i = 3; i < 9; i++)
      tma_load_2d(sbase + i * kWAtom, &tm_w, bar + kBarX, (i / 3) * 192 + head * 48 + (i % 3) * 16, 0);
    TRACE(10);
  }
  __syncwarp();
  if (strip_cta && wg == 2 && threadIdx.x < 256 + 96) {
    using namespace ka;
    uint4 v[12];
    const int wk = ((int)threadIdx.x - 256) / 6, wu = (int)threadIdx.x - 256 - 6 * wk;
    const uint8_t* src = reinterpret_cast<const uint8_t*>(wqkv) + wk * 1152 + head * 96 + wu * 16;
#pragma unroll
    for (int i = 0; i < 12; i++) v[i] = ldg128(src + i * 16 * 1152);
    const uint32_t dst = sbase + (wu >> 1) * kWAtom + wk * 32 + (((wu ^ (wk >> 2)) & 1) << 4);
#pragma unroll
    for (int i = 0; i < 12; i++) sts128(dst + i * 16 * 32, v[i]);
    if (warp == 8) TRACE(6);
    fence_proxy_async();
  }
  if (threadIdx.x == 480) GT(0);

  if (strip_cta) {
    using namespace ka;
    const uint32_t bar = sbase + kOffBar, ring = sbase + kOffRing;
    const int tskip = (head ^ (head >> 1)) & 1, thalf = head >> 1;
    if (wg < 2) {
      reg_inc<184>();
      AttnState s;
      const int qc0 = 16 * strip + 2 * warp;
      const int kc0 = clampi(qc0 - 3, 0, kS - 8);
      const uint32_t colb = ring + (kc0 - (16 * strip - 3) + (lane & 7)) * kCol;
      s.kaddr = colb + ((lane >> 3) & 1) * 192 + (lane >> 4) * 16;
      s.vaddr = colb + 96 + (lane >> 4) * 192 + ((lane >> 3) & 1) * 16;
      {
        const int qr = (lane & 7) >> 1;
        const uint32_t qa = ring + kQOff + (2 * warp + (lane & 1)) * kQCol + (lane >> 3) * 16;
        s.qaddr = qa + (qr == 3 ? 5 * kQSlot : 4 * kQSlot + (qr + 1) * 96);
      }
      s.bar = bar;
      s.optr = reinterpret_cast<uint32_t*>(g_o + (size_t)ps * kSteps * kOTileBytes + head * 6144 + warp * 768) + lane - 3 * kOTileBytes / 4;
#pragma unroll
      for (int i = 0; i < 5; i++) {
        s.p[i][0] = s.p[i][1] = 0u;
        s.bias[i][0] = s.bias[i][1] = s.bias[i][2] = s.bias[i][3] = 0.f;
#pragma unroll
        for (int k = 0; k < 3; k++)
#pragma unroll
          for (int c = 0; c < 4; c++) s.kf[i][k][c] = s.vf[i][k][c] = 0u;
      }
      s.junk = s.fence = 0;
      s.rdy = true;
      if (lane == 0) {
        mbar_init(bar + kBarOwn + 8 * warp, 1);
        mbar_arrive(bar + kBarOwn + 8 * warp);
      }
      __syncwarp();
#pragma unroll
      for (int i = 0; i < 4; i++) s.ones[i] = 0x3F803F80u;
      s.pm = (7u << (lane & 3) & 7u) | ((7u << (lane >> 3) & 7u) << 3) | (lane == 0 ? 64u : 0u);
      s.pm = __shfl_sync(0xffffffffu, s.pm, lane);
      s.kaddr = __shfl_sync(0xffffffffu, s.kaddr, lane);
      s.vaddr = __shfl_sync(0xffffffffu, s.vaddr, lane);
#pragma unroll 1
      for (int g = -2; g < kSteps; g += 5) {
        attn_step<3>(s, g, warp, rpb);
        attn_step<4>(s, g + 1, warp, rpb);
        attn_step<0>(s, g + 2, warp, rpb);
        attn_step<1>(s, g + 3, warp, rpb);
        attn_step<2>(s, g + 4, warp, rpb);
      }
      {
        float o[3][4], z[4];
#pragma unroll
        for (int mt = 0; mt < 3; mt++) mma16816_z(o[mt], s.vf[4][mt], s.p[0][0], s.p[0][1]);
        mma16816_z(z, s.ones, s.p[0][0], s.p[0][1]);
#pragma unroll
        for (int i = 1; i < 5; i++) {
#pragma unroll
          for (int mt = 0; mt < 3; mt++) mma16816(o[mt], s.vf[i - 1][mt], s.p[i][0], s.p[i][1]);
          mma16816(z, s.ones, s.p[i][0], s.p[i][1]);
        }
        store_o(s, o, rcp_approx(z[0]), rcp_approx(z[1]), true);
        __syncwarp();
        if (lane == 0) mbar_arrive(bar + kBarO + 8 * (kSteps - 1));
      }
      s.junk ^= s.fence;
      if (s.junk == 0x9e3779b9u) sts32(bar + kBarJunk, 0);
      if (warp == 0) TRACE(1);
      if (threadIdx.x == 128) GT(3);
    } else if (wg == 2) {
      reg_dec<104>();
      const int col = ((lane >> 3) & 1) * 8 + (lane & 7);
      uint32_t kva = ring + (3 + col) * kCol + wl * 192 + (lane >> 4) * 16;
      uint32_t qa = ring + kQOff + col * kQCol + wl * 96 + (lane >> 4) * 16;
      const uint32_t alo = (uint32_t)make_desc(sbase + kOffX, 16, 1024, 1), blo = (uint32_t)make_desc(sbase, kWAtom, 256, 3);
      constexpr uint32_t ahi = (1u << 30) | (1024 >> 4), bhi = (3u << 30) | (256 >> 4);
      if (wl == 0) TRACE(2);
      uint32_t gj = 0, qprev = 0, qk[12];
#pragma unroll
      for (int j = 0; j < 12; j++) qk[j] = 0;
      int bid = kNbBurst, tid = kNbTile;
      named_bar_arrive(kNbBurst + (kD - 2) % 5, 384);
      named_bar_arrive(kNbBurst + (kD - 1) % 5, 384);
      named_bar_sync(kNbX, 160);
      if (wl == 0) TRACE(7);
      mbar_wait(bar + kBarX, 0);
      if (wl == 0) TRACE(16 + 0);
#pragma unroll 1
      for (int a = 0; a < kArr; a++) {
        float acc[72];
        const uint32_t al = alo + (a & 1) * (kXBytes >> 4);
        if (a >= kD) named_bar_sync(bid, 384);
        if (wl == 0) TRACE(16 + a * 4 + 1);
        wg_fence();
#pragma unroll
        for (int k = 0; k < 12; k++)
          wgmma_m64n144k16_ss<0, 1>(acc, desc64(al + (((k >> 2) * 8192 + (k & 3) * 32) >> 4), ahi), desc64(blo + k * 32, bhi), k != 0);
        wg_commit();
        const uint32_t gjv = sched_fence();
        gj ^= gjv;
        if (a > 0) {
#pragma unroll
          for (int j = 0; j < 3; j++) stmatrix_x4(qprev + j * 32, qk[4 * j], qk[4 * j + 1], qk[4 * j + 2], qk[4 * j + 3]);
          __syncwarp();
          if (lane == 0 && a - 1 < kExch) mbar_arrive(bar + kBarFull + 8 * (a - 1));
        }
        bid = bid == kNbBurst + 4 ? kNbBurst : bid + 1;
        if (a == 0) named_bar_sync(kNbInit, 256);
        const bool xok = mbar_test_wait(bar + kBarX + 8 * (a + 1), 0);
        if (a == kArr - 1 && wl != 0) {
          const int r = col / 3, c = col - 3 * r;
          qa = sbase + kOffDummy + lane * 16;
          kva = col < 15 && wl < 3 ? ring + ((kExch + (r >> 2)) % 5) * kSlot + ((wl - 1) * 19 + c) * kCol + (r & 3) * 192 + (lane >> 4) * 16
                                   : qa;
        }
        wg_wait<0>();
        fence_regs(acc);
        named_bar_arrive(kNbX + (a & 1), 160);
        if (a == 5) named_bar_sync(kNbFirst, 384);
        if (wl == 0) TRACE(16 + a * 4 + 2);
#pragma unroll
        for (int j = 3; j < 9; j++)
          stmatrix_x4(kva + (j - 3) * 32, pack_bf16(acc[8 * j + 0], acc[8 * j + 1]), pack_bf16(acc[8 * j + 2], acc[8 * j + 3]),
                      pack_bf16(acc[8 * j + 4], acc[8 * j + 5]), pack_bf16(acc[8 * j + 6], acc[8 * j + 7]));
#pragma unroll
        for (int j = 0; j < 12; j++) qk[j] = pack_bf16(acc[2 * j], acc[2 * j + 1]);
        qprev = qa;
        if (a < kExch) named_bar_arrive(tid, 160);
        tid = tid == kNbTile + 5 ? kNbTile : tid + 1;
        if (wl == 0) TRACE(16 + a * 4 + 3);
        if (!xok && a + 1 < kArr) mbar_wait(bar + kBarX + 8 * (a + 1), 0);
        if (wl == 0) TRACE(16 + (a + 1) * 4 + 0);
        kva += kSlot;
        if (kva >= ring + 5 * kSlot) kva -= 5 * kSlot;
        qa += kQSlot;
        if (qa >= bar) qa -= 6 * kQSlot;
      }
#pragma unroll
      for (int j = 0; j < 3; j++) stmatrix_x4(qprev + j * 32, qk[4 * j], qk[4 * j + 1], qk[4 * j + 2], qk[4 * j + 3]);
      __syncwarp();
      if (lane < kArr - kExch) mbar_arrive(bar + kBarFull + 8 * (kExch + lane));
      if (gj == 0x9e3779b9u) sts32(bar + kBarJunk, 0);
#pragma unroll 1
      for (int g = kArr - kD; g < kSteps - 1; g++) {
        named_bar_arrive(bid, 384);
        bid = bid == kNbBurst + 4 ? kNbBurst : bid + 1;
      }
      {
        const uint32_t wlo = (uint32_t)make_desc(sbase + kOffWo, kWAtom, 256, 3);
        const int n = lane & 7, j = 2 * wl + ((lane >> 3) & 1);
        const uint32_t sta = sbase + kOffStage + ((2 * j + (n & 1)) * 4 + (n >> 1)) * 96 + (lane >> 4) * 16;
        mbar_wait(bar + kBarX + 8 * kArr, 0);
        named_bar_sync(bid, 384);
        if (tskip) mbar_wait(bar + kBarO + 8 * (kSteps - 1), 0);
#pragma unroll 1
        for (int g = kTail0 + tskip, i = 0; g < kSteps; g += 2, i++) {
          float acc[48];
          mbar_wait(bar + kBarT + 8 * i, 0);
          if (wl == 0) TRACE(144 + i * 2);
          const uint32_t tlo = (uint32_t)make_desc(sbase + tail_buf(i), 128, 768, 0);
          wg_fence();
#pragma unroll
          for (int k = 0; k < 12; k++)
            wgmma_m64n96k16_ss<1, 1>(acc, desc64(tlo + (((k / 3) * 6144 + (k % 3) * 256) >> 4), 768 >> 4), desc64(wlo + k * 32, bhi), k != 0);
          wg_commit();
          if (threadIdx.x == 256) bulk_wait_read();
          named_bar_sync(kNbMisc, 128);
          wg_wait<0>();
          fence_regs(acc);
#pragma unroll
          for (int jp = 0; jp < 6; jp++)
            stmatrix_x4(sta + (jp / 3) * kWAtom + (jp % 3) * 32, pack_bf16(acc[8 * jp + 0], acc[8 * jp + 1]),
                        pack_bf16(acc[8 * jp + 2], acc[8 * jp + 3]), pack_bf16(acc[8 * jp + 4], acc[8 * jp + 5]),
                        pack_bf16(acc[8 * jp + 6], acc[8 * jp + 7]));
          fence_proxy_async();
          named_bar_sync(kNbMisc, 128);
          if (threadIdx.x == 256) {
            tma_store_5d(&tm_out, sbase + kOffStage, thalf * 96, 4 * g, 16 * strip, par & 1, par >> 1);
            tma_store_5d(&tm_out, sbase + kOffStage + kWAtom, thalf * 96 + 48, 4 * g, 16 * strip, par & 1, par >> 1);
            bulk_commit();
          }
          __syncwarp();
          if (wl == 0) TRACE(145 + i * 2);
        }
        if (threadIdx.x == 256) {
          bulk_wait<0>();
          GT(2);
        }
      }
    } else {
      reg_dec<40>();
      if (wl == 0) named_bar_arrive(kNbX, 160);
      if (lane == 0) {
        const uint32_t b0 = bar + 64 * wl;
        if (wl == 1 && head == 1) tma_prefetch_5d(&tm_x, 0, 16 * strip, 3, 3 * (par & 1), par >> 1);
#pragma unroll
        for (int i = 0; i < 64; i += 8) {
          if (i || wl) mbar_init(b0 + kBarX + i, 1);
          mbar_init(b0 + kBarFull + i, wl < 3 || i < 8 * (kExch - 24) ? 6 : 4);
          mbar_init(b0 + kBarO + i, 8);
          if (wl == 0 && i < 32) mbar_init(b0 + kBarT + i, 1);
        }
#pragma unroll
        for (int i = 0; i < 64; i += 8) {
          if (i || wl)
            mbar_expect_tx(b0 + kBarX + i, wl < 3 || i < 32 ? kXBytes : (i == 32 ? kLastBytes : 6 * kWAtom));
          if (wl == 0 && i < 32) mbar_expect_tx(bar + kBarT + i, kOTileBytes);
        }
        fence_mbar_init();
        if (wl == 0) {
          tma_load_5d(sbase + kOffX + kXBytes, &tm_x, bar + kBarX + 8, 0, 16 * strip, 3, 3 * (par & 1), par >> 1);
          tma_prefetch_5d(&tm_x, 0, 16 * strip, 4 * (2 + ((head - 2) & 3)) - 1, 3 * (par & 1), par >> 1);
          TRACE(5);
        }
      }
      __syncwarp();
      const uint32_t ep = ld_relaxed(halo_flags(cta) + 32 + wl) * 32u;
      named_bar_arrive(kNbMisc, 384);
      named_bar_sync(kNbInit, 256);
      if (wl == 0) {
#pragma unroll 1
        for (int a = 2; a < kArr - 1; a++) {
          named_bar_sync(kNbX + (a & 1), 160);
          if (lane == 0) {
            tma_load_5d(sbase + kOffX + (a & 1) * kXBytes, &tm_x, bar + kBarX + 8 * a, 0, 16 * strip, 4 * a - 1,
                        3 * (par & 1), par >> 1);
            if (a == 20) {
              prefetch_map(&tm_h);
              prefetch_map(&tm_r);
              prefetch_map(&tm_out);
            }
            const int ap = a + 4;
            if (ap < kArr && (ap & 3) == head) tma_prefetch_5d(&tm_x, 0, 16 * strip, 4 * ap - 1, 3 * (par & 1), par >> 1);
          }
          __syncwarp();
        }
        named_bar_sync(kNbX, 160);
        if (lane < 9) {
          const int kb = lane / 3, w = lane - 3 * kb;
          tma_load_5d(sbase + kOffX + kb * 8192 + w * 2048, w == 0 ? &tm_r : &tm_h, bar + kBarX + 8 * (kArr - 1), 0,
                      16 * strip + (w == 0 ? 0 : (w == 1 ? -3 : 16)), w == 0 ? kS - 1 : 4 * kExch - 1, 3 * (par & 1) + kb, par >> 1);
        }
        {
          uint32_t it = 0;
          while (!__all_sync(0xffffffffu, (int)(ld_acquire(&g_wflag[(lane & 3) * 32]) - (ep + 1)) >= 0))
            if (++it > LIMIT) { BAIL(0x5000000); break; }
        }
        const uint8_t* wsrc = g_wop + thalf * 6 * kWAtom;
        named_bar_sync(kNbX + 1, 160);
        if (lane == 0) bulk_load(sbase + kOffWo + 2 * kWAtom, wsrc + 2 * kWAtom, 4 * kWAtom, bar + kBarX + 8 * kArr);
        uint32_t seen = ld_acquire(&g_oflag[ps * 32 + (lane & 3)]);
        named_bar_sync(kNbX, 160);
        if (lane == 0) bulk_load(sbase + kOffWo, wsrc, 2 * kWAtom, bar + kBarX + 8 * kArr);
#pragma unroll 1
        for (int g = kTail0 + tskip, i = 0; g < kSteps; g += 2, i++) {
          uint32_t it = 0;
          while (!__all_sync(0xffffffffu, (int)(seen - (ep + g + 1)) >= 0)) {
            seen = ld_acquire(&g_oflag[ps * 32 + (lane & 3)]);
            if (++it > LIMIT) { BAIL(0x3000000 + g); break; }
          }
          if (lane == 0)
            bulk_load(sbase + tail_buf(i), o_tile(g, ps), kOTileBytes, bar + kBarT + 8 * i);
          __syncwarp();
        }
      } else {
        const int p = wl - 1;
        const bool on = lane == 0 ? strip > 0 : strip < 6;
        const int nb = on ? cta + (lane == 0 ? -4 : 4) : cta;
        const uint32_t bytes = (strip > 0 && strip < 6) ? 2 * kHaloBytes : kHaloBytes;
        int slot = p, g = 0;
#pragma unroll 1
        for (int a = p; a < kExch; a += 3) {
          named_bar_sync(kNbTile + a % 6, 160);
          const uint32_t sl = ring + slot * kSlot;
          if (lane < 2) {
            fence_proxy_async();
            if (on) bulk_store(g_halo + (size_t)cta * kHaloBlock + (lane * kHaloRing + a % kHaloRing) * kHaloPitch, sl + (3 + 13 * lane) * kCol, kHaloBytes);
            bulk_commit();
          }
          __syncwarp();
          g += __ffs(~__ballot_sync(0xffffffffu, lane < 4 && mbar_test_wait(bar + kBarO + 8 * (g + lane), 0))) - 1;
          __syncwarp();
          if (lane < 2) {
            bulk_wait<0>();
            if (lane == 0) mbar_expect_tx(bar + kBarFull + 8 * a, bytes);
            else mbar_arrive(bar + kBarFull + 8 * a);
            TRACE(160 + a * 4 + 0);
            fence_proxy_async_global();
          }
          __syncwarp();
          if (lane < 3) red_max_release(lane < 2 ? halo_flags(cta) + 4 * lane + p : &g_oflag[ps * 32 + head], lane < 2 ? ep + a + 1 : ep + g);
          __syncwarp();
          TRACE(160 + a * 4 + 1);
          {
            const uint32_t* fl = halo_flags(nb) + 4 * ((lane & 1) ^ 1) + p;
            uint32_t it = 0;
            while (!__all_sync(0xffffffffu, !(lane < 2 && on) || (int)(ld_acquire(fl) - (ep + a + 1)) >= 0))
              if (++it > LIMIT) { BAIL(0x1000000 + a); break; }
          }
          TRACE(160 + a * 4 + 2);
          if (lane < 2 && on)
            bulk_load(sl + lane * 19 * kCol, g_halo + (size_t)nb * kHaloBlock + ((lane ^ 1) * kHaloRing + a % kHaloRing) * kHaloPitch,
                      kHaloBytes, bar + kBarFull + 8 * a);
          TRACE(160 + a * 4 + 3);
          __syncwarp();
          slot = slot >= 2 ? slot - 2 : slot + 3;
        }
        if (lane == 0) {
#pragma unroll 1
          for (g = kSteps - 7 + p; g < kSteps; g += 3) {
            if (g < kSteps - 3) mbar_wait_sleep(bar + kBarO + 8 * g, 0);
            else mbar_wait(bar + kBarO + 8 * g, 0);
            TRACE(370 + g * 2);
            fence_proxy_async_global();
            red_max_release(&g_oflag[ps * 32 + head], ep + g + 1);
            TRACE(371 + g * 2);
          }
          if (p == 0) GT(1);
        }
      }
      __syncwarp();
      if (lane == 0) st_relaxed(halo_flags(cta) + 32 + wl, (ep >> 5) + 1);
    }
  } else {
    using namespace kb;
    const uint32_t bar = sbase + kOffBar, sA = sbase + kOffA;
    const int k = cta - kStripCtas;
    if (wg < 3) {
      named_bar_sync(0, 512);
      uint32_t wf[12][4];
      mbar_wait(bar + 56, 0);
      {
        const int kr = (lane & 7) + ((lane >> 4) << 3);
        const uint32_t wa = sbase + wg * kWoBlk + kr * 128 + (((2 * wl + ((lane >> 3) & 1)) ^ (lane & 7)) << 4);
#pragma unroll
        for (int kk = 0; kk < 12; kk++) ldmatrix_x4_t(wf[kk], wa + kk * 2048);
      }
      named_bar_sync(3 + wg, 128);
      const int px = (2 * (lane >> 4) + (lane & 1)) * 4 + ((lane & 7) >> 1);
      const uint32_t sto = sbase + wg * kWoBlk + px * 128 + (((2 * wl + ((lane >> 3) & 1)) ^ (px & 7)) << 4);
      int st = 0, sb = 0;
      uint32_t ph = 0;
      uint32_t pk[16];
#pragma unroll
      for (int i = 0; i < 16; i++) pk[i] = 0u;
      auto store = [&](int tq) {
        const int g = tq / 28, tp = tq - 28 * g, tpar = tp / 7, tstrip = tp - 7 * tpar;
#pragma unroll
        for (int jp = 0; jp < 4; jp++)
          stmatrix_x4_t(sto + sb * 8192 + jp * 2048, pk[4 * jp], pk[4 * jp + 1], pk[4 * jp + 2], pk[4 * jp + 3]);
        fence_proxy_async();
        if (wl == 0 && lane == 0) bulk_wait_read1();
        named_bar_sync(3 + wg, 128);
        if (wl == 0 && lane == 0 && tq >= 0) {
          tma_store_5d(&tm_o2, sbase + wg * kWoBlk + sb * 8192, 0, 4 * g, 16 * tstrip, 3 * (tpar & 1) + wg, tpar >> 1);
          bulk_commit();
        }
        __syncwarp();
        sb = sb == 2 ? 0 : sb + 1;
      };
      int t = k, cur = -1;
#pragma unroll 1
      for (; t < kProjTiles; t += kProjCtas) {
        float acc[32];
        mbar_wait(bar + 8 * st, ph);
        if (warp == 0) TRACE(16 + (t / kProjCtas) * 4 + 1);
        const uint32_t blo = (uint32_t)make_desc(sA + st * kOTileBytes, 128, 768, 0);
        if (t > k || wg) named_bar_sync(6 + wg, 256);
        wg_fence();
#pragma unroll
        for (int kk = 0; kk < 12; kk++)
          wgmma_m64n64k16_rs<1>(acc, wf[kk][0], wf[kk][1], wf[kk][2], wf[kk][3],
                                desc64(blo + (((kk / 3) * 6144 + (kk % 3) * 256) >> 4), 768 >> 4), kk != 0);
        wg_commit();
        if (wg < 2 || t + kProjCtas < kProjTiles) named_bar_arrive(6 + (wg == 2 ? 0 : wg + 1), 256);
        const int nxt = (int)lds32(bar + 128 + 4 * st);
        store(cur);
        cur = nxt;
        if (warp == 0) TRACE(12 + (t / kProjCtas) * 4 + 3);
        wg_wait<0>();
        fence_regs(acc);
        if (lane == 0) mbar_arrive(bar + 64 + 8 * st);
        if (warp == 0) TRACE(16 + (t / kProjCtas) * 4 + 2);
#pragma unroll
        for (int i = 0; i < 16; i++) pk[i] = pack_bf16(acc[2 * i], acc[2 * i + 1]);
        if (++st == kStages) { st = 0; ph ^= 1; }
      }
      store(cur);
      if (warp == 0) TRACE(12 + (t / kProjCtas) * 4 + 3);
      if (wl == 0 && lane == 0) bulk_wait<0>();
      if (threadIdx.x == 0) GT(1);
    } else {
      if (lane == 0) {
        mbar_init(bar + 16 * wl, 1);
        mbar_init(bar + 16 * wl + 8, 1);
        mbar_init(bar + 64 + 16 * wl, 12);
        mbar_init(bar + 64 + 16 * wl + 8, 12);
        sts32(bar + 160, 0);
        fence_mbar_init();
      }
      __syncwarp();
      named_bar_sync(0, 512);
      if (wl == 3 && lane == 0) {
        prefetch_map(&tm_o2);
        __nanosleep(2000);
        mbar_expect_tx(bar + 56, 3 * kWoBlk);
#pragma unroll 1
        for (int i = 0; i < 3; i++) tma_load_2d(sbase + i * kWoBlk, &tm_wo2, bar + 56, i * 64, 0);
      }
      __syncwarp();
      if (wl == 3 && k < 4) {
        if (lane == 0) {
          const uint32_t e0 = ld_relaxed(&g_epoch[k * 32 + 3]);
          const uint32_t stg = sA + (kStages - 1) * kOTileBytes;
          mbar_expect_tx(bar + 48, 3 * ka::kWAtom);
#pragma unroll 1
          for (int i = 0; i < 3; i++) tma_load_2d(stg + i * ka::kWAtom, &tm_wo, bar + 48, k * 48 + i * 16, 0);
          mbar_wait(bar + 48, 0);
          bulk_store(g_wop + k * 3 * ka::kWAtom, stg, 3 * ka::kWAtom);
          bulk_commit();
          bulk_wait<0>();
          publish_fence();
          st_relaxed(&g_wflag[k * 32], e0 * 32u + 1);
          st_relaxed(&g_epoch[k * 32 + 3], e0 + 1);
        }
        __syncwarp();
        named_bar_arrive(2, 128);
      }
      if (wl < 3 && k < 4) named_bar_sync(2, 128);
      if (wl < 3 && lane < 4) {
        const uint32_t e0 = ld_relaxed(&g_epoch[k * 32 + wl]);
#pragma unroll 1
        for (int it = wl;; it += 3) {
          const int t = k + it * kProjCtas;
          if (t >= kProjTiles) break;
          const int g = t / 28, tp = t - 28 * g;
          uint32_t sp = 0;
          while (true) {
            const bool ok = (int)(ld_acquire(&g_oflag[tp * 32 + lane]) - (e0 * 32u + g + 1)) >= 0;
            if (__all_sync(15u, ok)) break;
            if (++sp > LIMIT) { BAIL(0x2000000 + t); break; }
          }
          if (lane == 0) {
            const int n = (int)atom_inc_shared(bar + 160), st = n % kStages;
            if (n >= kStages) mbar_wait(bar + 64 + 8 * st, ((n / kStages) & 1) ^ 1);
            TRACE(16 + n * 4 + 0);
            sts32(bar + 128 + 4 * st, t);
            mbar_expect_tx(bar + 8 * st, kOTileBytes);
            bulk_load_hint(sA + st * kOTileBytes, o_tile(g, tp), kOTileBytes, bar + 8 * st, policy_evict_first());
          }
          __syncwarp(15u);
        }
        if (lane == 0) st_relaxed(&g_epoch[k * 32 + wl], e0 + 1);
      }
    }
  }
}

}

namespace {

typedef CUresult (*EncodeTiledFn)(CUtensorMap*, CUtensorMapDataType, cuuint32_t, void*, const cuuint64_t*,
                                  const cuuint64_t*, const cuuint32_t*, const cuuint32_t*, CUtensorMapInterleave,
                                  CUtensorMapSwizzle, CUtensorMapL2promotion, CUtensorMapFloatOOBfill);

EncodeTiledFn get_encode_fn() {
  static EncodeTiledFn fn = nullptr;
  if (!fn) {
    void* p = nullptr;
    cudaDriverEntryPointQueryResult qres;
    if (cudaGetDriverEntryPoint("cuTensorMapEncodeTiled", &p, cudaEnableDefault, &qres) == cudaSuccess)
      fn = reinterpret_cast<EncodeTiledFn>(p);
  }
  return fn;
}

CUtensorMap make_map(void* base, int rank, const cuuint64_t* dims, const cuuint64_t* strides, const cuuint32_t* box,
                     CUtensorMapSwizzle swz) {
  CUtensorMap m;
  cuuint32_t es[5] = {1, 1, 1, 1, 1};
  get_encode_fn()(&m, CU_TENSOR_MAP_DATA_TYPE_BFLOAT16, (cuuint32_t)rank, base, dims, strides, box, es,
                  CU_TENSOR_MAP_INTERLEAVE_NONE, swz, CU_TENSOR_MAP_L2_PROMOTION_L2_128B,
                  CU_TENSOR_MAP_FLOAT_OOB_FILL_NONE);
  return m;
}

}

extern "C" void kernel_launch(void* const* d_in, const int* in_sizes, int n_in, void* d_out, int out_size) {
  using namespace nat;
  (void)in_sizes; (void)n_in; (void)out_size;
  const __nv_bfloat16* x = (const __nv_bfloat16*)d_in[0];
  const __nv_bfloat16* wqkv = (const __nv_bfloat16*)d_in[1];
  const __nv_bfloat16* wo = (const __nv_bfloat16*)d_in[2];
  const __nv_bfloat16* rpb = (const __nv_bfloat16*)d_in[3];
  __nv_bfloat16* out = (__nv_bfloat16*)d_out;

  CUtensorMap tm_x, tm_h, tm_r, tm_w, tm_wo, tm_out, tm_wo2, tm_o2;
  {
    cuuint64_t dims[5] = {64, 112, 112, 6, 2};
    cuuint64_t str[4] = {768, 2ull * 224 * 384, 128, 224ull * 384};
    cuuint32_t box[5] = {64, 16, 4, 3, 1};
    tm_x = make_map((void*)x, 5, dims, str, box, CU_TENSOR_MAP_SWIZZLE_128B);
    cuuint32_t boxh[5] = {64, 3, 5, 1, 1}, boxr[5] = {64, 16, 1, 1, 1};
    tm_h = make_map((void*)x, 5, dims, str, boxh, CU_TENSOR_MAP_SWIZZLE_128B);
    tm_r = make_map((void*)x, 5, dims, str, boxr, CU_TENSOR_MAP_SWIZZLE_128B);
  }
  {
    cuuint64_t dims[2] = {576, 192};
    cuuint64_t str[1] = {1152};
    cuuint32_t box[2] = {16, 192};
    tm_w = make_map((void*)wqkv, 2, dims, str, box, CU_TENSOR_MAP_SWIZZLE_32B);
  }
  {
    cuuint64_t dims[2] = {192, 192};
    cuuint64_t str[1] = {384};
    cuuint32_t box[2] = {16, 192};
    tm_wo = make_map((void*)wo, 2, dims, str, box, CU_TENSOR_MAP_SWIZZLE_32B);
    cuuint32_t box2[2] = {64, 192};
    tm_wo2 = make_map((void*)wo, 2, dims, str, box2, CU_TENSOR_MAP_SWIZZLE_128B);
  }
  {
    cuuint64_t dims[5] = {192, 112, 112, 2, 2};
    cuuint64_t str[4] = {2ull * 224 * 384, 768, 384, 224ull * 384};
    cuuint32_t box[5] = {48, 4, 16, 1, 1};
    tm_out = make_map((void*)out, 5, dims, str, box, CU_TENSOR_MAP_SWIZZLE_NONE);
  }
  {
    cuuint64_t dims[5] = {64, 112, 112, 6, 2};
    cuuint64_t str[4] = {2ull * 224 * 384, 768, 128, 224ull * 384};
    cuuint32_t box[5] = {64, 4, 16, 1, 1};
    tm_o2 = make_map((void*)out, 5, dims, str, box, CU_TENSOR_MAP_SWIZZLE_128B);
  }
  cudaFuncSetAttribute(nat_kernel, cudaFuncAttributeMaxDynamicSharedMemorySize, kSmemBytes);
  nat_kernel<<<kStripCtas + kProjCtas, kThreads, kSmemBytes>>>(wqkv, rpb, tm_x, tm_w, tm_h, tm_r, tm_wo, tm_out, tm_wo2, tm_o2);
}
```

```cpp
#include <cuda_runtime.h>
#include <cuda_bf16.h>
#include <cuda.h>
#include <stdint.h>

#define DEVI __device__ __forceinline__

namespace nat {

DEVI uint32_t smem_u32(const void* p) { return (uint32_t)__cvta_generic_to_shared(p); }

DEVI void mbar_init(uint32_t bar, uint32_t count) {
  asm volatile("mbarrier.init.shared::cta.b64 [%0], %1;" ::"r"(bar), "r"(count) : "memory");
}
DEVI void mbar_expect_tx(uint32_t bar, uint32_t bytes) {
  asm volatile("mbarrier.arrive.expect_tx.shared::cta.b64 _, [%0], %1;" ::"r"(bar), "r"(bytes) : "memory");
}
DEVI void mbar_arrive(uint32_t bar) {
  asm volatile("mbarrier.arrive.shared::cta.b64 _, [%0];" ::"r"(bar) : "memory");
}
DEVI bool mbar_try_wait(uint32_t bar, uint32_t parity) {
  uint32_t ok;
  asm volatile(
      "{\n.reg .pred p;\nmbarrier.try_wait.parity.shared::cta.b64 p, [%1], %2;\nselp.u32 %0, 1, 0, p;\n}\n"
      : "=r"(ok)
      : "r"(bar), "r"(parity)
      : "memory");
  return ok != 0;
}
DEVI bool mbar_test_wait(uint32_t bar, uint32_t parity) {
  uint32_t ok;
  asm volatile(
      "{\n.reg .pred p;\nmbarrier.test_wait.parity.shared::cta.b64 p, [%1], %2;\nselp.u32 %0, 1, 0, p;\n}\n"
      : "=r"(ok)
      : "r"(bar), "r"(parity)
      : "memory");
  return ok != 0;
}
#define BAIL(code) __trap()
#define LIMIT (1u << 20)
DEVI void mbar_wait(uint32_t bar, uint32_t parity) {
  uint32_t it = 0;
  while (!mbar_try_wait(bar, parity)) {
    if (++it > LIMIT) { BAIL(bar & 0xfffff); break; }
  }
}
DEVI void fence_mbar_init() { asm volatile("fence.mbarrier_init.release.cluster;" ::: "memory"); }

DEVI void tma_load_2d(uint32_t dst, const CUtensorMap* tm, uint32_t bar, int c0, int c1) {
  asm volatile(
      "cp.async.bulk.tensor.2d.shared::cluster.global.mbarrier::complete_tx::bytes [%0], [%1, {%3, %4}], [%2];"
      ::"r"(dst), "l"(tm), "r"(bar), "r"(c0), "r"(c1)
      : "memory");
}
DEVI void tma_store_5d(const CUtensorMap* tm, uint32_t src, int c0, int c1, int c2, int c3, int c4) {
  asm volatile("cp.async.bulk.tensor.5d.global.shared::cta.bulk_group [%0, {%2, %3, %4, %5, %6}], [%1];"
               ::"l"(tm), "r"(src), "r"(c0), "r"(c1), "r"(c2), "r"(c3), "r"(c4)
               : "memory");
}
DEVI void bulk_wait_read1() { asm volatile("cp.async.bulk.wait_group.read 1;" ::: "memory"); }
DEVI void bulk_wait_read() { asm volatile("cp.async.bulk.wait_group.read 0;" ::: "memory"); }
DEVI void tma_load_5d(uint32_t dst, const CUtensorMap* tm, uint32_t bar, int c0, int c1, int c2, int c3, int c4) {
  asm volatile(
      "cp.async.bulk.tensor.5d.shared::cluster.global.mbarrier::complete_tx::bytes [%0], [%1, {%3, %4, %5, %6, %7}], [%2];"
      ::"r"(dst), "l"(tm), "r"(bar), "r"(c0), "r"(c1), "r"(c2), "r"(c3), "r"(c4)
      : "memory");
}
DEVI uint64_t policy_evict_first() {
  uint64_t p;
  asm("createpolicy.fractional.L2::evict_first.b64 %0, 1.0;" : "=l"(p));
  return p;
}
DEVI void bulk_load_hint(uint32_t dst, const void* src, uint32_t bytes, uint32_t bar, uint64_t pol) {
  asm volatile("cp.async.bulk.shared::cluster.global.mbarrier::complete_tx::bytes.L2::cache_hint [%0], [%1], %2, [%3], %4;"
               ::"r"(dst), "l"(src), "r"(bytes), "r"(bar), "l"(pol) : "memory");
}
DEVI void prefetch_map(const CUtensorMap* tm) {
  asm volatile("prefetch.tensormap [%0];" ::"l"(tm) : "memory");
}
DEVI void tma_prefetch_5d(const CUtensorMap* tm, int c0, int c1, int c2, int c3, int c4) {
  asm volatile("cp.async.bulk.prefetch.tensor.5d.L2.global [%0, {%1, %2, %3, %4, %5}];"
               ::"l"(tm), "r"(c0), "r"(c1), "r"(c2), "r"(c3), "r"(c4)
               : "memory");
}
DEVI void bulk_load(uint32_t dst, const void* src, uint32_t bytes, uint32_t bar) {
  asm volatile("cp.async.bulk.shared::cluster.global.mbarrier::complete_tx::bytes [%0], [%1], %2, [%3];"
               ::"r"(dst), "l"(src), "r"(bytes), "r"(bar) : "memory");
}
DEVI void bulk_store(void* dst, uint32_t src, uint32_t bytes) {
  asm volatile("cp.async.bulk.global.shared::cta.bulk_group [%0], [%1], %2;" ::"l"(dst), "r"(src), "r"(bytes) : "memory");
}
DEVI void bulk_commit() { asm volatile("cp.async.bulk.commit_group;" ::: "memory"); }
template <int N>
DEVI void bulk_wait() { asm volatile("cp.async.bulk.wait_group %0;" ::"n"(N) : "memory"); }

template <int N>
DEVI void reg_dec() { asm volatile("setmaxnreg.dec.sync.aligned.u32 %0;" ::"n"(N)); }
template <int N>
DEVI void reg_inc() { asm volatile("setmaxnreg.inc.sync.aligned.u32 %0;" ::"n"(N)); }

DEVI void wg_fence() { asm volatile("wgmma.fence.sync.aligned;" ::: "memory"); }
DEVI void wg_commit() { asm volatile("wgmma.commit_group.sync.aligned;" ::: "memory"); }
template <int N>
DEVI void wg_wait() { asm volatile("wgmma.wait_group.sync.aligned %0;" ::"n"(N) : "memory"); }
template <int N>
DEVI void fence_regs(float (&d)[N]) {
#pragma unroll
  for (int i = 0; i < N; i++) asm volatile("" : "+f"(d[i])::"memory");
}

DEVI uint64_t make_desc(uint32_t addr, uint32_t lbo, uint32_t sbo, uint32_t swz) {
  return (uint64_t)((addr & 0x3FFFFu) >> 4) | ((uint64_t)((lbo & 0x3FFFFu) >> 4) << 16) |
         ((uint64_t)((sbo & 0x3FFFFu) >> 4) << 32) | ((uint64_t)swz << 62);
}

DEVI uint64_t desc64(uint32_t lo, uint32_t hi) {
  uint64_t d;
  asm("mov.b64 %0, {%1, %2};" : "=l"(d) : "r"(lo), "r"(hi));
  return d;
}
DEVI uint32_t pack_bf16(float lo, float hi) {
  uint32_t r;
  asm("cvt.rn.bf16x2.f32 %0, %1, %2;" : "=r"(r) : "f"(hi), "f"(lo));
  return r;
}
DEVI float ex2(float x) {
  float r;
  asm("ex2.approx.ftz.f32 %0, %1;" : "=f"(r) : "f"(x));
  return r;
}
DEVI float rcp_approx(float x) {
  float r;
  asm("rcp.approx.ftz.f32 %0, %1;" : "=f"(r) : "f"(x));
  return r;
}
DEVI uint32_t movmatrix_t(uint32_t a) {
  uint32_t r;
  asm("movmatrix.sync.aligned.m8n8.trans.b16 %0, %1;" : "=r"(r) : "r"(a));
  return r;
}
DEVI void ldmatrix_x4(uint32_t (&r)[4], uint32_t addr) {
  asm volatile("ldmatrix.sync.aligned.m8n8.x4.shared.b16 {%0, %1, %2, %3}, [%4];"
               : "=r"(r[0]), "=r"(r[1]), "=r"(r[2]), "=r"(r[3]) : "r"(addr) : "memory");
}
DEVI void ldmatrix_x4(uint32_t& r0, uint32_t& r1, uint32_t& r2, uint32_t& r3, uint32_t addr) {
  asm volatile("ldmatrix.sync.aligned.m8n8.x4.shared.b16 {%0, %1, %2, %3}, [%4];"
               : "=r"(r0), "=r"(r1), "=r"(r2), "=r"(r3) : "r"(addr) : "memory");
}
DEVI void ldmatrix_x2(uint32_t& r0, uint32_t& r1, uint32_t addr) {
  asm volatile("ldmatrix.sync.aligned.m8n8.x2.shared.b16 {%0, %1}, [%2];"
               : "=r"(r0), "=r"(r1) : "r"(addr) : "memory");
}
DEVI void ldmatrix_x4_t(uint32_t (&r)[4], uint32_t addr) {
  asm volatile("ldmatrix.sync.aligned.m8n8.x4.trans.shared.b16 {%0, %1, %2, %3}, [%4];"
               : "=r"(r[0]), "=r"(r[1]), "=r"(r[2]), "=r"(r[3]) : "r"(addr) : "memory");
}
DEVI void stmatrix_x4(uint32_t addr, uint32_t r0, uint32_t r1, uint32_t r2, uint32_t r3) {
  asm volatile("stmatrix.sync.aligned.m8n8.x4.shared.b16 [%0], {%1, %2, %3, %4};"
               ::"r"(addr), "r"(r0), "r"(r1), "r"(r2), "r"(r3) : "memory");
}
DEVI void stmatrix_x4_t(uint32_t addr, uint32_t r0, uint32_t r1, uint32_t r2, uint32_t r3) {
  asm volatile("stmatrix.sync.aligned.m8n8.x4.trans.shared.b16 [%0], {%1, %2, %3, %4};"
               ::"r"(addr), "r"(r0), "r"(r1), "r"(r2), "r"(r3) : "memory");
}
DEVI void mma16816(float (&d)[4], const uint32_t (&a)[4], uint32_t b0, uint32_t b1) {
  asm volatile("mma.sync.aligned.m16n8k16.row.col.f32.bf16.bf16.f32 {%0, %1, %2, %3}, {%4, %5, %6, %7}, {%8, %9}, {%0, %1, %2, %3};"
               : "+f"(d[0]), "+f"(d[1]), "+f"(d[2]), "+f"(d[3])
               : "r"(a[0]), "r"(a[1]), "r"(a[2]), "r"(a[3]), "r"(b0), "r"(b1));
}
DEVI void mma16816_z(float (&d)[4], const uint32_t (&a)[4], uint32_t b0, uint32_t b1) {
  asm volatile("mma.sync.aligned.m16n8k16.row.col.f32.bf16.bf16.f32 {%0, %1, %2, %3}, {%4, %5, %6, %7}, {%8, %9}, {%10, %10, %10, %10};"
               : "=f"(d[0]), "=f"(d[1]), "=f"(d[2]), "=f"(d[3])
               : "r"(a[0]), "r"(a[1]), "r"(a[2]), "r"(a[3]), "r"(b0), "r"(b1), "f"(0.f));
}
DEVI void mma16816_c(float (&d)[4], const uint32_t (&a)[4], uint32_t b0, uint32_t b1, const float (&c)[4]) {
  asm volatile("mma.sync.aligned.m16n8k16.row.col.f32.bf16.bf16.f32 {%0, %1, %2, %3}, {%4, %5, %6, %7}, {%8, %9}, {%10, %11, %12, %13};"
               : "=f"(d[0]), "=f"(d[1]), "=f"(d[2]), "=f"(d[3])
               : "r"(a[0]), "r"(a[1]), "r"(a[2]), "r"(a[3]), "r"(b0), "r"(b1), "f"(c[0]), "f"(c[1]), "f"(c[2]), "f"(c[3]));
}
template <int BIT>
DEVI void sel2(uint32_t mask, float& r0, float& r1, float a0, float a1, float b0, float b1) {
  asm("{\n.reg .pred p;\n.reg .b32 t;\nand.b32 t, %2, %7;\nsetp.ne.b32 p, t, 0;\nselp.f32 %0, %3, %5, p;\nselp.f32 %1, %4, %6, p;\n}"
      : "=f"(r0), "=f"(r1) : "r"(mask), "f"(a0), "f"(a1), "f"(b0), "f"(b1), "n"(BIT));
}
template <int BIT>
DEVI void split2(uint32_t mask, uint32_t& r0, uint32_t& r1, uint32_t v) {
  asm("{\n.reg .pred p;\n.reg .b32 t;\nand.b32 t, %2, %4;\nsetp.ne.b32 p, t, 0;\nselp.b32 %0, %3, 0, p;\nselp.b32 %1, 0, %3, p;\n}"
      : "=r"(r0), "=r"(r1) : "r"(mask), "r"(v), "n"(BIT));
}
DEVI void stg32_if(uint32_t* p, uint32_t v, bool on) {
  asm volatile("{\n.reg .pred q;\nsetp.ne.u32 q, %2, 0;\n@q st.global.u32 [%0], %1;\n}" ::"l"(p), "r"(v), "r"((uint32_t)on) : "memory");
}
DEVI uint4 ldg128(const void* p) {
  uint4 v;
  asm volatile("ld.global.nc.v4.u32 {%0, %1, %2, %3}, [%4];" : "=r"(v.x), "=r"(v.y), "=r"(v.z), "=r"(v.w) : "l"(p));
  return v;
}
DEVI uint32_t ld_acquire(const uint32_t* p) {
  uint32_t v;
  asm volatile("ld.acquire.gpu.global.u32 %0, [%1];" : "=r"(v) : "l"(p) : "memory");
  return v;
}
DEVI uint32_t ld_relaxed(const uint32_t* p) {
  uint32_t v;
  asm volatile("ld.relaxed.gpu.global.u32 %0, [%1];" : "=r"(v) : "l"(p) : "memory");
  return v;
}
DEVI void st_relaxed(uint32_t* p, uint32_t v) {
  asm volatile("st.relaxed.gpu.global.u32 [%0], %1;" ::"l"(p), "r"(v) : "memory");
}
DEVI void red_max_release(uint32_t* p, uint32_t v) {
  asm volatile("red.release.gpu.global.max.u32 [%0], %1;" ::"l"(p), "r"(v) : "memory");
}
DEVI void fence_gpu() { asm volatile("fence.acq_rel.gpu;" ::: "memory"); }
DEVI uint32_t lds32(uint32_t addr) {
  uint32_t v;
  asm volatile("ld.shared.u32 %0, [%1];" : "=r"(v) : "r"(addr) : "memory");
  return v;
}
DEVI uint32_t atom_inc_shared(uint32_t addr) {
  uint32_t v;
  asm volatile("atom.shared.add.u32 %0, [%1], 1;" : "=r"(v) : "r"(addr) : "memory");
  return v;
}
DEVI void sts32(uint32_t addr, uint32_t v) {
  asm volatile("st.shared.u32 [%0], %1;" ::"r"(addr), "r"(v) : "memory");
}
DEVI void sts128(uint32_t addr, uint4 v) {
  asm volatile("st.shared.v4.u32 [%0], {%1, %2, %3, %4};" ::"r"(addr), "r"(v.x), "r"(v.y), "r"(v.z), "r"(v.w) : "memory");
}
DEVI void named_bar_arrive(int id, int n) { asm volatile("bar.arrive %0, %1;" ::"r"(id), "r"(n) : "memory"); }
DEVI void named_bar_sync(int id, int n) { asm volatile("bar.sync %0, %1;" ::"r"(id), "r"(n) : "memory"); }
DEVI void fence_proxy_async() { asm volatile("fence.proxy.async.shared::cta;" ::: "memory"); }
DEVI void fence_proxy_async_global() { asm volatile("fence.proxy.async.global;" ::: "memory"); }
DEVI int clampi(int v, int lo, int hi) { return v < lo ? lo : (v > hi ? hi : v); }

template <int TA, int TB> DEVI void wgmma_m64n144k16_ss(float (&d)[72], uint64_t descA, uint64_t descB, int scaleD) {
  asm volatile("{\n.reg .pred p;\nsetp.ne.b32 p, %74, 0;\nwgmma.mma_async.sync.aligned.m64n144k16.f32.bf16.bf16 {%0, %1, %2, %3, %4, %5, %6, %7, %8, %9, %10, %11, %12, %13, %14, %15, %16, %17, %18, %19, %20, %21, %22, %23, %24, %25, %26, %27, %28, %29, %30, %31, %32, %33, %34, %35, %36, %37, %38, %39, %40, %41, %42, %43, %44, %45, %46, %47, %48, %49, %50, %51, %52, %53, %54, %55, %56, %57, %58, %59, %60, %61, %62, %63, %64, %65, %66, %67, %68, %69, %70, %71}, %72, %73, p, 1, 1, %75, %76;\n}\n"
    : "+f"(d[0]), "+f"(d[1]), "+f"(d[2]), "+f"(d[3]), "+f"(d[4]), "+f"(d[5]), "+f"(d[6]), "+f"(d[7]), "+f"(d[8]), "+f"(d[9]), "+f"(d[10]), "+f"(d[11]), "+f"(d[12]), "+f"(d[13]), "+f"(d[14]), "+f"(d[15]), "+f"(d[16]), "+f"(d[17]), "+f"(d[18]), "+f"(d[19]), "+f"(d[20]), "+f"(d[21]), "+f"(d[22]), "+f"(d[23]), "+f"(d[24]), "+f"(d[25]), "+f"(d[26]), "+f"(d[27]), "+f"(d[28]), "+f"(d[29]), "+f"(d[30]), "+f"(d[31]), "+f"(d[32]), "+f"(d[33]), "+f"(d[34]), "+f"(d[35]), "+f"(d[36]), "+f"(d[37]), "+f"(d[38]), "+f"(d[39]), "+f"(d[40]), "+f"(d[41]), "+f"(d[42]), "+f"(d[43]), "+f"(d[44]), "+f"(d[45]), "+f"(d[46]), "+f"(d[47]), "+f"(d[48]), "+f"(d[49]), "+f"(d[50]), "+f"(d[51]), "+f"(d[52]), "+f"(d[53]), "+f"(d[54]), "+f"(d[55]), "+f"(d[56]), "+f"(d[57]), "+f"(d[58]), "+f"(d[59]), "+f"(d[60]), "+f"(d[61]), "+f"(d[62]), "+f"(d[63]), "+f"(d[64]), "+f"(d[65]), "+f"(d[66]), "+f"(d[67]), "+f"(d[68]), "+f"(d[69]), "+f"(d[70]), "+f"(d[71])
    : "l"(descA), "l"(descB), "r"(scaleD), "n"(TA), "n"(TB));
}

template <int TB> DEVI void wgmma_m64n64k16_rs(float (&d)[32], uint32_t a0, uint32_t a1, uint32_t a2, uint32_t a3, uint64_t descB, int scaleD) {
  asm volatile("{\n.reg .pred p;\nsetp.ne.b32 p, %37, 0;\nwgmma.mma_async.sync.aligned.m64n64k16.f32.bf16.bf16 {%0, %1, %2, %3, %4, %5, %6, %7, %8, %9, %10, %11, %12, %13, %14, %15, %16, %17, %18, %19, %20, %21, %22, %23, %24, %25, %26, %27, %28, %29, %30, %31}, {%32, %33, %34, %35}, %36, p, 1, 1, %38;\n}\n"
    : "+f"(d[0]), "+f"(d[1]), "+f"(d[2]), "+f"(d[3]), "+f"(d[4]), "+f"(d[5]), "+f"(d[6]), "+f"(d[7]), "+f"(d[8]), "+f"(d[9]), "+f"(d[10]), "+f"(d[11]), "+f"(d[12]), "+f"(d[13]), "+f"(d[14]), "+f"(d[15]), "+f"(d[16]), "+f"(d[17]), "+f"(d[18]), "+f"(d[19]), "+f"(d[20]), "+f"(d[21]), "+f"(d[22]), "+f"(d[23]), "+f"(d[24]), "+f"(d[25]), "+f"(d[26]), "+f"(d[27]), "+f"(d[28]), "+f"(d[29]), "+f"(d[30]), "+f"(d[31])
    : "r"(a0), "r"(a1), "r"(a2), "r"(a3), "l"(descB), "r"(scaleD), "n"(TB));
}

template <int TA, int TB> DEVI void wgmma_m64n96k16_ss(float (&d)[48], uint64_t descA, uint64_t descB, int scaleD) {
  asm volatile("{\n.reg .pred p;\nsetp.ne.b32 p, %50, 0;\nwgmma.mma_async.sync.aligned.m64n96k16.f32.bf16.bf16 {%0, %1, %2, %3, %4, %5, %6, %7, %8, %9, %10, %11, %12, %13, %14, %15, %16, %17, %18, %19, %20, %21, %22, %23, %24, %25, %26, %27, %28, %29, %30, %31, %32, %33, %34, %35, %36, %37, %38, %39, %40, %41, %42, %43, %44, %45, %46, %47}, %48, %49, p, 1, 1, %51, %52;\n}\n"
    : "+f"(d[0]), "+f"(d[1]), "+f"(d[2]), "+f"(d[3]), "+f"(d[4]), "+f"(d[5]), "+f"(d[6]), "+f"(d[7]), "+f"(d[8]), "+f"(d[9]), "+f"(d[10]), "+f"(d[11]), "+f"(d[12]), "+f"(d[13]), "+f"(d[14]), "+f"(d[15]), "+f"(d[16]), "+f"(d[17]), "+f"(d[18]), "+f"(d[19]), "+f"(d[20]), "+f"(d[21]), "+f"(d[22]), "+f"(d[23]), "+f"(d[24]), "+f"(d[25]), "+f"(d[26]), "+f"(d[27]), "+f"(d[28]), "+f"(d[29]), "+f"(d[30]), "+f"(d[31]), "+f"(d[32]), "+f"(d[33]), "+f"(d[34]), "+f"(d[35]), "+f"(d[36]), "+f"(d[37]), "+f"(d[38]), "+f"(d[39]), "+f"(d[40]), "+f"(d[41]), "+f"(d[42]), "+f"(d[43]), "+f"(d[44]), "+f"(d[45]), "+f"(d[46]), "+f"(d[47])
    : "l"(descA), "l"(descB), "r"(scaleD), "n"(TA), "n"(TB));
}

constexpr int kS = 112;
constexpr int kStripCtas = 112;
constexpr int kProjCtas = 20;
constexpr int kThreads = 512;
constexpr int kArr = 29;
constexpr int kExch = 27;
constexpr int kSteps = 28;
constexpr int kTiles = kSteps * 28;
constexpr int kOTileBytes = 64 * 192 * 2;
constexpr int kTailBands = 7;
constexpr int kTail0 = kSteps - kTailBands;
constexpr int kProjTiles = kTail0 * 28;
constexpr int kHaloBytes = 3 * 784 - 16, kHaloPitch = 2432;

__device__ __align__(1024) uint8_t g_o[(size_t)kTiles * kOTileBytes];
constexpr int kHaloRing = 10;
constexpr int kHaloBlock = (2 * kHaloRing + 1) * kHaloPitch;
__device__ __align__(1024) uint8_t g_halo[(size_t)kStripCtas * kHaloBlock];
__device__ __align__(1024) uint8_t g_wop[4 * 3 * 192 * 32];
__device__ uint32_t g_oflag[28 * 32];
__device__ uint32_t g_wflag[4 * 32];
__device__ uint32_t g_epoch[kProjCtas * 32];

DEVI uint32_t* halo_flags(int cta) {
  return reinterpret_cast<uint32_t*>(g_halo + (size_t)cta * kHaloBlock + 2 * kHaloRing * kHaloPitch);
}
DEVI const uint8_t* o_tile(int g, int ps) { return g_o + (size_t)(ps * kSteps + g) * kOTileBytes; }

DEVI int cta_role() {
  const int b = blockIdx.x, s = b >> 1, pat = s / 7, o = s - 7 * pat;
  return (o == 6 || s == 65) ? kStripCtas + 2 * pat + (b & 1) : 12 * pat + 2 * o + (b & 1);
}

namespace ka {
constexpr int kWAtom = 192 * 32;
constexpr int kWBytes = 9 * kWAtom;
constexpr int kXBytes = 64 * 384;
constexpr int kCol = 784;
constexpr int kQCol = 400;
constexpr int kSlot = 22 * kCol;
constexpr int kQSlot = 16 * kQCol;
constexpr int kQOff = 5 * kSlot + 32;
constexpr int kOffX = kWBytes;
constexpr int kOffRing = kOffX + 2 * kXBytes;
constexpr int kOffBar = kOffRing + kQOff + 6 * kQSlot;
constexpr int kOffStage = kOffX, kOffWo = kOffX + 2 * kWAtom;
constexpr int kOffDummy = kOffBar + 896;
DEVI uint32_t tail_buf(int i) { return i < 2 ? i * kOTileBytes : kOffRing + (i - 2) * 2 * kSlot; }
constexpr int kLastBytes = 3 * (16 + 2 * 15) * 128;
constexpr int kBarX = 0, kBarFull = 256, kBarO = 512, kBarT = 768, kBarOwn = 832, kBarJunk = 896;
constexpr int kSmemBytes = kOffBar + 896 + 704;
constexpr int kD = 6;
static_assert(kTailBands <= 8, "buffers");
constexpr int kShift = kArr - kD + 1;
constexpr int kNbInit = 0, kNbMisc = 1, kNbBurst = 2, kNbTile = 7, kNbFirst = 13, kNbX = 14;
}

namespace kb {
constexpr int kWoBlk = 192 * 128;
constexpr int kStages = 6;
constexpr int kOffA = 3 * kWoBlk;
constexpr int kOffBar = kOffA + kStages * kOTileBytes;
constexpr int kSmemBytes = kOffBar + 192;
}

constexpr int kSmemBytes = ka::kSmemBytes > kb::kSmemBytes ? ka::kSmemBytes : kb::kSmemBytes;
static_assert(kSmemBytes <= 232448, "smem");

#define TRACE(idx)
#define GT(i)
#define ATRACE(k)
#define TRBASE (sbase + kTraceOff)

DEVI void mbar_wait_sleep(uint32_t bar, uint32_t parity) {
  uint32_t it = 0;
  while (!mbar_test_wait(bar, parity)) {
    __nanosleep(200);
    if (++it > LIMIT) { BAIL(bar & 0xfffff); break; }
  }
}

DEVI void publish_fence() {
  fence_proxy_async_global();
  fence_gpu();
}

DEVI uint32_t sched_fence() {
  uint32_t t;
  asm volatile("mov.u32 %0, %clock;" : "=r"(t)::"memory");
  return t;
}

struct AttnState {
  uint32_t kf[5][3][4];
  uint32_t vf[5][3][4];
  float bias[5][4];
  uint32_t p[5][2];
  uint32_t kaddr, vaddr, qaddr, bar, junk, fence;
  uint32_t ones[4];
  bool rdy;
  uint32_t pm;
  uint32_t* optr;
};

DEVI void store_o(AttnState& s, float (&o)[3][4], float i0, float i1, bool on) {
#pragma unroll
  for (int mt = 0; mt < 3; mt++) {
    stg32_if(s.optr + (2 * mt) * 32, pack_bf16(o[mt][0] * i0, o[mt][1] * i1), on);
    stg32_if(s.optr + (2 * mt + 1) * 32, pack_bf16(o[mt][2] * i0, o[mt][3] * i1), on);
  }
  s.optr += kOTileBytes / 4;
}

template <int PH>
DEVI void attn_step(AttnState& s, int g, int warp, const __nv_bfloat16* __restrict__ rpb) {
  using namespace ka;
  constexpr int R = (2 * PH) % 5, N0 = (R + 3) % 5, N1 = (R + 4) % 5;
  constexpr int SL = ((PH + 1) % 5) * kSlot;
  if (PH == 0 && g == 0) {
    {
      const int lane = threadIdx.x & 31, me = cta_role(), qc0 = 16 * ((me >> 2) % 7) + 2 * warp;
      const int kc = clampi(qc0 - 3, 0, kS - 8) + (lane >> 2);
      const unsigned short* r = reinterpret_cast<const unsigned short*>(rpb) + (me & 3) * 169 + (3 - (lane & 3)) * 13 + kc - qc0 + 6;
      const int sw0 = clampi(qc0 - 3, 0, kS - 7), sw1 = clampi(qc0 - 2, 0, kS - 7);
      const bool ok0 = kc >= sw0 && kc < sw0 + 7, ok1 = kc >= sw1 && kc < sw1 + 7;
#pragma unroll
      for (int i = 0; i < 10; i++) {
        const uint32_t v0 = ok0 ? (uint32_t)__ldg(r + i * 13) : 0xFF80u;
        const uint32_t v1 = ok1 ? (uint32_t)__ldg(r + i * 13 - 1) : 0xFF80u;
        s.bias[i >> 1][2 * (i & 1)] = __uint_as_float(v0 << 16) * 6.928203230275509f;
        s.bias[i >> 1][2 * (i & 1) + 1] = __uint_as_float(v1 << 16) * 6.928203230275509f;
      }
    }
    named_bar_sync(kNbMisc, 384);
    mbar_wait(s.bar + kBarFull, 0);
#pragma unroll
    for (int k = 0; k < 3; k++) {
      ldmatrix_x4(s.kf[1][k], s.kaddr + k * 32);
      ldmatrix_x4(s.kf[2][k], s.kaddr + 384 + k * 32);
      ldmatrix_x4_t(s.vf[1][k], s.vaddr + k * 32);
      ldmatrix_x4_t(s.vf[2][k], s.vaddr + 384 + k * 32);
      s.vf[0][k][0] = s.vf[0][k][1] = s.vf[0][k][2] = s.vf[0][k][3] = 0u;
    }
    named_bar_arrive(kNbFirst, 384);
    s.rdy = false;
    s.pm = (s.pm << 8) | (s.pm & 64);
  }
  if (!s.rdy) {
    mbar_wait(s.bar + kBarFull + 8 * (g + 1), 0);
    if (PH == 1 && g == 1) s.pm >>= 8;
    if (PH == 2 && g == kSteps - 1) s.pm |= 0x3Fu;
    if (PH == kShift % 5 && g == kShift && warp >= 4) {
      const uint32_t t0 = sched_fence();
      while (sched_fence() - t0 < 200) {}
    }
  }
  ATRACE(0);
  float t[5][4], o[3][4], z[4];
  uint32_t q[6];
  ldmatrix_x4(q[0], q[1], q[2], q[3], s.qaddr);
  ldmatrix_x2(q[4], q[5], s.qaddr + 64);
#define LDK(ks) { ldmatrix_x4(s.kf[N0][ks], s.kaddr + SL + (ks) * 32); ldmatrix_x4(s.kf[N1][ks], s.kaddr + SL + 384 + (ks) * 32); }
#define LDV(n) ldmatrix_x4_t(s.vf[(n) < 3 ? N0 : N1][(n) % 3], s.vaddr + SL + ((n) / 3) * 384 + ((n) % 3) * 32);
#define PV(i) { _Pragma("unroll") for (int mt = 0; mt < 3; mt++) { \
                  if ((i) == 0) mma16816_z(o[mt], s.vf[N0][mt], s.p[0][0], s.p[0][1]); \
                  else mma16816(o[mt], s.vf[(R + 3 + (i)) % 5][mt], s.p[i][0], s.p[i][1]); } \
                if ((i) == 0) mma16816_z(z, s.ones, s.p[0][0] | s.p[4][0], s.p[0][1] | s.p[4][1]); \
                else if ((i) < 4) mma16816(z, s.ones, s.p[i][0], s.p[i][1]); }
#define QK(ks) { _Pragma("unroll") for (int i = 0; i < 5; i++) { \
                   if ((ks) == 0) mma16816_c(t[i], s.kf[(R + i) % 5][0], q[0], q[1], s.bias[i]); \
                   else mma16816(t[i], s.kf[(R + i) % 5][ks], q[2 * (ks)], q[2 * (ks) + 1]); } }
#define FN(x) x = sched_fence();
  uint32_t f0 = 0, f1;
  if (PH == 1) {
    LDK(0) LDK(1) LDK(2) PV(0) PV(1) PV(2) PV(3) PV(4) FN(f1)
    LDV(5) LDV(4) LDV(3) LDV(2) LDV(1) LDV(0) QK(0) QK(1) FN(f0) QK(2)
  } else if (PH == 2) {
    LDK(0) LDK(1) LDK(2) PV(0) PV(1) PV(2) FN(f1)
    LDV(5) LDV(4) LDV(3) PV(3) PV(4) FN(f0) LDV(2) LDV(1) LDV(0) QK(0) QK(1) QK(2)
  } else {
    LDK(0) LDK(1) LDK(2) PV(0) PV(1) PV(2) PV(3) PV(4) FN(f1)
    LDV(5) LDV(4) LDV(3) LDV(2) LDV(1) LDV(0) QK(0) QK(1) QK(2)
  }
#undef LDK
#undef LDV
#undef PV
#undef QK
#undef FN
  const uint32_t f2 = sched_fence();
  named_bar_arrive(kNbBurst + (PH + kD) % 5, 384);
  const uint32_t fo = s.fence;
  s.fence = sched_fence();
  ATRACE(1);
  const uint32_t pm = s.pm;
  float x[7][2];
  sel2<1>(pm, x[0][0], x[0][1], t[0][0], t[0][1], t[3][2], t[3][3]);
  sel2<2>(pm, x[1][0], x[1][1], t[0][2], t[0][3], t[4][0], t[4][1]);
  sel2<4>(pm, x[2][0], x[2][1], t[1][0], t[1][1], t[4][2], t[4][3]);
#pragma unroll
  for (int e = 0; e < 2; e++) {
    x[3][e] = t[1][2 + e]; x[4][e] = t[2][e]; x[5][e] = t[2][2 + e]; x[6][e] = t[3][e];
  }
  float m0 = fmaxf(fmaxf(fmaxf(x[0][0], x[1][0]), fmaxf(x[2][0], x[3][0])), fmaxf(fmaxf(x[4][0], x[5][0]), x[6][0]));
  float m1 = fmaxf(fmaxf(fmaxf(x[0][1], x[1][1]), fmaxf(x[2][1], x[3][1])), fmaxf(fmaxf(x[4][1], x[5][1]), x[6][1]));
#pragma unroll
  for (int d = 4; d <= 16; d <<= 1) {
    m0 = fmaxf(m0, __shfl_xor_sync(0xffffffffu, m0, d));
    m1 = fmaxf(m1, __shfl_xor_sync(0xffffffffu, m1, d));
  }
  {
    int nx = kBarFull + 8 * (g + 2);
    if (PH >= 3 && g < 0) nx = kBarOwn + 8 * warp;
    if ((PH == (kShift - 1) % 5 && g == kShift - 1) || (PH == 0 && g == 0) || (PH == 1 && g == kSteps - 2)) nx = kBarFull + 8 * 31;
    s.rdy = mbar_test_wait(s.bar + nx, 0);
  }
  const float c = 0.14433756729740643f * 1.4426950408889634f;
  const float n0 = -m0 * c, n1 = -m1 * c;
  uint32_t pt[7];
#pragma unroll
  for (int i = 0; i < 7; i++) {
    const float e0 = ex2(fmaf(x[i][0], c, n0)), e1 = ex2(fmaf(x[i][1], c, n1));
    pt[i] = movmatrix_t(pack_bf16(e0, e1));
  }
  split2<8>(pm, s.p[0][0], s.p[3][1], pt[0]);
  split2<16>(pm, s.p[0][1], s.p[4][0], pt[1]);
  split2<32>(pm, s.p[1][0], s.p[4][1], pt[2]);
  s.p[1][1] = pt[3]; s.p[2][0] = pt[4]; s.p[2][1] = pt[5]; s.p[3][0] = pt[6];
#pragma unroll
  for (int i = 0; i < 5; i++) asm volatile("" : "+r"(s.p[i][0]), "+r"(s.p[i][1])::"memory");
  const bool real = PH == 1 || PH == 2 || g > 0;
  store_o(s, o, rcp_approx(z[0]), rcp_approx(z[1]), real);
  __syncwarp();
  if ((s.pm & 64) && real) mbar_arrive(s.bar + kBarO + 8 * (g - 1));
  s.junk ^= fo ^ f0 ^ f1 ^ f2;
  s.qaddr += kQSlot;
  if (s.qaddr >= s.bar) s.qaddr -= 6 * kQSlot;
  asm volatile("" : "+r"(s.junk)::"memory");
  ATRACE(2);
}

__global__ void __launch_bounds__(kThreads, 1)
nat_kernel(const __nv_bfloat16* __restrict__ wqkv, const __nv_bfloat16* __restrict__ rpb,
           const __grid_constant__ CUtensorMap tm_x, const __grid_constant__ CUtensorMap tm_w,
           const __grid_constant__ CUtensorMap tm_h, const __grid_constant__ CUtensorMap tm_r,
           const __grid_constant__ CUtensorMap tm_wo, const __grid_constant__ CUtensorMap tm_out,
           const __grid_constant__ CUtensorMap tm_wo2, const __grid_constant__ CUtensorMap tm_o2) {
  extern __shared__ __align__(1024) uint8_t smem_raw[];
  const uint32_t sbase = smem_u32(smem_raw);
  if (sbase & 1023u) __trap();
  const int warp = __shfl_sync(0xffffffffu, (int)(threadIdx.x >> 5), 0), lane = threadIdx.x & 31;
  const int wg = warp >> 2, wl = warp & 3;
  const int cta = cta_role();
  const bool strip_cta = cta < kStripCtas;
  const int head = cta & 3, ps = cta >> 2, par = ps / 7, strip = ps - 7 * par;
  if (threadIdx.x == 0) TRACE(0);

  if (threadIdx.x == 416) prefetch_map(strip_cta ? &tm_w : &tm_wo2);
  if (strip_cta && threadIdx.x == 384) {
    using namespace ka;
    const uint32_t bar = sbase + kOffBar;
    mbar_init(bar + kBarX, 1);
    mbar_expect_tx(bar + kBarX, kXBytes + 6 * kWAtom);
    tma_load_5d(sbase + kOffX, &tm_x, bar + kBarX, 0, 16 * strip, -1, 3 * (par & 1), par >> 1);
#pragma unroll
    for (int i = 3; i < 9; i++)
      tma_load_2d(sbase + i * kWAtom, &tm_w, bar + kBarX, (i / 3) * 192 + head * 48 + (i % 3) * 16, 0);
    TRACE(10);
  }
  __syncwarp();
  if (strip_cta && wg == 2 && threadIdx.x < 256 + 96) {
    using namespace ka;
    uint4 v[12];
    const int wk = ((int)threadIdx.x - 256) / 6, wu = (int)threadIdx.x - 256 - 6 * wk;
    const uint8_t* src = reinterpret_cast<const uint8_t*>(wqkv) + wk * 1152 + head * 96 + wu * 16;
#pragma unroll
    for (int i = 0; i < 12; i++) v[i] = ldg128(src + i * 16 * 1152);
    const uint32_t dst = sbase + (wu >> 1) * kWAtom + wk * 32 + (((wu ^ (wk >> 2)) & 1) << 4);
#pragma unroll
    for (int i = 0; i < 12; i++) sts128(dst + i * 16 * 32, v[i]);
    if (warp == 8) TRACE(6);
    fence_proxy_async();
  }
  if (threadIdx.x == 480) GT(0);

  if (strip_cta) {
    using namespace ka;
    const uint32_t bar = sbase + kOffBar, ring = sbase + kOffRing;
    const int tskip = (head ^ (head >> 1)) & 1, thalf = head >> 1;
    if (wg < 2) {
      reg_inc<184>();
      AttnState s;
      const int qc0 = 16 * strip + 2 * warp;
      const int kc0 = clampi(qc0 - 3, 0, kS - 8);
      const uint32_t colb = ring + (kc0 - (16 * strip - 3) + (lane & 7)) * kCol;
      s.kaddr = colb + ((lane >> 3) & 1) * 192 + (lane >> 4) * 16;
      s.vaddr = colb + 96 + (lane >> 4) * 192 + ((lane >> 3) & 1) * 16;
      {
        const int qr = (lane & 7) >> 1;
        const uint32_t qa = ring + kQOff + (2 * warp + (lane & 1)) * kQCol + (lane >> 3) * 16;
        s.qaddr = qa + (qr == 3 ? 5 * kQSlot : 4 * kQSlot + (qr + 1) * 96);
      }
      s.bar = bar;
      s.optr = reinterpret_cast<uint32_t*>(g_o + (size_t)ps * kSteps * kOTileBytes + head * 6144 + warp * 768) + lane - 3 * kOTileBytes / 4;
#pragma unroll
      for (int i = 0; i < 5; i++) {
        s.p[i][0] = s.p[i][1] = 0u;
        s.bias[i][0] = s.bias[i][1] = s.bias[i][2] = s.bias[i][3] = 0.f;
#pragma unroll
        for (int k = 0; k < 3; k++)
#pragma unroll
          for (int c = 0; c < 4; c++) s.kf[i][k][c] = s.vf[i][k][c] = 0u;
      }
      s.junk = s.fence = 0;
      s.rdy = true;
      if (lane == 0) {
        mbar_init(bar + kBarOwn + 8 * warp, 1);
        mbar_arrive(bar + kBarOwn + 8 * warp);
      }
      __syncwarp();
#pragma unroll
      for (int i = 0; i < 4; i++) s.ones[i] = 0x3F803F80u;
      s.pm = (7u << (lane & 3) & 7u) | ((7u << (lane >> 3) & 7u) << 3) | (lane == 0 ? 64u : 0u);
      s.pm = __shfl_sync(0xffffffffu, s.pm, lane);
      s.kaddr = __shfl_sync(0xffffffffu, s.kaddr, lane);
      s.vaddr = __shfl_sync(0xffffffffu, s.vaddr, lane);
#pragma unroll 1
      for (int g = -2; g < kSteps; g += 5) {
        attn_step<3>(s, g, warp, rpb);
        attn_step<4>(s, g + 1, warp, rpb);
        attn_step<0>(s, g + 2, warp, rpb);
        attn_step<1>(s, g + 3, warp, rpb);
        attn_step<2>(s, g + 4, warp, rpb);
      }
      {
        float o[3][4], z[4];
#pragma unroll
        for (int mt = 0; mt < 3; mt++) mma16816_z(o[mt], s.vf[4][mt], s.p[0][0], s.p[0][1]);
        mma16816_z(z, s.ones, s.p[0][0], s.p[0][1]);
#pragma unroll
        for (int i = 1; i < 5; i++) {
#pragma unroll
          for (int mt = 0; mt < 3; mt++) mma16816(o[mt], s.vf[i - 1][mt], s.p[i][0], s.p[i][1]);
          mma16816(z, s.ones, s.p[i][0], s.p[i][1]);
        }
        store_o(s, o, rcp_approx(z[0]), rcp_approx(z[1]), true);
        __syncwarp();
        if (lane == 0) mbar_arrive(bar + kBarO + 8 * (kSteps - 1));
      }
      s.junk ^= s.fence;
      if (s.junk == 0x9e3779b9u) sts32(bar + kBarJunk, 0);
      if (warp == 0) TRACE(1);
      if (threadIdx.x == 128) GT(3);
    } else if (wg == 2) {
      reg_dec<104>();
      const int col = ((lane >> 3) & 1) * 8 + (lane & 7);
      uint32_t kva = ring + (3 + col) * kCol + wl * 192 + (lane >> 4) * 16;
      uint32_t qa = ring + kQOff + col * kQCol + wl * 96 + (lane >> 4) * 16;
      const uint32_t alo = (uint32_t)make_desc(sbase + kOffX, 16, 1024, 1), blo = (uint32_t)make_desc(sbase, kWAtom, 256, 3);
      constexpr uint32_t ahi = (1u << 30) | (1024 >> 4), bhi = (3u << 30) | (256 >> 4);
      if (wl == 0) TRACE(2);
      uint32_t gj = 0, qprev = 0, qk[12];
#pragma unroll
      for (int j = 0; j < 12; j++) qk[j] = 0;
      int bid = kNbBurst, tid = kNbTile;
      named_bar_arrive(kNbBurst + (kD - 2) % 5, 384);
      named_bar_arrive(kNbBurst + (kD - 1) % 5, 384);
      named_bar_sync(kNbX, 160);
      if (wl == 0) TRACE(7);
      mbar_wait(bar + kBarX, 0);
      if (wl == 0) TRACE(16 + 0);
#pragma unroll 1
      for (int a = 0; a < kArr; a++) {
        float acc[72];
        const uint32_t al = alo + (a & 1) * (kXBytes >> 4);
        if (a >= kD) named_bar_sync(bid, 384);
        if (wl == 0) TRACE(16 + a * 4 + 1);
        wg_fence();
#pragma unroll
        for (int k = 0; k < 12; k++)
          wgmma_m64n144k16_ss<0, 1>(acc, desc64(al + (((k >> 2) * 8192 + (k & 3) * 32) >> 4), ahi), desc64(blo + k * 32, bhi), k != 0);
        wg_commit();
        const uint32_t gjv = sched_fence();
        gj ^= gjv;
        if (a > 0) {
#pragma unroll
          for (int j = 0; j < 3; j++) stmatrix_x4(qprev + j * 32, qk[4 * j], qk[4 * j + 1], qk[4 * j + 2], qk[4 * j + 3]);
          __syncwarp();
          if (lane == 0 && a - 1 < kExch) mbar_arrive(bar + kBarFull + 8 * (a - 1));
        }
        bid = bid == kNbBurst + 4 ? kNbBurst : bid + 1;
        if (a == 0) named_bar_sync(kNbInit, 256);
        const bool xok = mbar_test_wait(bar + kBarX + 8 * (a + 1), 0);
        if (a == kArr - 1 && wl != 0) {
          const int r = col / 3, c = col - 3 * r;
          qa = sbase + kOffDummy + lane * 16;
          kva = col < 15 && wl < 3 ? ring + ((kExch + (r >> 2)) % 5) * kSlot + ((wl - 1) * 19 + c) * kCol + (r & 3) * 192 + (lane >> 4) * 16
                                   : qa;
        }
        wg_wait<0>();
        fence_regs(acc);
        named_bar_arrive(kNbX + (a & 1), 160);
        if (a == 5) named_bar_sync(kNbFirst, 384);
        if (wl == 0) TRACE(16 + a * 4 + 2);
#pragma unroll
        for (int j = 3; j < 9; j++)
          stmatrix_x4(kva + (j - 3) * 32, pack_bf16(acc[8 * j + 0], acc[8 * j + 1]), pack_bf16(acc[8 * j + 2], acc[8 * j + 3]),
                      pack_bf16(acc[8 * j + 4], acc[8 * j + 5]), pack_bf16(acc[8 * j + 6], acc[8 * j + 7]));
#pragma unroll
        for (int j = 0; j < 12; j++) qk[j] = pack_bf16(acc[2 * j], acc[2 * j + 1]);
        qprev = qa;
        if (a < kExch) named_bar_arrive(tid, 160);
        tid = tid == kNbTile + 5 ? kNbTile : tid + 1;
        if (wl == 0) TRACE(16 + a * 4 + 3);
        if (!xok && a + 1 < kArr) mbar_wait(bar + kBarX + 8 * (a + 1), 0);
        if (wl == 0) TRACE(16 + (a + 1) * 4 + 0);
        kva += kSlot;
        if (kva >= ring + 5 * kSlot) kva -= 5 * kSlot;
        qa += kQSlot;
        if (qa >= bar) qa -= 6 * kQSlot;
      }
#pragma unroll
      for (int j = 0; j < 3; j++) stmatrix_x4(qprev + j * 32, qk[4 * j], qk[4 * j + 1], qk[4 * j + 2], qk[4 * j + 3]);
      __syncwarp();
      if (lane < kArr - kExch) mbar_arrive(bar + kBarFull + 8 * (kExch + lane));
      if (gj == 0x9e3779b9u) sts32(bar + kBarJunk, 0);
#pragma unroll 1
      for (int g = kArr - kD; g < kSteps - 1; g++) {
        named_bar_arrive(bid, 384);
        bid = bid == kNbBurst + 4 ? kNbBurst : bid + 1;
      }
      {
        const uint32_t wlo = (uint32_t)make_desc(sbase + kOffWo, kWAtom, 256, 3);
        const int n = lane & 7, j = 2 * wl + ((lane >> 3) & 1);
        const uint32_t sta = sbase + kOffStage + ((2 * j + (n & 1)) * 4 + (n >> 1)) * 96 + (lane >> 4) * 16;
        mbar_wait(bar + kBarX + 8 * kArr, 0);
        named_bar_sync(bid, 384);
        if (tskip) mbar_wait(bar + kBarO + 8 * (kSteps - 1), 0);
#pragma unroll 1
        for (int g = kTail0 + tskip, i = 0; g < kSteps; g += 2, i++) {
          float acc[48];
          mbar_wait(bar + kBarT + 8 * i, 0);
          if (wl == 0) TRACE(144 + i * 2);
          const uint32_t tlo = (uint32_t)make_desc(sbase + tail_buf(i), 128, 768, 0);
          wg_fence();
#pragma unroll
          for (int k = 0; k < 12; k++)
            wgmma_m64n96k16_ss<1, 1>(acc, desc64(tlo + (((k / 3) * 6144 + (k % 3) * 256) >> 4), 768 >> 4), desc64(wlo + k * 32, bhi), k != 0);
          wg_commit();
          if (threadIdx.x == 256) bulk_wait_read();
          named_bar_sync(kNbMisc, 128);
          wg_wait<0>();
          fence_regs(acc);
#pragma unroll
          for (int jp = 0; jp < 6; jp++)
            stmatrix_x4(sta + (jp / 3) * kWAtom + (jp % 3) * 32, pack_bf16(acc[8 * jp + 0], acc[8 * jp + 1]),
                        pack_bf16(acc[8 * jp + 2], acc[8 * jp + 3]), pack_bf16(acc[8 * jp + 4], acc[8 * jp + 5]),
                        pack_bf16(acc[8 * jp + 6], acc[8 * jp + 7]));
          fence_proxy_async();
          named_bar_sync(kNbMisc, 128);
          if (threadIdx.x == 256) {
            tma_store_5d(&tm_out, sbase + kOffStage, thalf * 96, 4 * g, 16 * strip, par & 1, par >> 1);
            tma_store_5d(&tm_out, sbase + kOffStage + kWAtom, thalf * 96 + 48, 4 * g, 16 * strip, par & 1, par >> 1);
            bulk_commit();
          }
          __syncwarp();
          if (wl == 0) TRACE(145 + i * 2);
        }
        if (threadIdx.x == 256) {
          bulk_wait<0>();
          GT(2);
        }
      }
    } else {
      reg_dec<40>();
      if (wl == 0) named_bar_arrive(kNbX, 160);
      if (lane == 0) {
        const uint32_t b0 = bar + 64 * wl;
        if (wl == 1 && head == 1) tma_prefetch_5d(&tm_x, 0, 16 * strip, 3, 3 * (par & 1), par >> 1);
#pragma unroll
        for (int i = 0; i < 64; i += 8) {
          if (i || wl) mbar_init(b0 + kBarX + i, 1);
          mbar_init(b0 + kBarFull + i, wl < 3 || i < 8 * (kExch - 24) ? 6 : 4);
          mbar_init(b0 + kBarO + i, 8);
          if (wl == 0 && i < 32) mbar_init(b0 + kBarT + i, 1);
        }
#pragma unroll
        for (int i = 0; i < 64; i += 8) {
          if (i || wl)
            mbar_expect_tx(b0 + kBarX + i, wl < 3 || i < 32 ? kXBytes : (i == 32 ? kLastBytes : 6 * kWAtom));
          if (wl == 0 && i < 32) mbar_expect_tx(bar + kBarT + i, kOTileBytes);
        }
        fence_mbar_init();
        if (wl == 0) {
          tma_load_5d(sbase + kOffX + kXBytes, &tm_x, bar + kBarX + 8, 0, 16 * strip, 3, 3 * (par & 1), par >> 1);
          tma_prefetch_5d(&tm_x, 0, 16 * strip, 4 * (2 + ((head - 2) & 3)) - 1, 3 * (par & 1), par >> 1);
          TRACE(5);
        }
      }
      __syncwarp();
      const uint32_t ep = ld_relaxed(halo_flags(cta) + 32 + wl) * 32u;
      named_bar_arrive(kNbMisc, 384);
      named_bar_sync(kNbInit, 256);
      if (wl == 0) {
#pragma unroll 1
        for (int a = 2; a < kArr - 1; a++) {
          named_bar_sync(kNbX + (a & 1), 160);
          if (lane == 0) {
            tma_load_5d(sbase + kOffX + (a & 1) * kXBytes, &tm_x, bar + kBarX + 8 * a, 0, 16 * strip, 4 * a - 1,
                        3 * (par & 1), par >> 1);
            if (a == 20) {
              prefetch_map(&tm_h);
              prefetch_map(&tm_r);
              prefetch_map(&tm_out);
            }
            const int ap = a + 4;
            if (ap < kArr && (ap & 3) == head) tma_prefetch_5d(&tm_x, 0, 16 * strip, 4 * ap - 1, 3 * (par & 1), par >> 1);
          }
          __syncwarp();
        }
        named_bar_sync(kNbX, 160);
        if (lane < 9) {
          const int kb = lane / 3, w = lane - 3 * kb;
          tma_load_5d(sbase + kOffX + kb * 8192 + w * 2048, w == 0 ? &tm_r : &tm_h, bar + kBarX + 8 * (kArr - 1), 0,
                      16 * strip + (w == 0 ? 0 : (w == 1 ? -3 : 16)), w == 0 ? kS - 1 : 4 * kExch - 1, 3 * (par & 1) + kb, par >> 1);
        }
        {
          uint32_t it = 0;
          while (!__all_sync(0xffffffffu, (int)(ld_acquire(&g_wflag[(lane & 3) * 32]) - (ep + 1)) >= 0))
            if (++it > LIMIT) { BAIL(0x5000000); break; }
        }
        const uint8_t* wsrc = g_wop + thalf * 6 * kWAtom;
        named_bar_sync(kNbX + 1, 160);
        if (lane == 0) bulk_load(sbase + kOffWo + 2 * kWAtom, wsrc + 2 * kWAtom, 4 * kWAtom, bar + kBarX + 8 * kArr);
        uint32_t seen = ld_acquire(&g_oflag[ps * 32 + (lane & 3)]);
        named_bar_sync(kNbX, 160);
        if (lane == 0) bulk_load(sbase + kOffWo, wsrc, 2 * kWAtom, bar + kBarX + 8 * kArr);
#pragma unroll 1
        for (int g = kTail0 + tskip, i = 0; g < kSteps; g += 2, i++) {
          uint32_t it = 0;
          while (!__all_sync(0xffffffffu, (int)(seen - (ep + g + 1)) >= 0)) {
            seen = ld_acquire(&g_oflag[ps * 32 + (lane & 3)]);
            if (++it > LIMIT) { BAIL(0x3000000 + g); break; }
          }
          if (lane == 0)
            bulk_load(sbase + tail_buf(i), o_tile(g, ps), kOTileBytes, bar + kBarT + 8 * i);
          __syncwarp();
        }
      } else {
        const int p = wl - 1;
        const bool on = lane == 0 ? strip > 0 : strip < 6;
        const int nb = on ? cta + (lane == 0 ? -4 : 4) : cta;
        const uint32_t bytes = (strip > 0 && strip < 6) ? 2 * kHaloBytes : kHaloBytes;
        int slot = p, g = 0;
#pragma unroll 1
        for (int a = p; a < kExch; a += 3) {
          named_bar_sync(kNbTile + a % 6, 160);
          const uint32_t sl = ring + slot * kSlot;
          if (lane < 2) {
            fence_proxy_async();
            if (on) bulk_store(g_halo + (size_t)cta * kHaloBlock + (lane * kHaloRing + a % kHaloRing) * kHaloPitch, sl + (3 + 13 * lane) * kCol, kHaloBytes);
            bulk_commit();
          }
          __syncwarp();
          g += __ffs(~__ballot_sync(0xffffffffu, lane < 4 && mbar_test_wait(bar + kBarO + 8 * (g + lane), 0))) - 1;
          __syncwarp();
          if (lane < 2) {
            bulk_wait<0>();
            if (lane == 0) mbar_expect_tx(bar + kBarFull + 8 * a, bytes);
            else mbar_arrive(bar + kBarFull + 8 * a);
            TRACE(160 + a * 4 + 0);
            fence_proxy_async_global();
          }
          __syncwarp();
          if (lane < 3) red_max_release(lane < 2 ? halo_flags(cta) + 4 * lane + p : &g_oflag[ps * 32 + head], lane < 2 ? ep + a + 1 : ep + g);
          __syncwarp();
          TRACE(160 + a * 4 + 1);
          {
            const uint32_t* fl = halo_flags(nb) + 4 * ((lane & 1) ^ 1) + p;
            uint32_t it = 0;
            while (!__all_sync(0xffffffffu, !(lane < 2 && on) || (int)(ld_acquire(fl) - (ep + a + 1)) >= 0))
              if (++it > LIMIT) { BAIL(0x1000000 + a); break; }
          }
          TRACE(160 + a * 4 + 2);
          if (lane < 2 && on)
            bulk_load(sl + lane * 19 * kCol, g_halo + (size_t)nb * kHaloBlock + ((lane ^ 1) * kHaloRing + a % kHaloRing) * kHaloPitch,
                      kHaloBytes, bar + kBarFull + 8 * a);
          TRACE(160 + a * 4 + 3);
          __syncwarp();
          slot = slot >= 2 ? slot - 2 : slot + 3;
        }
        if (lane == 0) {
#pragma unroll 1
          for (g = kSteps - 7 + p; g < kSteps; g += 3) {
            if (g < kSteps - 3) mbar_wait_sleep(bar + kBarO + 8 * g, 0);
            else mbar_wait(bar + kBarO + 8 * g, 0);
            TRACE(370 + g * 2);
            fence_proxy_async_global();
            red_max_release(&g_oflag[ps * 32 + head], ep + g + 1);
            TRACE(371 + g * 2);
          }
          if (p == 0) GT(1);
        }
      }
      __syncwarp();
      if (lane == 0) st_relaxed(halo_flags(cta) + 32 + wl, (ep >> 5) + 1);
    }
  } else {
    using namespace kb;
    const uint32_t bar = sbase + kOffBar, sA = sbase + kOffA;
    const int k = cta - kStripCtas;
    if (wg < 3) {
      named_bar_sync(0, 512);
      uint32_t wf[12][4];
      mbar_wait(bar + 56, 0);
      {
        const int kr = (lane & 7) + ((lane >> 4) << 3);
        const uint32_t wa = sbase + wg * kWoBlk + kr * 128 + (((2 * wl + ((lane >> 3) & 1)) ^ (lane & 7)) << 4);
#pragma unroll
        for (int kk = 0; kk < 12; kk++) ldmatrix_x4_t(wf[kk], wa + kk * 2048);
      }
      named_bar_sync(3 + wg, 128);
      const int px = (2 * (lane >> 4) + (lane & 1)) * 4 + ((lane & 7) >> 1);
      const uint32_t sto = sbase + wg * kWoBlk + px * 128 + (((2 * wl + ((lane >> 3) & 1)) ^ (px & 7)) << 4);
      int st = 0, sb = 0;
      uint32_t ph = 0;
      uint32_t pk[16];
#pragma unroll
      for (int i = 0; i < 16; i++) pk[i] = 0u;
      auto store = [&](int tq) {
        const int g = tq / 28, tp = tq - 28 * g, tpar = tp / 7, tstrip = tp - 7 * tpar;
#pragma unroll
        for (int jp = 0; jp < 4; jp++)
          stmatrix_x4_t(sto + sb * 8192 + jp * 2048, pk[4 * jp], pk[4 * jp + 1], pk[4 * jp + 2], pk[4 * jp + 3]);
        fence_proxy_async();
        if (wl == 0 && lane == 0) bulk_wait_read1();
        named_bar_sync(3 + wg, 128);
        if (wl == 0 && lane == 0 && tq >= 0) {
          tma_store_5d(&tm_o2, sbase + wg * kWoBlk + sb * 8192, 0, 4 * g, 16 * tstrip, 3 * (tpar & 1) + wg, tpar >> 1);
          bulk_commit();
        }
        __syncwarp();
        sb = sb == 2 ? 0 : sb + 1;
      };
      int t = k, cur = -1;
#pragma unroll 1
      for (; t < kProjTiles; t += kProjCtas) {
        float acc[32];
        const bool rdy = mbar_test_wait(bar + 8 * st, ph);
        if (warp == 0) TRACE(16 + (t / kProjCtas) * 4 + 1);
        const uint32_t blo = (uint32_t)make_desc(sA + st * kOTileBytes, 128, 768, 0);
        if (t > k || wg) named_bar_sync(6 + wg, 256);
        if (!rdy) mbar_wait(bar + 8 * st, ph);
        wg_fence();
#pragma unroll
        for (int kk = 0; kk < 12; kk++)
          wgmma_m64n64k16_rs<1>(acc, wf[kk][0], wf[kk][1], wf[kk][2], wf[kk][3],
                                desc64(blo + (((kk / 3) * 6144 + (kk % 3) * 256) >> 4), 768 >> 4), kk != 0);
        wg_commit();
        if (wg < 2 || t + kProjCtas < kProjTiles) named_bar_arrive(6 + (wg == 2 ? 0 : wg + 1), 256);
        const int nxt = (int)lds32(bar + 128 + 4 * st);
        store(cur);
        cur = nxt;
        if (warp == 0) TRACE(12 + (t / kProjCtas) * 4 + 3);
        wg_wait<0>();
        fence_regs(acc);
        if (lane == 0) mbar_arrive(bar + 64 + 8 * st);
        if (warp == 0) TRACE(16 + (t / kProjCtas) * 4 + 2);
#pragma unroll
        for (int i = 0; i < 16; i++) pk[i] = pack_bf16(acc[2 * i], acc[2 * i + 1]);
        if (++st == kStages) { st = 0; ph ^= 1; }
      }
      store(cur);
      if (warp == 0) TRACE(12 + (t / kProjCtas) * 4 + 3);
      if (wl == 0 && lane == 0) bulk_wait<0>();
      if (threadIdx.x == 0) GT(1);
    } else {
      if (lane == 0) {
        mbar_init(bar + 16 * wl, 1);
        mbar_init(bar + 16 * wl + 8, 1);
        mbar_init(bar + 64 + 16 * wl, 12);
        mbar_init(bar + 64 + 16 * wl + 8, 12);
        sts32(bar + 160, 0);
        fence_mbar_init();
      }
      __syncwarp();
      named_bar_sync(0, 512);
      if (wl == 3 && lane == 0) {
        prefetch_map(&tm_o2);
        __nanosleep(2000);
        mbar_expect_tx(bar + 56, 3 * kWoBlk);
#pragma unroll 1
        for (int i = 0; i < 3; i++) tma_load_2d(sbase + i * kWoBlk, &tm_wo2, bar + 56, i * 64, 0);
      }
      __syncwarp();
      if (wl == 3 && k < 4) {
        if (lane == 0) {
          const uint32_t e0 = ld_relaxed(&g_epoch[k * 32 + 3]);
          const uint32_t stg = sA + (kStages - 1) * kOTileBytes;
          mbar_expect_tx(bar + 48, 3 * ka::kWAtom);
#pragma unroll 1
          for (int i = 0; i < 3; i++) tma_load_2d(stg + i * ka::kWAtom, &tm_wo, bar + 48, k * 48 + i * 16, 0);
          mbar_wait(bar + 48, 0);
          bulk_store(g_wop + k * 3 * ka::kWAtom, stg, 3 * ka::kWAtom);
          bulk_commit();
          bulk_wait<0>();
          publish_fence();
          st_relaxed(&g_wflag[k * 32], e0 * 32u + 1);
          st_relaxed(&g_epoch[k * 32 + 3], e0 + 1);
        }
        __syncwarp();
        named_bar_arrive(2, 128);
      }
      if (wl < 3 && k < 4) named_bar_sync(2, 128);
      if (wl < 3 && lane < 4) {
        const uint32_t e0 = ld_relaxed(&g_epoch[k * 32 + wl]);
#pragma unroll 1
        for (int it = wl;; it += 3) {
          const int t = k + it * kProjCtas;
          if (t >= kProjTiles) break;
          const int g = t / 28, tp = t - 28 * g;
          uint32_t sp = 0;
          while (true) {
            const bool ok = (int)(ld_acquire(&g_oflag[tp * 32 + lane]) - (e0 * 32u + g + 1)) >= 0;
            if (__all_sync(15u, ok)) break;
            if (++sp > LIMIT) { BAIL(0x2000000 + t); break; }
          }
          if (lane == 0) {
            const int n = (int)atom_inc_shared(bar + 160), st = n % kStages;
            if (n >= kStages) mbar_wait_sleep(bar + 64 + 8 * st, ((n / kStages) & 1) ^ 1);
            TRACE(16 + n * 4 + 0);
            sts32(bar + 128 + 4 * st, t);
            mbar_expect_tx(bar + 8 * st, kOTileBytes);
            bulk_load_hint(sA + st * kOTileBytes, o_tile(g, tp), kOTileBytes, bar + 8 * st, policy_evict_first());
          }
          __syncwarp(15u);
        }
        if (lane == 0) st_relaxed(&g_epoch[k * 32 + wl], e0 + 1);
      }
    }
  }
}

}

namespace {

typedef CUresult (*EncodeTiledFn)(CUtensorMap*, CUtensorMapDataType, cuuint32_t, void*, const cuuint64_t*,
                                  const cuuint64_t*, const cuuint32_t*, const cuuint32_t*, CUtensorMapInterleave,
                                  CUtensorMapSwizzle, CUtensorMapL2promotion, CUtensorMapFloatOOBfill);

EncodeTiledFn get_encode_fn() {
  static EncodeTiledFn fn = nullptr;
  if (!fn) {
    void* p = nullptr;
    cudaDriverEntryPointQueryResult qres;
    if (cudaGetDriverEntryPoint("cuTensorMapEncodeTiled", &p, cudaEnableDefault, &qres) == cudaSuccess)
      fn = reinterpret_cast<EncodeTiledFn>(p);
  }
  return fn;
}

CUtensorMap make_map(void* base, int rank, const cuuint64_t* dims, const cuuint64_t* strides, const cuuint32_t* box,
                     CUtensorMapSwizzle swz) {
  CUtensorMap m;
  cuuint32_t es[5] = {1, 1, 1, 1, 1};
  get_encode_fn()(&m, CU_TENSOR_MAP_DATA_TYPE_BFLOAT16, (cuuint32_t)rank, base, dims, strides, box, es,
                  CU_TENSOR_MAP_INTERLEAVE_NONE, swz, CU_TENSOR_MAP_L2_PROMOTION_L2_128B,
                  CU_TENSOR_MAP_FLOAT_OOB_FILL_NONE);
  return m;
}

}

extern "C" void kernel_launch(void* const* d_in, const int* in_sizes, int n_in, void* d_out, int out_size) {
  using namespace nat;
  (void)in_sizes; (void)n_in; (void)out_size;
  const __nv_bfloat16* x = (const __nv_bfloat16*)d_in[0];
  const __nv_bfloat16* wqkv = (const __nv_bfloat16*)d_in[1];
  const __nv_bfloat16* wo = (const __nv_bfloat16*)d_in[2];
  const __nv_bfloat16* rpb = (const __nv_bfloat16*)d_in[3];
  __nv_bfloat16* out = (__nv_bfloat16*)d_out;

  CUtensorMap tm_x, tm_h, tm_r, tm_w, tm_wo, tm_out, tm_wo2, tm_o2;
  {
    cuuint64_t dims[5] = {64, 112, 112, 6, 2};
    cuuint64_t str[4] = {768, 2ull * 224 * 384, 128, 224ull * 384};
    cuuint32_t box[5] = {64, 16, 4, 3, 1};
    tm_x = make_map((void*)x, 5, dims, str, box, CU_TENSOR_MAP_SWIZZLE_128B);
    cuuint32_t boxh[5] = {64, 3, 5, 1, 1}, boxr[5] = {64, 16, 1, 1, 1};
    tm_h = make_map((void*)x, 5, dims, str, boxh, CU_TENSOR_MAP_SWIZZLE_128B);
    tm_r = make_map((void*)x, 5, dims, str, boxr, CU_TENSOR_MAP_SWIZZLE_128B);
  }
  {
    cuuint64_t dims[2] = {576, 192};
    cuuint64_t str[1] = {1152};
    cuuint32_t box[2] = {16, 192};
    tm_w = make_map((void*)wqkv, 2, dims, str, box, CU_TENSOR_MAP_SWIZZLE_32B);
  }
  {
    cuuint64_t dims[2] = {192, 192};
    cuuint64_t str[1] = {384};
    cuuint32_t box[2] = {16, 192};
    tm_wo = make_map((void*)wo, 2, dims, str, box, CU_TENSOR_MAP_SWIZZLE_32B);
    cuuint32_t box2[2] = {64, 192};
    tm_wo2 = make_map((void*)wo, 2, dims, str, box2, CU_TENSOR_MAP_SWIZZLE_128B);
  }
  {
    cuuint64_t dims[5] = {192, 112, 112, 2, 2};
    cuuint64_t str[4] = {2ull * 224 * 384, 768, 384, 224ull * 384};
    cuuint32_t box[5] = {48, 4, 16, 1, 1};
    tm_out = make_map((void*)out, 5, dims, str, box, CU_TENSOR_MAP_SWIZZLE_NONE);
  }
  {
    cuuint64_t dims[5] = {64, 112, 112, 6, 2};
    cuuint64_t str[4] = {2ull * 224 * 384, 768, 128, 224ull * 384};
    cuuint32_t box[5] = {64, 4, 16, 1, 1};
    tm_o2 = make_map((void*)out, 5, dims, str, box, CU_TENSOR_MAP_SWIZZLE_128B);
  }
  cudaFuncSetAttribute(nat_kernel, cudaFuncAttributeMaxDynamicSharedMemorySize, kSmemBytes);
  nat_kernel<<<kStripCtas + kProjCtas, kThreads, kSmemBytes>>>(wqkv, rpb, tm_x, tm_w, tm_h, tm_r, tm_wo, tm_out, tm_wo2, tm_o2);
}
```

```cpp
#include <cuda_runtime.h>
#include <cuda_bf16.h>
#include <cuda.h>
#include <stdint.h>

#define DEVI __device__ __forceinline__

namespace nat {

DEVI uint32_t smem_u32(const void* p) { return (uint32_t)__cvta_generic_to_shared(p); }

DEVI void mbar_init(uint32_t bar, uint32_t count) {
  asm volatile("mbarrier.init.shared::cta.b64 [%0], %1;" ::"r"(bar), "r"(count) : "memory");
}
DEVI void mbar_expect_tx(uint32_t bar, uint32_t bytes) {
  asm volatile("mbarrier.arrive.expect_tx.shared::cta.b64 _, [%0], %1;" ::"r"(bar), "r"(bytes) : "memory");
}
DEVI void mbar_arrive(uint32_t bar) {
  asm volatile("mbarrier.arrive.shared::cta.b64 _, [%0];" ::"r"(bar) : "memory");
}
DEVI bool mbar_try_wait(uint32_t bar, uint32_t parity) {
  uint32_t ok;
  asm volatile(
      "{\n.reg .pred p;\nmbarrier.try_wait.parity.shared::cta.b64 p, [%1], %2;\nselp.u32 %0, 1, 0, p;\n}\n"
      : "=r"(ok)
      : "r"(bar), "r"(parity)
      : "memory");
  return ok != 0;
}
DEVI bool mbar_test_wait(uint32_t bar, uint32_t parity) {
  uint32_t ok;
  asm volatile(
      "{\n.reg .pred p;\nmbarrier.test_wait.parity.shared::cta.b64 p, [%1], %2;\nselp.u32 %0, 1, 0, p;\n}\n"
      : "=r"(ok)
      : "r"(bar), "r"(parity)
      : "memory");
  return ok != 0;
}
#define LIMIT (1u << 20)
DEVI void mbar_wait(uint32_t bar, uint32_t parity) {
  uint32_t it = 0;
  while (!mbar_try_wait(bar, parity)) {
    if (++it > LIMIT) { __trap(); break; }
  }
}
DEVI void fence_mbar_init() { asm volatile("fence.mbarrier_init.release.cluster;" ::: "memory"); }

DEVI void tma_load_2d(uint32_t dst, const CUtensorMap* tm, uint32_t bar, int c0, int c1) {
  asm volatile(
      "cp.async.bulk.tensor.2d.shared::cluster.global.mbarrier::complete_tx::bytes [%0], [%1, {%3, %4}], [%2];"
      ::"r"(dst), "l"(tm), "r"(bar), "r"(c0), "r"(c1)
      : "memory");
}
DEVI void tma_store_5d(const CUtensorMap* tm, uint32_t src, int c0, int c1, int c2, int c3, int c4) {
  asm volatile("cp.async.bulk.tensor.5d.global.shared::cta.bulk_group [%0, {%2, %3, %4, %5, %6}], [%1];"
               ::"l"(tm), "r"(src), "r"(c0), "r"(c1), "r"(c2), "r"(c3), "r"(c4)
               : "memory");
}
DEVI void bulk_wait_read1() { asm volatile("cp.async.bulk.wait_group.read 1;" ::: "memory"); }
DEVI void bulk_wait_read() { asm volatile("cp.async.bulk.wait_group.read 0;" ::: "memory"); }
DEVI void tma_load_5d(uint32_t dst, const CUtensorMap* tm, uint32_t bar, int c0, int c1, int c2, int c3, int c4) {
  asm volatile(
      "cp.async.bulk.tensor.5d.shared::cluster.global.mbarrier::complete_tx::bytes [%0], [%1, {%3, %4, %5, %6, %7}], [%2];"
      ::"r"(dst), "l"(tm), "r"(bar), "r"(c0), "r"(c1), "r"(c2), "r"(c3), "r"(c4)
      : "memory");
}
DEVI uint64_t policy_evict_first() {
  uint64_t p;
  asm("createpolicy.fractional.L2::evict_first.b64 %0, 1.0;" : "=l"(p));
  return p;
}
DEVI void bulk_load_hint(uint32_t dst, const void* src, uint32_t bytes, uint32_t bar, uint64_t pol) {
  asm volatile("cp.async.bulk.shared::cluster.global.mbarrier::complete_tx::bytes.L2::cache_hint [%0], [%1], %2, [%3], %4;"
               ::"r"(dst), "l"(src), "r"(bytes), "r"(bar), "l"(pol) : "memory");
}
DEVI void prefetch_map(const CUtensorMap* tm) {
  asm volatile("prefetch.tensormap [%0];" ::"l"(tm) : "memory");
}
DEVI void tma_prefetch_5d(const CUtensorMap* tm, int c0, int c1, int c2, int c3, int c4) {
  asm volatile("cp.async.bulk.prefetch.tensor.5d.L2.global [%0, {%1, %2, %3, %4, %5}];"
               ::"l"(tm), "r"(c0), "r"(c1), "r"(c2), "r"(c3), "r"(c4)
               : "memory");
}
DEVI void bulk_load(uint32_t dst, const void* src, uint32_t bytes, uint32_t bar) {
  asm volatile("cp.async.bulk.shared::cluster.global.mbarrier::complete_tx::bytes [%0], [%1], %2, [%3];"
               ::"r"(dst), "l"(src), "r"(bytes), "r"(bar) : "memory");
}
DEVI void bulk_store(void* dst, uint32_t src, uint32_t bytes) {
  asm volatile("cp.async.bulk.global.shared::cta.bulk_group [%0], [%1], %2;" ::"l"(dst), "r"(src), "r"(bytes) : "memory");
}
DEVI void bulk_commit() { asm volatile("cp.async.bulk.commit_group;" ::: "memory"); }
template <int N>
DEVI void bulk_wait() { asm volatile("cp.async.bulk.wait_group %0;" ::"n"(N) : "memory"); }

template <int N>
DEVI void reg_dec() { asm volatile("setmaxnreg.dec.sync.aligned.u32 %0;" ::"n"(N)); }
template <int N>
DEVI void reg_inc() { asm volatile("setmaxnreg.inc.sync.aligned.u32 %0;" ::"n"(N)); }

DEVI void wg_fence() { asm volatile("wgmma.fence.sync.aligned;" ::: "memory"); }
DEVI void wg_commit() { asm volatile("wgmma.commit_group.sync.aligned;" ::: "memory"); }
template <int N>
DEVI void wg_wait() { asm volatile("wgmma.wait_group.sync.aligned %0;" ::"n"(N) : "memory"); }
template <int N>
DEVI void fence_regs(float (&d)[N]) {
#pragma unroll
  for (int i = 0; i < N; i++) asm volatile("" : "+f"(d[i])::"memory");
}

DEVI uint64_t make_desc(uint32_t addr, uint32_t lbo, uint32_t sbo, uint32_t swz) {
  return (uint64_t)((addr & 0x3FFFFu) >> 4) | ((uint64_t)((lbo & 0x3FFFFu) >> 4) << 16) |
         ((uint64_t)((sbo & 0x3FFFFu) >> 4) << 32) | ((uint64_t)swz << 62);
}

DEVI uint64_t desc64(uint32_t lo, uint32_t hi) {
  uint64_t d;
  asm("mov.b64 %0, {%1, %2};" : "=l"(d) : "r"(lo), "r"(hi));
  return d;
}
DEVI uint32_t pack_bf16(float lo, float hi) {
  uint32_t r;
  asm("cvt.rn.bf16x2.f32 %0, %1, %2;" : "=r"(r) : "f"(hi), "f"(lo));
  return r;
}
DEVI float ex2(float x) {
  float r;
  asm("ex2.approx.ftz.f32 %0, %1;" : "=f"(r) : "f"(x));
  return r;
}
DEVI float rcp_approx(float x) {
  float r;
  asm("rcp.approx.ftz.f32 %0, %1;" : "=f"(r) : "f"(x));
  return r;
}
DEVI uint32_t movmatrix_t(uint32_t a) {
  uint32_t r;
  asm("movmatrix.sync.aligned.m8n8.trans.b16 %0, %1;" : "=r"(r) : "r"(a));
  return r;
}
DEVI void ldmatrix_x4(uint32_t (&r)[4], uint32_t addr) {
  asm volatile("ldmatrix.sync.aligned.m8n8.x4.shared.b16 {%0, %1, %2, %3}, [%4];"
               : "=r"(r[0]), "=r"(r[1]), "=r"(r[2]), "=r"(r[3]) : "r"(addr) : "memory");
}
DEVI void ldmatrix_x4(uint32_t& r0, uint32_t& r1, uint32_t& r2, uint32_t& r3, uint32_t addr) {
  asm volatile("ldmatrix.sync.aligned.m8n8.x4.shared.b16 {%0, %1, %2, %3}, [%4];"
               : "=r"(r0), "=r"(r1), "=r"(r2), "=r"(r3) : "r"(addr) : "memory");
}
DEVI void ldmatrix_x2(uint32_t& r0, uint32_t& r1, uint32_t addr) {
  asm volatile("ldmatrix.sync.aligned.m8n8.x2.shared.b16 {%0, %1}, [%2];"
               : "=r"(r0), "=r"(r1) : "r"(addr) : "memory");
}
DEVI void ldmatrix_x4_t(uint32_t (&r)[4], uint32_t addr) {
  asm volatile("ldmatrix.sync.aligned.m8n8.x4.trans.shared.b16 {%0, %1, %2, %3}, [%4];"
               : "=r"(r[0]), "=r"(r[1]), "=r"(r[2]), "=r"(r[3]) : "r"(addr) : "memory");
}
DEVI void stmatrix_x4(uint32_t addr, uint32_t r0, uint32_t r1, uint32_t r2, uint32_t r3) {
  asm volatile("stmatrix.sync.aligned.m8n8.x4.shared.b16 [%0], {%1, %2, %3, %4};"
               ::"r"(addr), "r"(r0), "r"(r1), "r"(r2), "r"(r3) : "memory");
}
DEVI void stmatrix_x4_t(uint32_t addr, uint32_t r0, uint32_t r1, uint32_t r2, uint32_t r3) {
  asm volatile("stmatrix.sync.aligned.m8n8.x4.trans.shared.b16 [%0], {%1, %2, %3, %4};"
               ::"r"(addr), "r"(r0), "r"(r1), "r"(r2), "r"(r3) : "memory");
}
DEVI void mma16816(float (&d)[4], const uint32_t (&a)[4], uint32_t b0, uint32_t b1) {
  asm volatile("mma.sync.aligned.m16n8k16.row.col.f32.bf16.bf16.f32 {%0, %1, %2, %3}, {%4, %5, %6, %7}, {%8, %9}, {%0, %1, %2, %3};"
               : "+f"(d[0]), "+f"(d[1]), "+f"(d[2]), "+f"(d[3])
               : "r"(a[0]), "r"(a[1]), "r"(a[2]), "r"(a[3]), "r"(b0), "r"(b1));
}
DEVI void mma16816_z(float (&d)[4], const uint32_t (&a)[4], uint32_t b0, uint32_t b1) {
  asm volatile("mma.sync.aligned.m16n8k16.row.col.f32.bf16.bf16.f32 {%0, %1, %2, %3}, {%4, %5, %6, %7}, {%8, %9}, {%10, %10, %10, %10};"
               : "=f"(d[0]), "=f"(d[1]), "=f"(d[2]), "=f"(d[3])
               : "r"(a[0]), "r"(a[1]), "r"(a[2]), "r"(a[3]), "r"(b0), "r"(b1), "f"(0.f));
}
DEVI void mma16816_c(float (&d)[4], const uint32_t (&a)[4], uint32_t b0, uint32_t b1, const float (&c)[4]) {
  asm volatile("mma.sync.aligned.m16n8k16.row.col.f32.bf16.bf16.f32 {%0, %1, %2, %3}, {%4, %5, %6, %7}, {%8, %9}, {%10, %11, %12, %13};"
               : "=f"(d[0]), "=f"(d[1]), "=f"(d[2]), "=f"(d[3])
               : "r"(a[0]), "r"(a[1]), "r"(a[2]), "r"(a[3]), "r"(b0), "r"(b1), "f"(c[0]), "f"(c[1]), "f"(c[2]), "f"(c[3]));
}
template <int BIT>
DEVI void sel2(uint32_t mask, float& r0, float& r1, float a0, float a1, float b0, float b1) {
  asm("{\n.reg .pred p;\n.reg .b32 t;\nand.b32 t, %2, %7;\nsetp.ne.b32 p, t, 0;\nselp.f32 %0, %3, %5, p;\nselp.f32 %1, %4, %6, p;\n}"
      : "=f"(r0), "=f"(r1) : "r"(mask), "f"(a0), "f"(a1), "f"(b0), "f"(b1), "n"(BIT));
}
template <int BIT>
DEVI void split2(uint32_t mask, uint32_t& r0, uint32_t& r1, uint32_t v) {
  asm("{\n.reg .pred p;\n.reg .b32 t;\nand.b32 t, %2, %4;\nsetp.ne.b32 p, t, 0;\nselp.b32 %0, %3, 0, p;\nselp.b32 %1, 0, %3, p;\n}"
      : "=r"(r0), "=r"(r1) : "r"(mask), "r"(v), "n"(BIT));
}
DEVI void stg32_if(uint32_t* p, uint32_t v, bool on) {
  asm volatile("{\n.reg .pred q;\nsetp.ne.u32 q, %2, 0;\n@q st.global.u32 [%0], %1;\n}" ::"l"(p), "r"(v), "r"((uint32_t)on) : "memory");
}
DEVI uint4 ldg128(const void* p) {
  uint4 v;
  asm volatile("ld.global.nc.v4.u32 {%0, %1, %2, %3}, [%4];" : "=r"(v.x), "=r"(v.y), "=r"(v.z), "=r"(v.w) : "l"(p));
  return v;
}
DEVI uint32_t ld_acquire(const uint32_t* p) {
  uint32_t v;
  asm volatile("ld.acquire.gpu.global.u32 %0, [%1];" : "=r"(v) : "l"(p) : "memory");
  return v;
}
DEVI uint32_t ld_relaxed(const uint32_t* p) {
  uint32_t v;
  asm volatile("ld.relaxed.gpu.global.u32 %0, [%1];" : "=r"(v) : "l"(p) : "memory");
  return v;
}
DEVI void st_relaxed(uint32_t* p, uint32_t v) {
  asm volatile("st.relaxed.gpu.global.u32 [%0], %1;" ::"l"(p), "r"(v) : "memory");
}
DEVI void red_max_release(uint32_t* p, uint32_t v) {
  asm volatile("red.release.gpu.global.max.u32 [%0], %1;" ::"l"(p), "r"(v) : "memory");
}
DEVI void fence_gpu() { asm volatile("fence.acq_rel.gpu;" ::: "memory"); }
DEVI uint32_t lds32(uint32_t addr) {
  uint32_t v;
  asm volatile("ld.shared.u32 %0, [%1];" : "=r"(v) : "r"(addr) : "memory");
  return v;
}
DEVI uint32_t atom_inc_shared(uint32_t addr) {
  uint32_t v;
  asm volatile("atom.shared.add.u32 %0, [%1], 1;" : "=r"(v) : "r"(addr) : "memory");
  return v;
}
DEVI void sts32(uint32_t addr, uint32_t v) {
  asm volatile("st.shared.u32 [%0], %1;" ::"r"(addr), "r"(v) : "memory");
}
DEVI void sts128(uint32_t addr, uint4 v) {
  asm volatile("st.shared.v4.u32 [%0], {%1, %2, %3, %4};" ::"r"(addr), "r"(v.x), "r"(v.y), "r"(v.z), "r"(v.w) : "memory");
}
DEVI void named_bar_arrive(int id, int n) { asm volatile("bar.arrive %0, %1;" ::"r"(id), "r"(n) : "memory"); }
DEVI void named_bar_sync(int id, int n) { asm volatile("bar.sync %0, %1;" ::"r"(id), "r"(n) : "memory"); }
DEVI void fence_proxy_async() { asm volatile("fence.proxy.async.shared::cta;" ::: "memory"); }
DEVI void fence_proxy_async_global() { asm volatile("fence.proxy.async.global;" ::: "memory"); }
DEVI int clampi(int v, int lo, int hi) { return v < lo ? lo : (v > hi ? hi : v); }

template <int TA, int TB> DEVI void wgmma_m64n144k16_ss(float (&d)[72], uint64_t descA, uint64_t descB, int scaleD) {
  asm volatile("{\n.reg .pred p;\nsetp.ne.b32 p, %74, 0;\nwgmma.mma_async.sync.aligned.m64n144k16.f32.bf16.bf16 {%0, %1, %2, %3, %4, %5, %6, %7, %8, %9, %10, %11, %12, %13, %14, %15, %16, %17, %18, %19, %20, %21, %22, %23, %24, %25, %26, %27, %28, %29, %30, %31, %32, %33, %34, %35, %36, %37, %38, %39, %40, %41, %42, %43, %44, %45, %46, %47, %48, %49, %50, %51, %52, %53, %54, %55, %56, %57, %58, %59, %60, %61, %62, %63, %64, %65, %66, %67, %68, %69, %70, %71}, %72, %73, p, 1, 1, %75, %76;\n}\n"
    : "+f"(d[0]), "+f"(d[1]), "+f"(d[2]), "+f"(d[3]), "+f"(d[4]), "+f"(d[5]), "+f"(d[6]), "+f"(d[7]), "+f"(d[8]), "+f"(d[9]), "+f"(d[10]), "+f"(d[11]), "+f"(d[12]), "+f"(d[13]), "+f"(d[14]), "+f"(d[15]), "+f"(d[16]), "+f"(d[17]), "+f"(d[18]), "+f"(d[19]), "+f"(d[20]), "+f"(d[21]), "+f"(d[22]), "+f"(d[23]), "+f"(d[24]), "+f"(d[25]), "+f"(d[26]), "+f"(d[27]), "+f"(d[28]), "+f"(d[29]), "+f"(d[30]), "+f"(d[31]), "+f"(d[32]), "+f"(d[33]), "+f"(d[34]), "+f"(d[35]), "+f"(d[36]), "+f"(d[37]), "+f"(d[38]), "+f"(d[39]), "+f"(d[40]), "+f"(d[41]), "+f"(d[42]), "+f"(d[43]), "+f"(d[44]), "+f"(d[45]), "+f"(d[46]), "+f"(d[47]), "+f"(d[48]), "+f"(d[49]), "+f"(d[50]), "+f"(d[51]), "+f"(d[52]), "+f"(d[53]), "+f"(d[54]), "+f"(d[55]), "+f"(d[56]), "+f"(d[57]), "+f"(d[58]), "+f"(d[59]), "+f"(d[60]), "+f"(d[61]), "+f"(d[62]), "+f"(d[63]), "+f"(d[64]), "+f"(d[65]), "+f"(d[66]), "+f"(d[67]), "+f"(d[68]), "+f"(d[69]), "+f"(d[70]), "+f"(d[71])
    : "l"(descA), "l"(descB), "r"(scaleD), "n"(TA), "n"(TB));
}

template <int TB> DEVI void wgmma_m64n64k16_rs(float (&d)[32], uint32_t a0, uint32_t a1, uint32_t a2, uint32_t a3, uint64_t descB, int scaleD) {
  asm volatile("{\n.reg .pred p;\nsetp.ne.b32 p, %37, 0;\nwgmma.mma_async.sync.aligned.m64n64k16.f32.bf16.bf16 {%0, %1, %2, %3, %4, %5, %6, %7, %8, %9, %10, %11, %12, %13, %14, %15, %16, %17, %18, %19, %20, %21, %22, %23, %24, %25, %26, %27, %28, %29, %30, %31}, {%32, %33, %34, %35}, %36, p, 1, 1, %38;\n}\n"
    : "+f"(d[0]), "+f"(d[1]), "+f"(d[2]), "+f"(d[3]), "+f"(d[4]), "+f"(d[5]), "+f"(d[6]), "+f"(d[7]), "+f"(d[8]), "+f"(d[9]), "+f"(d[10]), "+f"(d[11]), "+f"(d[12]), "+f"(d[13]), "+f"(d[14]), "+f"(d[15]), "+f"(d[16]), "+f"(d[17]), "+f"(d[18]), "+f"(d[19]), "+f"(d[20]), "+f"(d[21]), "+f"(d[22]), "+f"(d[23]), "+f"(d[24]), "+f"(d[25]), "+f"(d[26]), "+f"(d[27]), "+f"(d[28]), "+f"(d[29]), "+f"(d[30]), "+f"(d[31])
    : "r"(a0), "r"(a1), "r"(a2), "r"(a3), "l"(descB), "r"(scaleD), "n"(TB));
}

template <int TA, int TB> DEVI void wgmma_m64n96k16_ss(float (&d)[48], uint64_t descA, uint64_t descB, int scaleD) {
  asm volatile("{\n.reg .pred p;\nsetp.ne.b32 p, %50, 0;\nwgmma.mma_async.sync.aligned.m64n96k16.f32.bf16.bf16 {%0, %1, %2, %3, %4, %5, %6, %7, %8, %9, %10, %11, %12, %13, %14, %15, %16, %17, %18, %19, %20, %21, %22, %23, %24, %25, %26, %27, %28, %29, %30, %31, %32, %33, %34, %35, %36, %37, %38, %39, %40, %41, %42, %43, %44, %45, %46, %47}, %48, %49, p, 1, 1, %51, %52;\n}\n"
    : "+f"(d[0]), "+f"(d[1]), "+f"(d[2]), "+f"(d[3]), "+f"(d[4]), "+f"(d[5]), "+f"(d[6]), "+f"(d[7]), "+f"(d[8]), "+f"(d[9]), "+f"(d[10]), "+f"(d[11]), "+f"(d[12]), "+f"(d[13]), "+f"(d[14]), "+f"(d[15]), "+f"(d[16]), "+f"(d[17]), "+f"(d[18]), "+f"(d[19]), "+f"(d[20]), "+f"(d[21]), "+f"(d[22]), "+f"(d[23]), "+f"(d[24]), "+f"(d[25]), "+f"(d[26]), "+f"(d[27]), "+f"(d[28]), "+f"(d[29]), "+f"(d[30]), "+f"(d[31]), "+f"(d[32]), "+f"(d[33]), "+f"(d[34]), "+f"(d[35]), "+f"(d[36]), "+f"(d[37]), "+f"(d[38]), "+f"(d[39]), "+f"(d[40]), "+f"(d[41]), "+f"(d[42]), "+f"(d[43]), "+f"(d[44]), "+f"(d[45]), "+f"(d[46]), "+f"(d[47])
    : "l"(descA), "l"(descB), "r"(scaleD), "n"(TA), "n"(TB));
}

template <int TA, int TB> DEVI void wgmma_m64n48k16_ss(float (&d)[24], uint64_t descA, uint64_t descB, int scaleD) {
  asm volatile("{\n.reg .pred p;\nsetp.ne.b32 p, %26, 0;\nwgmma.mma_async.sync.aligned.m64n48k16.f32.bf16.bf16 {%0, %1, %2, %3, %4, %5, %6, %7, %8, %9, %10, %11, %12, %13, %14, %15, %16, %17, %18, %19, %20, %21, %22, %23}, %24, %25, p, 1, 1, %27, %28;\n}\n"
    : "+f"(d[0]), "+f"(d[1]), "+f"(d[2]), "+f"(d[3]), "+f"(d[4]), "+f"(d[5]), "+f"(d[6]), "+f"(d[7]), "+f"(d[8]), "+f"(d[9]), "+f"(d[10]), "+f"(d[11]), "+f"(d[12]), "+f"(d[13]), "+f"(d[14]), "+f"(d[15]), "+f"(d[16]), "+f"(d[17]), "+f"(d[18]), "+f"(d[19]), "+f"(d[20]), "+f"(d[21]), "+f"(d[22]), "+f"(d[23])
    : "l"(descA), "l"(descB), "r"(scaleD), "n"(TA), "n"(TB));
}

constexpr int kS = 112;
constexpr int kStripCtas = 112;
constexpr int kProjCtas = 20;
constexpr int kThreads = 512;
constexpr int kArr = 29;
constexpr int kExch = 27;
constexpr int kSteps = 28;
constexpr int kTiles = kSteps * 28;
constexpr int kOTileBytes = 64 * 192 * 2;
constexpr int kTailBands = 7;
constexpr int kTail0 = kSteps - kTailBands;
constexpr int kProjTiles = kTail0 * 28;
constexpr int kHaloBytes = 3 * 784 - 16, kHaloPitch = 2432;

__device__ __align__(1024) uint8_t g_o[(size_t)kTiles * kOTileBytes];
constexpr int kHaloRing = 10;
constexpr int kHaloBlock = (2 * kHaloRing + 1) * kHaloPitch;
__device__ __align__(1024) uint8_t g_halo[(size_t)kStripCtas * kHaloBlock];
__device__ __align__(1024) uint8_t g_wop[4 * 3 * 192 * 32];
__device__ uint32_t g_oflag[28 * 32];
__device__ uint32_t g_wflag[4 * 32];
__device__ uint32_t g_epoch[kProjCtas * 32];

DEVI uint32_t* halo_flags(int cta) {
  return reinterpret_cast<uint32_t*>(g_halo + (size_t)cta * kHaloBlock + 2 * kHaloRing * kHaloPitch);
}
DEVI const uint8_t* o_tile(int g, int ps) { return g_o + (size_t)(ps * kSteps + g) * kOTileBytes; }

DEVI int cta_role() {
  const int b = blockIdx.x, s = b >> 1, pat = s / 7, o = s - 7 * pat;
  return (o == 6 || s == 65) ? kStripCtas + 2 * pat + (b & 1) : 12 * pat + 2 * o + (b & 1);
}

namespace ka {
constexpr int kWAtom = 192 * 32;
constexpr int kWBytes = 9 * kWAtom;
constexpr int kXBytes = 64 * 384;
constexpr int kCol = 784;
constexpr int kQCol = 400;
constexpr int kSlot = 22 * kCol;
constexpr int kQSlot = 16 * kQCol;
constexpr int kQOff = 5 * kSlot + 32;
constexpr int kOffX = kWBytes;
constexpr int kOffRing = kOffX + 2 * kXBytes;
constexpr int kOffBar = kOffRing + kQOff + 6 * kQSlot;
constexpr int kOffStage = kOffX, kOffWo = kOffX + 2 * kWAtom;
constexpr int kOffDummy = kOffBar + 896;
DEVI uint32_t tail_buf(int i) { return i < 2 ? i * kOTileBytes : kOffRing + (i - 2) * 2 * kSlot; }
constexpr int kLastBytes = 3 * (16 + 2 * 15) * 128;
constexpr int kBarX = 0, kBarFull = 256, kBarO = 512, kBarT = 768, kBarOwn = 832, kBarJunk = 896;
constexpr int kSmemBytes = kOffBar + 896 + 704;
constexpr int kD = 6;
static_assert(kTailBands == 7, "one shared step + three per head pair; buffer reuse");
constexpr int kShift = kArr - kD + 1;
constexpr int kNbInit = 0, kNbMisc = 1, kNbBurst = 2, kNbTile = 7, kNbFirst = 13, kNbX = 14;
}

namespace kb {
constexpr int kWoBlk = 192 * 128;
constexpr int kStages = 6;
constexpr int kOffA = 3 * kWoBlk;
constexpr int kOffBar = kOffA + kStages * kOTileBytes;
constexpr int kSmemBytes = kOffBar + 192;
}

constexpr int kSmemBytes = ka::kSmemBytes > kb::kSmemBytes ? ka::kSmemBytes : kb::kSmemBytes;
static_assert(kSmemBytes <= 232448, "smem");

DEVI void mbar_wait_sleep(uint32_t bar, uint32_t parity) {
  uint32_t it = 0;
  while (!mbar_test_wait(bar, parity)) {
    __nanosleep(200);
    if (++it > LIMIT) { __trap(); break; }
  }
}

DEVI void publish_fence() {
  fence_proxy_async_global();
  fence_gpu();
}

DEVI uint32_t sched_fence() {
  uint32_t t;
  asm volatile("mov.u32 %0, %clock;" : "=r"(t)::"memory");
  return t;
}

struct AttnState {
  uint32_t kf[5][3][4];
  uint32_t vf[5][3][4];
  float bias[5][4];
  uint32_t p[5][2];
  uint32_t kaddr, vaddr, qaddr, bar, junk, fence;
  uint32_t ones[4];
  bool rdy;
  uint32_t pm;
  uint32_t* optr;
};

DEVI void store_o(AttnState& s, float (&o)[3][4], float i0, float i1, bool on) {
#pragma unroll
  for (int mt = 0; mt < 3; mt++) {
    stg32_if(s.optr + (2 * mt) * 32, pack_bf16(o[mt][0] * i0, o[mt][1] * i1), on);
    stg32_if(s.optr + (2 * mt + 1) * 32, pack_bf16(o[mt][2] * i0, o[mt][3] * i1), on);
  }
  s.optr += kOTileBytes / 4;
}

template <int PH>
DEVI void attn_step(AttnState& s, int g, int warp, const __nv_bfloat16* __restrict__ rpb) {
  using namespace ka;
  constexpr int R = (2 * PH) % 5, N0 = (R + 3) % 5, N1 = (R + 4) % 5;
  constexpr int SL = ((PH + 1) % 5) * kSlot;
  if (PH == 0 && g == 0) {
    {
      const int lane = threadIdx.x & 31, me = cta_role(), qc0 = 16 * ((me >> 2) % 7) + 2 * warp;
      const int kc = clampi(qc0 - 3, 0, kS - 8) + (lane >> 2);
      const unsigned short* r = reinterpret_cast<const unsigned short*>(rpb) + (me & 3) * 169 + (3 - (lane & 3)) * 13 + kc - qc0 + 6;
      const int sw0 = clampi(qc0 - 3, 0, kS - 7), sw1 = clampi(qc0 - 2, 0, kS - 7);
      const bool ok0 = kc >= sw0 && kc < sw0 + 7, ok1 = kc >= sw1 && kc < sw1 + 7;
#pragma unroll
      for (int i = 0; i < 10; i++) {
        const uint32_t v0 = ok0 ? (uint32_t)__ldg(r + i * 13) : 0xFF80u;
        const uint32_t v1 = ok1 ? (uint32_t)__ldg(r + i * 13 - 1) : 0xFF80u;
        s.bias[i >> 1][2 * (i & 1)] = __uint_as_float(v0 << 16) * 6.928203230275509f;
        s.bias[i >> 1][2 * (i & 1) + 1] = __uint_as_float(v1 << 16) * 6.928203230275509f;
      }
    }
    named_bar_sync(kNbMisc, 384);
    mbar_wait(s.bar + kBarFull, 0);
#pragma unroll
    for (int k = 0; k < 3; k++) {
      ldmatrix_x4(s.kf[1][k], s.kaddr + k * 32);
      ldmatrix_x4(s.kf[2][k], s.kaddr + 384 + k * 32);
      ldmatrix_x4_t(s.vf[1][k], s.vaddr + k * 32);
      ldmatrix_x4_t(s.vf[2][k], s.vaddr + 384 + k * 32);
      s.vf[0][k][0] = s.vf[0][k][1] = s.vf[0][k][2] = s.vf[0][k][3] = 0u;
    }
    named_bar_arrive(kNbFirst, 384);
    s.rdy = false;
    s.pm = (s.pm << 8) | (s.pm & 64);
  }
  if (!s.rdy) {
    mbar_wait(s.bar + kBarFull + 8 * (g + 1), 0);
    if (PH == 1 && g == 1) s.pm >>= 8;
    if (PH == 2 && g == kSteps - 1) s.pm |= 0x3Fu;
    if (PH == kShift % 5 && g == kShift && warp >= 4) {
      const uint32_t t0 = sched_fence();
      while (sched_fence() - t0 < 200) {}
    }
  }
  float t[5][4], o[3][4], z[4];
  uint32_t q[6];
  ldmatrix_x4(q[0], q[1], q[2], q[3], s.qaddr);
  ldmatrix_x2(q[4], q[5], s.qaddr + 64);
#define LDK(ks) { ldmatrix_x4(s.kf[N0][ks], s.kaddr + SL + (ks) * 32); ldmatrix_x4(s.kf[N1][ks], s.kaddr + SL + 384 + (ks) * 32); }
#define LDV(n) ldmatrix_x4_t(s.vf[(n) < 3 ? N0 : N1][(n) % 3], s.vaddr + SL + ((n) / 3) * 384 + ((n) % 3) * 32);
#define PV(i) { _Pragma("unroll") for (int mt = 0; mt < 3; mt++) { \
                  if ((i) == 0) mma16816_z(o[mt], s.vf[N0][mt], s.p[0][0], s.p[0][1]); \
                  else mma16816(o[mt], s.vf[(R + 3 + (i)) % 5][mt], s.p[i][0], s.p[i][1]); } \
                if ((i) == 0) mma16816_z(z, s.ones, s.p[0][0] | s.p[4][0], s.p[0][1] | s.p[4][1]); \
                else if ((i) < 4) mma16816(z, s.ones, s.p[i][0], s.p[i][1]); }
#define QK(ks) { _Pragma("unroll") for (int i = 0; i < 5; i++) { \
                   if ((ks) == 0) mma16816_c(t[i], s.kf[(R + i) % 5][0], q[0], q[1], s.bias[i]); \
                   else mma16816(t[i], s.kf[(R + i) % 5][ks], q[2 * (ks)], q[2 * (ks) + 1]); } }
#define FN(x) x = sched_fence();
  uint32_t f0 = 0, f1;
  if (PH == 1) {
    LDK(0) LDK(1) LDK(2) PV(0) PV(1) PV(2) PV(3) PV(4) FN(f1)
    LDV(5) LDV(4) LDV(3) LDV(2) LDV(1) LDV(0) QK(0) QK(1) FN(f0) QK(2)
  } else if (PH == 2) {
    LDK(0) LDK(1) LDK(2) PV(0) PV(1) PV(2) FN(f1)
    LDV(5) LDV(4) LDV(3) PV(3) PV(4) FN(f0) LDV(2) LDV(1) LDV(0) QK(0) QK(1) QK(2)
  } else {
    LDK(0) LDK(1) LDK(2) PV(0) PV(1) PV(2) PV(3) PV(4) FN(f1)
    LDV(5) LDV(4) LDV(3) LDV(2) LDV(1) LDV(0) QK(0) QK(1) QK(2)
  }
#undef LDK
#undef LDV
#undef PV
#undef QK
#undef FN
  const uint32_t f2 = sched_fence();
  named_bar_arrive(kNbBurst + (PH + kD) % 5, 384);
  const uint32_t fo = s.fence;
  s.fence = sched_fence();
  const uint32_t pm = s.pm;
  float x[7][2];
  sel2<1>(pm, x[0][0], x[0][1], t[0][0], t[0][1], t[3][2], t[3][3]);
  sel2<2>(pm, x[1][0], x[1][1], t[0][2], t[0][3], t[4][0], t[4][1]);
  sel2<4>(pm, x[2][0], x[2][1], t[1][0], t[1][1], t[4][2], t[4][3]);
#pragma unroll
  for (int e = 0; e < 2; e++) {
    x[3][e] = t[1][2 + e]; x[4][e] = t[2][e]; x[5][e] = t[2][2 + e]; x[6][e] = t[3][e];
  }
  float m0 = fmaxf(fmaxf(fmaxf(x[0][0], x[1][0]), fmaxf(x[2][0], x[3][0])), fmaxf(fmaxf(x[4][0], x[5][0]), x[6][0]));
  float m1 = fmaxf(fmaxf(fmaxf(x[0][1], x[1][1]), fmaxf(x[2][1], x[3][1])), fmaxf(fmaxf(x[4][1], x[5][1]), x[6][1]));
#pragma unroll
  for (int d = 4; d <= 16; d <<= 1) {
    m0 = fmaxf(m0, __shfl_xor_sync(0xffffffffu, m0, d));
    m1 = fmaxf(m1, __shfl_xor_sync(0xffffffffu, m1, d));
  }
  {
    int nx = kBarFull + 8 * (g + 2);
    if (PH >= 3 && g < 0) nx = kBarOwn + 8 * warp;
    if ((PH == (kShift - 1) % 5 && g == kShift - 1) || (PH == 0 && g == 0) || (PH == 1 && g == kSteps - 2)) nx = kBarFull + 8 * 31;
    s.rdy = mbar_test_wait(s.bar + nx, 0);
  }
  const float c = 0.14433756729740643f * 1.4426950408889634f;
  const float n0 = -m0 * c, n1 = -m1 * c;
  uint32_t pt[7];
#pragma unroll
  for (int i = 0; i < 7; i++) {
    const float e0 = ex2(fmaf(x[i][0], c, n0)), e1 = ex2(fmaf(x[i][1], c, n1));
    pt[i] = movmatrix_t(pack_bf16(e0, e1));
  }
  split2<8>(pm, s.p[0][0], s.p[3][1], pt[0]);
  split2<16>(pm, s.p[0][1], s.p[4][0], pt[1]);
  split2<32>(pm, s.p[1][0], s.p[4][1], pt[2]);
  s.p[1][1] = pt[3]; s.p[2][0] = pt[4]; s.p[2][1] = pt[5]; s.p[3][0] = pt[6];
#pragma unroll
  for (int i = 0; i < 5; i++) asm volatile("" : "+r"(s.p[i][0]), "+r"(s.p[i][1])::"memory");
  const bool real = PH == 1 || PH == 2 || g > 0;
  store_o(s, o, rcp_approx(z[0]), rcp_approx(z[1]), real);
  __syncwarp();
  if ((s.pm & 64) && real) mbar_arrive(s.bar + kBarO + 8 * (g - 1));
  s.junk ^= fo ^ f0 ^ f1 ^ f2;
  s.qaddr += kQSlot;
  if (s.qaddr >= s.bar) s.qaddr -= 6 * kQSlot;
  asm volatile("" : "+r"(s.junk)::"memory");
}

__global__ void __launch_bounds__(kThreads, 1)
nat_kernel(const __nv_bfloat16* __restrict__ wqkv, const __nv_bfloat16* __restrict__ rpb,
           const __grid_constant__ CUtensorMap tm_x, const __grid_constant__ CUtensorMap tm_w,
           const __grid_constant__ CUtensorMap tm_h, const __grid_constant__ CUtensorMap tm_r,
           const __grid_constant__ CUtensorMap tm_wo, const __grid_constant__ CUtensorMap tm_out,
           const __grid_constant__ CUtensorMap tm_wo2, const __grid_constant__ CUtensorMap tm_o2) {
  extern __shared__ __align__(1024) uint8_t smem_raw[];
  const uint32_t sbase = smem_u32(smem_raw);
  if (sbase & 1023u) __trap();
  const int warp = __shfl_sync(0xffffffffu, (int)(threadIdx.x >> 5), 0), lane = threadIdx.x & 31;
  const int wg = warp >> 2, wl = warp & 3;
  const int cta = cta_role();
  const bool strip_cta = cta < kStripCtas;
  const int head = cta & 3, ps = cta >> 2, par = ps / 7, strip = ps - 7 * par;

  if (threadIdx.x == 416) prefetch_map(strip_cta ? &tm_w : &tm_wo2);
  const int wodd = head == 1 ? 0 : (head == 2 ? 2 : -1);
  if (strip_cta && threadIdx.x == 384) {
    using namespace ka;
    const uint32_t bar = sbase + kOffBar;
    mbar_init(bar + kBarX, 1);
    mbar_expect_tx(bar + kBarX, kXBytes + (wodd >= 0 ? 7 : 6) * kWAtom);
    tma_load_5d(sbase + kOffX, &tm_x, bar + kBarX, 0, 16 * strip, -1, 3 * (par & 1), par >> 1);
#pragma unroll
    for (int i = 3; i < 9; i++)
      tma_load_2d(sbase + i * kWAtom, &tm_w, bar + kBarX, (i / 3) * 192 + head * 48 + (i % 3) * 16, 0);
    if (wodd >= 0) tma_load_2d(sbase + wodd * kWAtom, &tm_w, bar + kBarX, head * 48 + wodd * 16, 0);
  }
  __syncwarp();
  if (strip_cta && wg == 2 && threadIdx.x < 256 + 96) {
    using namespace ka;
    uint4 v[12];
    const int wk = ((int)threadIdx.x - 256) / 6, wu = (int)threadIdx.x - 256 - 6 * wk;
    const uint8_t* src = reinterpret_cast<const uint8_t*>(wqkv) + wk * 1152 + head * 96 + wu * 16;
#pragma unroll
    for (int i = 0; i < 12; i++)
      if ((wu >> 1) != wodd) v[i] = ldg128(src + i * 16 * 1152);
    const uint32_t dst = sbase + (wu >> 1) * kWAtom + wk * 32 + (((wu ^ (wk >> 2)) & 1) << 4);
#pragma unroll
    for (int i = 0; i < 12; i++)
      if ((wu >> 1) != wodd) sts128(dst + i * 16 * 32, v[i]);
    fence_proxy_async();
  }

  if (strip_cta) {
    using namespace ka;
    const uint32_t bar = sbase + kOffBar, ring = sbase + kOffRing;
    const int tskip = (head ^ (head >> 1)) & 1, thalf = head >> 1;
    if (wg < 2) {
      reg_inc<184>();
      AttnState s;
      const int qc0 = 16 * strip + 2 * warp;
      const int kc0 = clampi(qc0 - 3, 0, kS - 8);
      const uint32_t colb = ring + (kc0 - (16 * strip - 3) + (lane & 7)) * kCol;
      s.kaddr = colb + ((lane >> 3) & 1) * 192 + (lane >> 4) * 16;
      s.vaddr = colb + 96 + (lane >> 4) * 192 + ((lane >> 3) & 1) * 16;
      {
        const int qr = (lane & 7) >> 1;
        const uint32_t qa = ring + kQOff + (2 * warp + (lane & 1)) * kQCol + (lane >> 3) * 16;
        s.qaddr = qa + (qr == 3 ? 5 * kQSlot : 4 * kQSlot + (qr + 1) * 96);
      }
      s.bar = bar;
      s.optr = reinterpret_cast<uint32_t*>(g_o + (size_t)ps * kSteps * kOTileBytes + head * 6144 + warp * 768) + lane - 3 * kOTileBytes / 4;
#pragma unroll
      for (int i = 0; i < 5; i++) {
        s.p[i][0] = s.p[i][1] = 0u;
        s.bias[i][0] = s.bias[i][1] = s.bias[i][2] = s.bias[i][3] = 0.f;
#pragma unroll
        for (int k = 0; k < 3; k++)
#pragma unroll
          for (int c = 0; c < 4; c++) s.kf[i][k][c] = s.vf[i][k][c] = 0u;
      }
      s.junk = s.fence = 0;
      s.rdy = true;
      if (lane == 0) {
        mbar_init(bar + kBarOwn + 8 * warp, 1);
        mbar_arrive(bar + kBarOwn + 8 * warp);
      }
      __syncwarp();
#pragma unroll
      for (int i = 0; i < 4; i++) s.ones[i] = 0x3F803F80u;
      s.pm = (7u << (lane & 3) & 7u) | ((7u << (lane >> 3) & 7u) << 3) | (lane == 0 ? 64u : 0u);
      s.pm = __shfl_sync(0xffffffffu, s.pm, lane);
      s.kaddr = __shfl_sync(0xffffffffu, s.kaddr, lane);
      s.vaddr = __shfl_sync(0xffffffffu, s.vaddr, lane);
#pragma unroll 1
      for (int g = -2; g < kSteps; g += 5) {
        attn_step<3>(s, g, warp, rpb);
        attn_step<4>(s, g + 1, warp, rpb);
        attn_step<0>(s, g + 2, warp, rpb);
        attn_step<1>(s, g + 3, warp, rpb);
        attn_step<2>(s, g + 4, warp, rpb);
      }
      {
        float o[3][4], z[4];
#pragma unroll
        for (int mt = 0; mt < 3; mt++) mma16816_z(o[mt], s.vf[4][mt], s.p[0][0], s.p[0][1]);
        mma16816_z(z, s.ones, s.p[0][0], s.p[0][1]);
#pragma unroll
        for (int i = 1; i < 5; i++) {
#pragma unroll
          for (int mt = 0; mt < 3; mt++) mma16816(o[mt], s.vf[i - 1][mt], s.p[i][0], s.p[i][1]);
          mma16816(z, s.ones, s.p[i][0], s.p[i][1]);
        }
        store_o(s, o, rcp_approx(z[0]), rcp_approx(z[1]), true);
        __syncwarp();
        if (lane == 0) mbar_arrive(bar + kBarO + 8 * (kSteps - 1));
      }
      s.junk ^= s.fence;
      if (s.junk == 0x9e3779b9u) sts32(bar + kBarJunk, 0);
    } else if (wg == 2) {
      reg_dec<104>();
      const int col = ((lane >> 3) & 1) * 8 + (lane & 7);
      uint32_t kva = ring + (3 + col) * kCol + wl * 192 + (lane >> 4) * 16;
      uint32_t qa = ring + kQOff + col * kQCol + wl * 96 + (lane >> 4) * 16;
      const uint32_t alo = (uint32_t)make_desc(sbase + kOffX, 16, 1024, 1), blo = (uint32_t)make_desc(sbase, kWAtom, 256, 3);
      constexpr uint32_t ahi = (1u << 30) | (1024 >> 4), bhi = (3u << 30) | (256 >> 4);
      uint32_t gj = 0, qprev = 0, qk[12];
#pragma unroll
      for (int j = 0; j < 12; j++) qk[j] = 0;
      int bid = kNbBurst, tid = kNbTile;
      named_bar_arrive(kNbBurst + (kD - 2) % 5, 384);
      named_bar_arrive(kNbBurst + (kD - 1) % 5, 384);
      named_bar_sync(kNbX, 160);
      mbar_wait(bar + kBarX, 0);
#pragma unroll 1
      for (int a = 0; a < kArr; a++) {
        float acc[72];
        const uint32_t al = alo + (a & 1) * (kXBytes >> 4);
        if (a >= kD) named_bar_sync(bid, 384);
        wg_fence();
#pragma unroll
        for (int k = 0; k < 12; k++)
          wgmma_m64n144k16_ss<0, 1>(acc, desc64(al + (((k >> 2) * 8192 + (k & 3) * 32) >> 4), ahi), desc64(blo + k * 32, bhi), k != 0);
        wg_commit();
        const uint32_t gjv = sched_fence();
        gj ^= gjv;
        if (a > 0) {
#pragma unroll
          for (int j = 0; j < 3; j++) stmatrix_x4(qprev + j * 32, qk[4 * j], qk[4 * j + 1], qk[4 * j + 2], qk[4 * j + 3]);
          __syncwarp();
          if (lane == 0 && a - 1 < kExch) mbar_arrive(bar + kBarFull + 8 * (a - 1));
        }
        bid = bid == kNbBurst + 4 ? kNbBurst : bid + 1;
        if (a == 0) named_bar_sync(kNbInit, 256);
        const bool xok = mbar_test_wait(bar + kBarX + 8 * (a + 1), 0);
        if (a == kArr - 1 && wl != 0) {
          const int r = col / 3, c = col - 3 * r;
          qa = sbase + kOffDummy + lane * 16;
          kva = col < 15 && wl < 3 ? ring + ((kExch + (r >> 2)) % 5) * kSlot + ((wl - 1) * 19 + c) * kCol + (r & 3) * 192 + (lane >> 4) * 16
                                   : qa;
        }
        wg_wait<0>();
        fence_regs(acc);
        named_bar_arrive(kNbX + (a & 1), 160);
        if (a == 5) named_bar_sync(kNbFirst, 384);
#pragma unroll
        for (int j = 3; j < 9; j++)
          stmatrix_x4(kva + (j - 3) * 32, pack_bf16(acc[8 * j + 0], acc[8 * j + 1]), pack_bf16(acc[8 * j + 2], acc[8 * j + 3]),
                      pack_bf16(acc[8 * j + 4], acc[8 * j + 5]), pack_bf16(acc[8 * j + 6], acc[8 * j + 7]));
#pragma unroll
        for (int j = 0; j < 12; j++) qk[j] = pack_bf16(acc[2 * j], acc[2 * j + 1]);
        qprev = qa;
        if (a < kExch) named_bar_arrive(tid, 160);
        tid = tid == kNbTile + 5 ? kNbTile : tid + 1;
        if (!xok && a + 1 < kArr) mbar_wait(bar + kBarX + 8 * (a + 1), 0);
        kva += kSlot;
        if (kva >= ring + 5 * kSlot) kva -= 5 * kSlot;
        qa += kQSlot;
        if (qa >= bar) qa -= 6 * kQSlot;
      }
#pragma unroll
      for (int j = 0; j < 3; j++) stmatrix_x4(qprev + j * 32, qk[4 * j], qk[4 * j + 1], qk[4 * j + 2], qk[4 * j + 3]);
      __syncwarp();
      if (lane < kArr - kExch) mbar_arrive(bar + kBarFull + 8 * (kExch + lane));
      if (gj == 0x9e3779b9u) sts32(bar + kBarJunk, 0);
#pragma unroll 1
      for (int g = kArr - kD; g < kSteps - 1; g++) {
        named_bar_arrive(bid, 384);
        bid = bid == kNbBurst + 4 ? kNbBurst : bid + 1;
      }
      {
        const uint32_t wlo = (uint32_t)make_desc(sbase + kOffWo, kWAtom, 256, 3);
        const int n = lane & 7, j = 2 * wl + ((lane >> 3) & 1);
        const uint32_t sta = sbase + kOffStage + ((2 * j + (n & 1)) * 4 + (n >> 1)) * 96 + (lane >> 4) * 16;
        mbar_wait(bar + kBarX + 8 * kArr, 0);
        named_bar_sync(bid, 384);
        mbar_wait(bar + kBarO + 8 * (kSteps - 1), 0);
        {
          float acc[24];
          mbar_wait(bar + kBarT, 0);
          const uint32_t tlo = (uint32_t)make_desc(sbase + tail_buf(0), 128, 768, 0), wq = wlo + tskip * 3 * (kWAtom >> 4);
          wg_fence();
#pragma unroll
          for (int k = 0; k < 12; k++)
            wgmma_m64n48k16_ss<1, 1>(acc, desc64(tlo + (((k / 3) * 6144 + (k % 3) * 256) >> 4), 768 >> 4), desc64(wq + k * 32, bhi), k != 0);
          wg_commit();
          named_bar_sync(kNbMisc, 128);
          wg_wait<0>();
          fence_regs(acc);
#pragma unroll
          for (int jp = 0; jp < 3; jp++)
            stmatrix_x4(sta + jp * 32, pack_bf16(acc[8 * jp + 0], acc[8 * jp + 1]), pack_bf16(acc[8 * jp + 2], acc[8 * jp + 3]),
                        pack_bf16(acc[8 * jp + 4], acc[8 * jp + 5]), pack_bf16(acc[8 * jp + 6], acc[8 * jp + 7]));
          fence_proxy_async();
          named_bar_sync(kNbMisc, 128);
          if (threadIdx.x == 256) {
            tma_store_5d(&tm_out, sbase + kOffStage, thalf * 96 + tskip * 48, 4 * kTail0, 16 * strip, par & 1, par >> 1);
            bulk_commit();
          }
          __syncwarp();
        }
#pragma unroll 1
        for (int g = kTail0 + 2 - tskip, i = 1; g < kSteps; g += 2, i++) {
          float acc[48];
          mbar_wait(bar + kBarT + 8 * i, 0);
          const uint32_t tlo = (uint32_t)make_desc(sbase + tail_buf(i), 128, 768, 0);
          wg_fence();
#pragma unroll
          for (int k = 0; k < 12; k++)
            wgmma_m64n96k16_ss<1, 1>(acc, desc64(tlo + (((k / 3) * 6144 + (k % 3) * 256) >> 4), 768 >> 4), desc64(wlo + k * 32, bhi), k != 0);
          wg_commit();
          if (threadIdx.x == 256) bulk_wait_read();
          named_bar_sync(kNbMisc, 128);
          wg_wait<0>();
          fence_regs(acc);
#pragma unroll
          for (int jp = 0; jp < 6; jp++)
            stmatrix_x4(sta + (jp / 3) * kWAtom + (jp % 3) * 32, pack_bf16(acc[8 * jp + 0], acc[8 * jp + 1]),
                        pack_bf16(acc[8 * jp + 2], acc[8 * jp + 3]), pack_bf16(acc[8 * jp + 4], acc[8 * jp + 5]),
                        pack_bf16(acc[8 * jp + 6], acc[8 * jp + 7]));
          fence_proxy_async();
          named_bar_sync(kNbMisc, 128);
          if (threadIdx.x == 256) {
            tma_store_5d(&tm_out, sbase + kOffStage, thalf * 96, 4 * g, 16 * strip, par & 1, par >> 1);
            tma_store_5d(&tm_out, sbase + kOffStage + kWAtom, thalf * 96 + 48, 4 * g, 16 * strip, par & 1, par >> 1);
            bulk_commit();
          }
          __syncwarp();
        }
        if (threadIdx.x == 256) {
          bulk_wait<0>();
        }
      }
    } else {
      reg_dec<40>();
      if (wl == 0) named_bar_arrive(kNbX, 160);
      if (lane == 0) {
        const uint32_t b0 = bar + 64 * wl;
        if (wl == 1 && head == 1) tma_prefetch_5d(&tm_x, 0, 16 * strip, 3, 3 * (par & 1), par >> 1);
#pragma unroll
        for (int i = 0; i < 64; i += 8) {
          if (i || wl) mbar_init(b0 + kBarX + i, 1);
          mbar_init(b0 + kBarFull + i, wl < 3 || i < 8 * (kExch - 24) ? 6 : 4);
          mbar_init(b0 + kBarO + i, 8);
          if (wl == 0 && i < 32) mbar_init(b0 + kBarT + i, 1);
        }
#pragma unroll
        for (int i = 0; i < 64; i += 8) {
          if (i || wl)
            mbar_expect_tx(b0 + kBarX + i, wl < 3 || i < 32 ? kXBytes : (i == 32 ? kLastBytes : 6 * kWAtom));
          if (wl == 0 && i < 32) mbar_expect_tx(bar + kBarT + i, kOTileBytes);
        }
        fence_mbar_init();
        if (wl == 0) {
          tma_load_5d(sbase + kOffX + kXBytes, &tm_x, bar + kBarX + 8, 0, 16 * strip, 3, 3 * (par & 1), par >> 1);
          tma_prefetch_5d(&tm_x, 0, 16 * strip, 4 * (2 + ((head - 2) & 3)) - 1, 3 * (par & 1), par >> 1);
        }
      }
      __syncwarp();
      const uint32_t ep = ld_relaxed(halo_flags(cta) + 32 + wl) * 32u;
      named_bar_arrive(kNbMisc, 384);
      named_bar_sync(kNbInit, 256);
      if (wl == 0) {
#pragma unroll 1
        for (int a = 2; a < kArr - 1; a++) {
          named_bar_sync(kNbX + (a & 1), 160);
          if (lane == 0) {
            tma_load_5d(sbase + kOffX + (a & 1) * kXBytes, &tm_x, bar + kBarX + 8 * a, 0, 16 * strip, 4 * a - 1,
                        3 * (par & 1), par >> 1);
            if (a == 20) {
              prefetch_map(&tm_h);
              prefetch_map(&tm_r);
              prefetch_map(&tm_out);
            }
            const int ap = a + 4;
            if (ap < kArr && (ap & 3) == head) tma_prefetch_5d(&tm_x, 0, 16 * strip, 4 * ap - 1, 3 * (par & 1), par >> 1);
          }
          __syncwarp();
        }
        named_bar_sync(kNbX, 160);
        if (lane < 9) {
          const int kb = lane / 3, w = lane - 3 * kb;
          tma_load_5d(sbase + kOffX + kb * 8192 + w * 2048, w == 0 ? &tm_r : &tm_h, bar + kBarX + 8 * (kArr - 1), 0,
                      16 * strip + (w == 0 ? 0 : (w == 1 ? -3 : 16)), w == 0 ? kS - 1 : 4 * kExch - 1, 3 * (par & 1) + kb, par >> 1);
        }
        {
          uint32_t it = 0;
          while (!__all_sync(0xffffffffu, (int)(ld_acquire(&g_wflag[(lane & 3) * 32]) - (ep + 1)) >= 0))
            if (++it > LIMIT) { __trap(); break; }
        }
        const uint8_t* wsrc = g_wop + thalf * 6 * kWAtom;
        named_bar_sync(kNbX + 1, 160);
        if (lane == 0) bulk_load(sbase + kOffWo + 2 * kWAtom, wsrc + 2 * kWAtom, 4 * kWAtom, bar + kBarX + 8 * kArr);
        uint32_t seen = ld_acquire(&g_oflag[ps * 32 + (lane & 3)]);
        named_bar_sync(kNbX, 160);
        if (lane == 0) bulk_load(sbase + kOffWo, wsrc, 2 * kWAtom, bar + kBarX + 8 * kArr);
#pragma unroll 1
        for (int g = kTail0, i = 0; g < kSteps; g += i == 0 ? 2 - tskip : 2, i++) {
          uint32_t it = 0;
          while (!__all_sync(0xffffffffu, (int)(seen - (ep + g + 1)) >= 0)) {
            seen = ld_acquire(&g_oflag[ps * 32 + (lane & 3)]);
            if (++it > LIMIT) { __trap(); break; }
          }
          if (lane == 0)
            bulk_load(sbase + tail_buf(i), o_tile(g, ps), kOTileBytes, bar + kBarT + 8 * i);
          __syncwarp();
        }
      } else {
        const int p = wl - 1;
        const bool on = lane == 0 ? strip > 0 : strip < 6;
        const int nb = on ? cta + (lane == 0 ? -4 : 4) : cta;
        const uint32_t bytes = (strip > 0 && strip < 6) ? 2 * kHaloBytes : kHaloBytes;
        int slot = p, g = 0;
#pragma unroll 1
        for (int a = p; a < kExch; a += 3) {
          named_bar_sync(kNbTile + a % 6, 160);
          const uint32_t sl = ring + slot * kSlot;
          if (lane < 2) {
            fence_proxy_async();
            if (on) bulk_store(g_halo + (size_t)cta * kHaloBlock + (lane * kHaloRing + a % kHaloRing) * kHaloPitch, sl + (3 + 13 * lane) * kCol, kHaloBytes);
            bulk_commit();
          }
          __syncwarp();
          g += __ffs(~__ballot_sync(0xffffffffu, lane < 4 && mbar_test_wait(bar + kBarO + 8 * (g + lane), 0))) - 1;
          __syncwarp();
          if (lane < 2) {
            bulk_wait<0>();
            if (lane == 0) mbar_expect_tx(bar + kBarFull + 8 * a, bytes);
            else mbar_arrive(bar + kBarFull + 8 * a);
            fence_proxy_async_global();
          }
          __syncwarp();
          if (lane < 3) red_max_release(lane < 2 ? halo_flags(cta) + 4 * lane + p : &g_oflag[ps * 32 + head], lane < 2 ? ep + a + 1 : ep + g);
          __syncwarp();
          {
            const uint32_t* fl = halo_flags(nb) + 4 * ((lane & 1) ^ 1) + p;
            uint32_t it = 0;
            while (!__all_sync(0xffffffffu, !(lane < 2 && on) || (int)(ld_acquire(fl) - (ep + a + 1)) >= 0))
              if (++it > LIMIT) { __trap(); break; }
          }
          if (lane < 2 && on)
            bulk_load(sl + lane * 19 * kCol, g_halo + (size_t)nb * kHaloBlock + ((lane ^ 1) * kHaloRing + a % kHaloRing) * kHaloPitch,
                      kHaloBytes, bar + kBarFull + 8 * a);
          __syncwarp();
          slot = slot >= 2 ? slot - 2 : slot + 3;
        }
        if (lane == 0) {
#pragma unroll 1
          for (g = kSteps - 7 + p; g < kSteps; g += 3) {
            if (g < kSteps - 3) mbar_wait_sleep(bar + kBarO + 8 * g, 0);
            else mbar_wait(bar + kBarO + 8 * g, 0);
            fence_proxy_async_global();
            red_max_release(&g_oflag[ps * 32 + head], ep + g + 1);
          }
        }
      }
      __syncwarp();
      if (lane == 0) st_relaxed(halo_flags(cta) + 32 + wl, (ep >> 5) + 1);
    }
  } else {
    using namespace kb;
    const uint32_t bar = sbase + kOffBar, sA = sbase + kOffA;
    const int k = cta - kStripCtas;
    if (wg < 3) {
      named_bar_sync(0, 512);
      uint32_t wf[12][4];
      mbar_wait(bar + 56, 0);
      {
        const int kr = (lane & 7) + ((lane >> 4) << 3);
        const uint32_t wa = sbase + wg * kWoBlk + kr * 128 + (((2 * wl + ((lane >> 3) & 1)) ^ (lane & 7)) << 4);
#pragma unroll
        for (int kk = 0; kk < 12; kk++) ldmatrix_x4_t(wf[kk], wa + kk * 2048);
      }
      named_bar_sync(3 + wg, 128);
      const int px = (2 * (lane >> 4) + (lane & 1)) * 4 + ((lane & 7) >> 1);
      const uint32_t sto = sbase + wg * kWoBlk + px * 128 + (((2 * wl + ((lane >> 3) & 1)) ^ (px & 7)) << 4);
      int st = 0, sb = 0;
      uint32_t ph = 0;
      uint32_t pk[16];
#pragma unroll
      for (int i = 0; i < 16; i++) pk[i] = 0u;
      auto store = [&](int tq) {
        const int g = tq / 28, tp = tq - 28 * g, tpar = tp / 7, tstrip = tp - 7 * tpar;
#pragma unroll
        for (int jp = 0; jp < 4; jp++)
          stmatrix_x4_t(sto + sb * 8192 + jp * 2048, pk[4 * jp], pk[4 * jp + 1], pk[4 * jp + 2], pk[4 * jp + 3]);
        fence_proxy_async();
        if (wl == 0 && lane == 0) bulk_wait_read1();
        named_bar_sync(3 + wg, 128);
        if (wl == 0 && lane == 0 && tq >= 0) {
          tma_store_5d(&tm_o2, sbase + wg * kWoBlk + sb * 8192, 0, 4 * g, 16 * tstrip, 3 * (tpar & 1) + wg, tpar >> 1);
          bulk_commit();
        }
        __syncwarp();
        sb = sb == 2 ? 0 : sb + 1;
      };
      int t = k, cur = -1;
#pragma unroll 1
      for (; t < kProjTiles; t += kProjCtas) {
        float acc[32];
        const bool rdy = mbar_test_wait(bar + 8 * st, ph);
        const uint32_t blo = (uint32_t)make_desc(sA + st * kOTileBytes, 128, 768, 0);
        if (t > k || wg) named_bar_sync(6 + wg, 256);
        if (!rdy) mbar_wait(bar + 8 * st, ph);
        wg_fence();
#pragma unroll
        for (int kk = 0; kk < 12; kk++)
          wgmma_m64n64k16_rs<1>(acc, wf[kk][0], wf[kk][1], wf[kk][2], wf[kk][3],
                                desc64(blo + (((kk / 3) * 6144 + (kk % 3) * 256) >> 4), 768 >> 4), kk != 0);
        wg_commit();
        if (wg < 2 || t + kProjCtas < kProjTiles) named_bar_arrive(6 + (wg == 2 ? 0 : wg + 1), 256);
        const int nxt = (int)lds32(bar + 128 + 4 * st);
        store(cur);
        cur = nxt;
        wg_wait<0>();
        fence_regs(acc);
        if (lane == 0) mbar_arrive(bar + 64 + 8 * st);
#pragma unroll
        for (int i = 0; i < 16; i++) pk[i] = pack_bf16(acc[2 * i], acc[2 * i + 1]);
        if (++st == kStages) { st = 0; ph ^= 1; }
      }
      store(cur);
      if (wl == 0 && lane == 0) bulk_wait<0>();
    } else {
      if (lane == 0) {
        mbar_init(bar + 16 * wl, 1);
        mbar_init(bar + 16 * wl + 8, 1);
        mbar_init(bar + 64 + 16 * wl, 12);
        mbar_init(bar + 64 + 16 * wl + 8, 12);
        sts32(bar + 160, 0);
        fence_mbar_init();
      }
      __syncwarp();
      named_bar_sync(0, 512);
      if (wl == 3 && lane == 0) {
        prefetch_map(&tm_o2);
        __nanosleep(2000);
        mbar_expect_tx(bar + 56, 3 * kWoBlk);
#pragma unroll 1
        for (int i = 0; i < 3; i++) tma_load_2d(sbase + i * kWoBlk, &tm_wo2, bar + 56, i * 64, 0);
      }
      __syncwarp();
      if (wl == 3 && k < 4) {
        if (lane == 0) {
          const uint32_t e0 = ld_relaxed(&g_epoch[k * 32 + 3]);
          const uint32_t stg = sA + (kStages - 1) * kOTileBytes;
          mbar_expect_tx(bar + 48, 3 * ka::kWAtom);
#pragma unroll 1
          for (int i = 0; i < 3; i++) tma_load_2d(stg + i * ka::kWAtom, &tm_wo, bar + 48, k * 48 + i * 16, 0);
          mbar_wait(bar + 48, 0);
          bulk_store(g_wop + k * 3 * ka::kWAtom, stg, 3 * ka::kWAtom);
          bulk_commit();
          bulk_wait<0>();
          publish_fence();
          st_relaxed(&g_wflag[k * 32], e0 * 32u + 1);
          st_relaxed(&g_epoch[k * 32 + 3], e0 + 1);
        }
        __syncwarp();
        named_bar_arrive(2, 128);
      }
      if (wl < 3 && k < 4) named_bar_sync(2, 128);
      if (wl < 3 && lane < 4) {
        const uint32_t e0 = ld_relaxed(&g_epoch[k * 32 + wl]);
#pragma unroll 1
        for (int it = wl;; it += 3) {
          const int t = k + it * kProjCtas;
          if (t >= kProjTiles) break;
          const int g = t / 28, tp = t - 28 * g;
          uint32_t sp = 0;
          while (true) {
            const bool ok = (int)(ld_acquire(&g_oflag[tp * 32 + lane]) - (e0 * 32u + g + 1)) >= 0;
            if (__all_sync(15u, ok)) break;
            if (++sp > LIMIT) { __trap(); break; }
          }
          if (lane == 0) {
            const int n = (int)atom_inc_shared(bar + 160), st = n % kStages;
            if (n >= kStages) mbar_wait_sleep(bar + 64 + 8 * st, ((n / kStages) & 1) ^ 1);
            sts32(bar + 128 + 4 * st, t);
            mbar_expect_tx(bar + 8 * st, kOTileBytes);
            bulk_load_hint(sA + st * kOTileBytes, o_tile(g, tp), kOTileBytes, bar + 8 * st, policy_evict_first());
          }
          __syncwarp(15u);
        }
        if (lane == 0) st_relaxed(&g_epoch[k * 32 + wl], e0 + 1);
      }
    }
  }
}

}

namespace {

typedef CUresult (*EncodeTiledFn)(CUtensorMap*, CUtensorMapDataType, cuuint32_t, void*, const cuuint64_t*,
                                  const cuuint64_t*, const cuuint32_t*, const cuuint32_t*, CUtensorMapInterleave,
                                  CUtensorMapSwizzle, CUtensorMapL2promotion, CUtensorMapFloatOOBfill);

EncodeTiledFn get_encode_fn() {
  static EncodeTiledFn fn = nullptr;
  if (!fn) {
    void* p = nullptr;
    cudaDriverEntryPointQueryResult qres;
    if (cudaGetDriverEntryPoint("cuTensorMapEncodeTiled", &p, cudaEnableDefault, &qres) == cudaSuccess)
      fn = reinterpret_cast<EncodeTiledFn>(p);
  }
  return fn;
}

CUtensorMap make_map(void* base, int rank, const cuuint64_t* dims, const cuuint64_t* strides, const cuuint32_t* box,
                     CUtensorMapSwizzle swz) {
  CUtensorMap m;
  cuuint32_t es[5] = {1, 1, 1, 1, 1};
  get_encode_fn()(&m, CU_TENSOR_MAP_DATA_TYPE_BFLOAT16, (cuuint32_t)rank, base, dims, strides, box, es,
                  CU_TENSOR_MAP_INTERLEAVE_NONE, swz, CU_TENSOR_MAP_L2_PROMOTION_L2_128B,
                  CU_TENSOR_MAP_FLOAT_OOB_FILL_NONE);
  return m;
}

}

extern "C" void kernel_launch(void* const* d_in, const int* in_sizes, int n_in, void* d_out, int out_size) {
  using namespace nat;
  (void)in_sizes; (void)n_in; (void)out_size;
  const __nv_bfloat16* x = (const __nv_bfloat16*)d_in[0];
  const __nv_bfloat16* wqkv = (const __nv_bfloat16*)d_in[1];
  const __nv_bfloat16* wo = (const __nv_bfloat16*)d_in[2];
  const __nv_bfloat16* rpb = (const __nv_bfloat16*)d_in[3];
  __nv_bfloat16* out = (__nv_bfloat16*)d_out;

  CUtensorMap tm_x, tm_h, tm_r, tm_w, tm_wo, tm_out, tm_wo2, tm_o2;
  {
    cuuint64_t dims[5] = {64, 112, 112, 6, 2};
    cuuint64_t str[4] = {768, 2ull * 224 * 384, 128, 224ull * 384};
    cuuint32_t box[5] = {64, 16, 4, 3, 1};
    tm_x = make_map((void*)x, 5, dims, str, box, CU_TENSOR_MAP_SWIZZLE_128B);
    cuuint32_t boxh[5] = {64, 3, 5, 1, 1}, boxr[5] = {64, 16, 1, 1, 1};
    tm_h = make_map((void*)x, 5, dims, str, boxh, CU_TENSOR_MAP_SWIZZLE_128B);
    tm_r = make_map((void*)x, 5, dims, str, boxr, CU_TENSOR_MAP_SWIZZLE_128B);
  }
  {
    cuuint64_t dims[2] = {576, 192};
    cuuint64_t str[1] = {1152};
    cuuint32_t box[2] = {16, 192};
    tm_w = make_map((void*)wqkv, 2, dims, str, box, CU_TENSOR_MAP_SWIZZLE_32B);
  }
  {
    cuuint64_t dims[2] = {192, 192};
    cuuint64_t str[1] = {384};
    cuuint32_t box[2] = {16, 192};
    tm_wo = make_map((void*)wo, 2, dims, str, box, CU_TENSOR_MAP_SWIZZLE_32B);
    cuuint32_t box2[2] = {64, 192};
    tm_wo2 = make_map((void*)wo, 2, dims, str, box2, CU_TENSOR_MAP_SWIZZLE_128B);
  }
  {
    cuuint64_t dims[5] = {192, 112, 112, 2, 2};
    cuuint64_t str[4] = {2ull * 224 * 384, 768, 384, 224ull * 384};
    cuuint32_t box[5] = {48, 4, 16, 1, 1};
    tm_out = make_map((void*)out, 5, dims, str, box, CU_TENSOR_MAP_SWIZZLE_NONE);
  }
  {
    cuuint64_t dims[5] = {64, 112, 112, 6, 2};
    cuuint64_t str[4] = {2ull * 224 * 384, 768, 128, 224ull * 384};
    cuuint32_t box[5] = {64, 4, 16, 1, 1};
    tm_o2 = make_map((void*)out, 5, dims, str, box, CU_TENSOR_MAP_SWIZZLE_128B);
  }
  cudaFuncSetAttribute(nat_kernel, cudaFuncAttributeMaxDynamicSharedMemorySize, kSmemBytes);
  nat_kernel<<<kStripCtas + kProjCtas, kThreads, kSmemBytes>>>(wqkv, rpb, tm_x, tm_w, tm_h, tm_r, tm_wo, tm_out, tm_wo2, tm_o2);
}
```

```cpp
#include <cuda_runtime.h>
#include <cuda_bf16.h>
#include <cuda.h>
#include <stdint.h>

#define DEVI __device__ __forceinline__

namespace nat {

DEVI uint32_t smem_u32(const void* p) { return (uint32_t)__cvta_generic_to_shared(p); }

DEVI void mbar_init(uint32_t bar, uint32_t count) {
  asm volatile("mbarrier.init.shared::cta.b64 [%0], %1;" ::"r"(bar), "r"(count) : "memory");
}
DEVI void mbar_expect_tx(uint32_t bar, uint32_t bytes) {
  asm volatile("mbarrier.arrive.expect_tx.shared::cta.b64 _, [%0], %1;" ::"r"(bar), "r"(bytes) : "memory");
}
DEVI void mbar_arrive(uint32_t bar) {
  asm volatile("mbarrier.arrive.shared::cta.b64 _, [%0];" ::"r"(bar) : "memory");
}
DEVI bool mbar_try_wait(uint32_t bar, uint32_t parity) {
  uint32_t ok;
  asm volatile(
      "{\n.reg .pred p;\nmbarrier.try_wait.parity.shared::cta.b64 p, [%1], %2;\nselp.u32 %0, 1, 0, p;\n}\n"
      : "=r"(ok)
      : "r"(bar), "r"(parity)
      : "memory");
  return ok != 0;
}
DEVI bool mbar_test_wait(uint32_t bar, uint32_t parity) {
  uint32_t ok;
  asm volatile(
      "{\n.reg .pred p;\nmbarrier.test_wait.parity.shared::cta.b64 p, [%1], %2;\nselp.u32 %0, 1, 0, p;\n}\n"
      : "=r"(ok)
      : "r"(bar), "r"(parity)
      : "memory");
  return ok != 0;
}
#define LIMIT (1u << 20)
DEVI void mbar_wait(uint32_t bar, uint32_t parity) {
  uint32_t it = 0;
  while (!mbar_try_wait(bar, parity)) {
    if (++it > LIMIT) { __trap(); break; }
  }
}
DEVI void fence_mbar_init() { asm volatile("fence.mbarrier_init.release.cluster;" ::: "memory"); }

DEVI void tma_load_2d(uint32_t dst, const CUtensorMap* tm, uint32_t bar, int c0, int c1) {
  asm volatile(
      "cp.async.bulk.tensor.2d.shared::cluster.global.mbarrier::complete_tx::bytes [%0], [%1, {%3, %4}], [%2];"
      ::"r"(dst), "l"(tm), "r"(bar), "r"(c0), "r"(c1)
      : "memory");
}
DEVI void tma_store_5d(const CUtensorMap* tm, uint32_t src, int c0, int c1, int c2, int c3, int c4) {
  asm volatile("cp.async.bulk.tensor.5d.global.shared::cta.bulk_group [%0, {%2, %3, %4, %5, %6}], [%1];"
               ::"l"(tm), "r"(src), "r"(c0), "r"(c1), "r"(c2), "r"(c3), "r"(c4)
               : "memory");
}
DEVI void bulk_wait_read1() { asm volatile("cp.async.bulk.wait_group.read 1;" ::: "memory"); }
DEVI void tma_load_5d(uint32_t dst, const CUtensorMap* tm, uint32_t bar, int c0, int c1, int c2, int c3, int c4) {
  asm volatile(
      "cp.async.bulk.tensor.5d.shared::cluster.global.mbarrier::complete_tx::bytes [%0], [%1, {%3, %4, %5, %6, %7}], [%2];"
      ::"r"(dst), "l"(tm), "r"(bar), "r"(c0), "r"(c1), "r"(c2), "r"(c3), "r"(c4)
      : "memory");
}
DEVI uint64_t policy_evict_first() {
  uint64_t p;
  asm("createpolicy.fractional.L2::evict_first.b64 %0, 1.0;" : "=l"(p));
  return p;
}
DEVI void bulk_load_hint(uint32_t dst, const void* src, uint32_t bytes, uint32_t bar, uint64_t pol) {
  asm volatile("cp.async.bulk.shared::cluster.global.mbarrier::complete_tx::bytes.L2::cache_hint [%0], [%1], %2, [%3], %4;"
               ::"r"(dst), "l"(src), "r"(bytes), "r"(bar), "l"(pol) : "memory");
}
DEVI void prefetch_map(const CUtensorMap* tm) {
  asm volatile("prefetch.tensormap [%0];" ::"l"(tm) : "memory");
}
DEVI void tma_prefetch_5d(const CUtensorMap* tm, int c0, int c1, int c2, int c3, int c4) {
  asm volatile("cp.async.bulk.prefetch.tensor.5d.L2.global [%0, {%1, %2, %3, %4, %5}];"
               ::"l"(tm), "r"(c0), "r"(c1), "r"(c2), "r"(c3), "r"(c4)
               : "memory");
}
DEVI void bulk_load(uint32_t dst, const void* src, uint32_t bytes, uint32_t bar) {
  asm volatile("cp.async.bulk.shared::cluster.global.mbarrier::complete_tx::bytes [%0], [%1], %2, [%3];"
               ::"r"(dst), "l"(src), "r"(bytes), "r"(bar) : "memory");
}
DEVI void bulk_store(void* dst, uint32_t src, uint32_t bytes) {
  asm volatile("cp.async.bulk.global.shared::cta.bulk_group [%0], [%1], %2;" ::"l"(dst), "r"(src), "r"(bytes) : "memory");
}
DEVI void bulk_commit() { asm volatile("cp.async.bulk.commit_group;" ::: "memory"); }
template <int N>
DEVI void bulk_wait() { asm volatile("cp.async.bulk.wait_group %0;" ::"n"(N) : "memory"); }

template <int N>
DEVI void reg_dec() { asm volatile("setmaxnreg.dec.sync.aligned.u32 %0;" ::"n"(N)); }
template <int N>
DEVI void reg_inc() { asm volatile("setmaxnreg.inc.sync.aligned.u32 %0;" ::"n"(N)); }

DEVI void wg_fence() { asm volatile("wgmma.fence.sync.aligned;" ::: "memory"); }
DEVI void wg_commit() { asm volatile("wgmma.commit_group.sync.aligned;" ::: "memory"); }
template <int N>
DEVI void wg_wait() { asm volatile("wgmma.wait_group.sync.aligned %0;" ::"n"(N) : "memory"); }
template <int N>
DEVI void fence_regs(float (&d)[N]) {
#pragma unroll
  for (int i = 0; i < N; i++) asm volatile("" : "+f"(d[i])::"memory");
}

DEVI uint64_t make_desc(uint32_t addr, uint32_t lbo, uint32_t sbo, uint32_t swz) {
  return (uint64_t)((addr & 0x3FFFFu) >> 4) | ((uint64_t)((lbo & 0x3FFFFu) >> 4) << 16) |
         ((uint64_t)((sbo & 0x3FFFFu) >> 4) << 32) | ((uint64_t)swz << 62);
}

DEVI uint64_t desc64(uint32_t lo, uint32_t hi) {
  uint64_t d;
  asm("mov.b64 %0, {%1, %2};" : "=l"(d) : "r"(lo), "r"(hi));
  return d;
}
DEVI uint32_t pack_bf16(float lo, float hi) {
  uint32_t r;
  asm("cvt.rn.bf16x2.f32 %0, %1, %2;" : "=r"(r) : "f"(hi), "f"(lo));
  return r;
}
DEVI float ex2(float x) {
  float r;
  asm("ex2.approx.ftz.f32 %0, %1;" : "=f"(r) : "f"(x));
  return r;
}
DEVI float rcp_approx(float x) {
  float r;
  asm("rcp.approx.ftz.f32 %0, %1;" : "=f"(r) : "f"(x));
  return r;
}
DEVI uint32_t movmatrix_t(uint32_t a) {
  uint32_t r;
  asm("movmatrix.sync.aligned.m8n8.trans.b16 %0, %1;" : "=r"(r) : "r"(a));
  return r;
}
DEVI void ldmatrix_x4(uint32_t (&r)[4], uint32_t addr) {
  asm volatile("ldmatrix.sync.aligned.m8n8.x4.shared.b16 {%0, %1, %2, %3}, [%4];"
               : "=r"(r[0]), "=r"(r[1]), "=r"(r[2]), "=r"(r[3]) : "r"(addr) : "memory");
}
DEVI void ldmatrix_x4(uint32_t& r0, uint32_t& r1, uint32_t& r2, uint32_t& r3, uint32_t addr) {
  asm volatile("ldmatrix.sync.aligned.m8n8.x4.shared.b16 {%0, %1, %2, %3}, [%4];"
               : "=r"(r0), "=r"(r1), "=r"(r2), "=r"(r3) : "r"(addr) : "memory");
}
DEVI void ldmatrix_x2(uint32_t& r0, uint32_t& r1, uint32_t addr) {
  asm volatile("ldmatrix.sync.aligned.m8n8.x2.shared.b16 {%0, %1}, [%2];"
               : "=r"(r0), "=r"(r1) : "r"(addr) : "memory");
}
DEVI void ldmatrix_x4_t(uint32_t (&r)[4], uint32_t addr) {
  asm volatile("ldmatrix.sync.aligned.m8n8.x4.trans.shared.b16 {%0, %1, %2, %3}, [%4];"
               : "=r"(r[0]), "=r"(r[1]), "=r"(r[2]), "=r"(r[3]) : "r"(addr) : "memory");
}
DEVI void stmatrix_x4(uint32_t addr, uint32_t r0, uint32_t r1, uint32_t r2, uint32_t r3) {
  asm volatile("stmatrix.sync.aligned.m8n8.x4.shared.b16 [%0], {%1, %2, %3, %4};"
               ::"r"(addr), "r"(r0), "r"(r1), "r"(r2), "r"(r3) : "memory");
}
DEVI void stmatrix_x4_t(uint32_t addr, uint32_t r0, uint32_t r1, uint32_t r2, uint32_t r3) {
  asm volatile("stmatrix.sync.aligned.m8n8.x4.trans.shared.b16 [%0], {%1, %2, %3, %4};"
               ::"r"(addr), "r"(r0), "r"(r1), "r"(r2), "r"(r3) : "memory");
}
DEVI void mma16816(float (&d)[4], const uint32_t (&a)[4], uint32_t b0, uint32_t b1) {
  asm volatile("mma.sync.aligned.m16n8k16.row.col.f32.bf16.bf16.f32 {%0, %1, %2, %3}, {%4, %5, %6, %7}, {%8, %9}, {%0, %1, %2, %3};"
               : "+f"(d[0]), "+f"(d[1]), "+f"(d[2]), "+f"(d[3])
               : "r"(a[0]), "r"(a[1]), "r"(a[2]), "r"(a[3]), "r"(b0), "r"(b1));
}
DEVI void mma16816_z(float (&d)[4], const uint32_t (&a)[4], uint32_t b0, uint32_t b1) {
  asm volatile("mma.sync.aligned.m16n8k16.row.col.f32.bf16.bf16.f32 {%0, %1, %2, %3}, {%4, %5, %6, %7}, {%8, %9}, {%10, %10, %10, %10};"
               : "=f"(d[0]), "=f"(d[1]), "=f"(d[2]), "=f"(d[3])
               : "r"(a[0]), "r"(a[1]), "r"(a[2]), "r"(a[3]), "r"(b0), "r"(b1), "f"(0.f));
}
DEVI void mma16816_c(float (&d)[4], const uint32_t (&a)[4], uint32_t b0, uint32_t b1, const float (&c)[4]) {
  asm volatile("mma.sync.aligned.m16n8k16.row.col.f32.bf16.bf16.f32 {%0, %1, %2, %3}, {%4, %5, %6, %7}, {%8, %9}, {%10, %11, %12, %13};"
               : "=f"(d[0]), "=f"(d[1]), "=f"(d[2]), "=f"(d[3])
               : "r"(a[0]), "r"(a[1]), "r"(a[2]), "r"(a[3]), "r"(b0), "r"(b1), "f"(c[0]), "f"(c[1]), "f"(c[2]), "f"(c[3]));
}
template <int BIT>
DEVI void sel2(uint32_t mask, float& r0, float& r1, float a0, float a1, float b0, float b1) {
  asm("{\n.reg .pred p;\n.reg .b32 t;\nand.b32 t, %2, %7;\nsetp.ne.b32 p, t, 0;\nselp.f32 %0, %3, %5, p;\nselp.f32 %1, %4, %6, p;\n}"
      : "=f"(r0), "=f"(r1) : "r"(mask), "f"(a0), "f"(a1), "f"(b0), "f"(b1), "n"(BIT));
}
template <int BIT>
DEVI void split2(uint32_t mask, uint32_t& r0, uint32_t& r1, uint32_t v) {
  asm("{\n.reg .pred p;\n.reg .b32 t;\nand.b32 t, %2, %4;\nsetp.ne.b32 p, t, 0;\nselp.b32 %0, %3, 0, p;\nselp.b32 %1, 0, %3, p;\n}"
      : "=r"(r0), "=r"(r1) : "r"(mask), "r"(v), "n"(BIT));
}
DEVI void stg32_if(uint32_t* p, uint32_t v, bool on) {
  asm volatile("{\n.reg .pred q;\nsetp.ne.u32 q, %2, 0;\n@q st.global.u32 [%0], %1;\n}" ::"l"(p), "r"(v), "r"((uint32_t)on) : "memory");
}
DEVI uint4 ldg128(const void* p) {
  uint4 v;
  asm volatile("ld.global.nc.v4.u32 {%0, %1, %2, %3}, [%4];" : "=r"(v.x), "=r"(v.y), "=r"(v.z), "=r"(v.w) : "l"(p));
  return v;
}
DEVI uint32_t ld_acquire(const uint32_t* p) {
  uint32_t v;
  asm volatile("ld.acquire.gpu.global.u32 %0, [%1];" : "=r"(v) : "l"(p) : "memory");
  return v;
}
DEVI uint32_t ld_relaxed(const uint32_t* p) {
  uint32_t v;
  asm volatile("ld.relaxed.gpu.global.u32 %0, [%1];" : "=r"(v) : "l"(p) : "memory");
  return v;
}
DEVI void st_relaxed(uint32_t* p, uint32_t v) {
  asm volatile("st.relaxed.gpu.global.u32 [%0], %1;" ::"l"(p), "r"(v) : "memory");
}
DEVI void red_max_release(uint32_t* p, uint32_t v) {
  asm volatile("red.release.gpu.global.max.u32 [%0], %1;" ::"l"(p), "r"(v) : "memory");
}
DEVI void fence_gpu() { asm volatile("fence.acq_rel.gpu;" ::: "memory"); }
DEVI uint32_t lds32(uint32_t addr) {
  uint32_t v;
  asm volatile("ld.shared.u32 %0, [%1];" : "=r"(v) : "r"(addr) : "memory");
  return v;
}
DEVI uint32_t atom_inc_shared(uint32_t addr) {
  uint32_t v;
  asm volatile("atom.shared.add.u32 %0, [%1], 1;" : "=r"(v) : "r"(addr) : "memory");
  return v;
}
DEVI void sts32(uint32_t addr, uint32_t v) {
  asm volatile("st.shared.u32 [%0], %1;" ::"r"(addr), "r"(v) : "memory");
}
DEVI void sts128(uint32_t addr, uint4 v) {
  asm volatile("st.shared.v4.u32 [%0], {%1, %2, %3, %4};" ::"r"(addr), "r"(v.x), "r"(v.y), "r"(v.z), "r"(v.w) : "memory");
}
DEVI void named_bar_arrive(int id, int n) { asm volatile("bar.arrive %0, %1;" ::"r"(id), "r"(n) : "memory"); }
DEVI void named_bar_sync(int id, int n) { asm volatile("bar.sync %0, %1;" ::"r"(id), "r"(n) : "memory"); }
DEVI void fence_proxy_async() { asm volatile("fence.proxy.async.shared::cta;" ::: "memory"); }
DEVI void fence_proxy_async_global() { asm volatile("fence.proxy.async.global;" ::: "memory"); }
DEVI int clampi(int v, int lo, int hi) { return v < lo ? lo : (v > hi ? hi : v); }

template <int TA, int TB> DEVI void wgmma_m64n144k16_ss(float (&d)[72], uint64_t descA, uint64_t descB, int scaleD) {
  asm volatile("{\n.reg .pred p;\nsetp.ne.b32 p, %74, 0;\nwgmma.mma_async.sync.aligned.m64n144k16.f32.bf16.bf16 {%0, %1, %2, %3, %4, %5, %6, %7, %8, %9, %10, %11, %12, %13, %14, %15, %16, %17, %18, %19, %20, %21, %22, %23, %24, %25, %26, %27, %28, %29, %30, %31, %32, %33, %34, %35, %36, %37, %38, %39, %40, %41, %42, %43, %44, %45, %46, %47, %48, %49, %50, %51, %52, %53, %54, %55, %56, %57, %58, %59, %60, %61, %62, %63, %64, %65, %66, %67, %68, %69, %70, %71}, %72, %73, p, 1, 1, %75, %76;\n}\n"
    : "+f"(d[0]), "+f"(d[1]), "+f"(d[2]), "+f"(d[3]), "+f"(d[4]), "+f"(d[5]), "+f"(d[6]), "+f"(d[7]), "+f"(d[8]), "+f"(d[9]), "+f"(d[10]), "+f"(d[11]), "+f"(d[12]), "+f"(d[13]), "+f"(d[14]), "+f"(d[15]), "+f"(d[16]), "+f"(d[17]), "+f"(d[18]), "+f"(d[19]), "+f"(d[20]), "+f"(d[21]), "+f"(d[22]), "+f"(d[23]), "+f"(d[24]), "+f"(d[25]), "+f"(d[26]), "+f"(d[27]), "+f"(d[28]), "+f"(d[29]), "+f"(d[30]), "+f"(d[31]), "+f"(d[32]), "+f"(d[33]), "+f"(d[34]), "+f"(d[35]), "+f"(d[36]), "+f"(d[37]), "+f"(d[38]), "+f"(d[39]), "+f"(d[40]), "+f"(d[41]), "+f"(d[42]), "+f"(d[43]), "+f"(d[44]), "+f"(d[45]), "+f"(d[46]), "+f"(d[47]), "+f"(d[48]), "+f"(d[49]), "+f"(d[50]), "+f"(d[51]), "+f"(d[52]), "+f"(d[53]), "+f"(d[54]), "+f"(d[55]), "+f"(d[56]), "+f"(d[57]), "+f"(d[58]), "+f"(d[59]), "+f"(d[60]), "+f"(d[61]), "+f"(d[62]), "+f"(d[63]), "+f"(d[64]), "+f"(d[65]), "+f"(d[66]), "+f"(d[67]), "+f"(d[68]), "+f"(d[69]), "+f"(d[70]), "+f"(d[71])
    : "l"(descA), "l"(descB), "r"(scaleD), "n"(TA), "n"(TB));
}

template <int TB> DEVI void wgmma_m64n64k16_rs(float (&d)[32], uint32_t a0, uint32_t a1, uint32_t a2, uint32_t a3, uint64_t descB, int scaleD) {
  asm volatile("{\n.reg .pred p;\nsetp.ne.b32 p, %37, 0;\nwgmma.mma_async.sync.aligned.m64n64k16.f32.bf16.bf16 {%0, %1, %2, %3, %4, %5, %6, %7, %8, %9, %10, %11, %12, %13, %14, %15, %16, %17, %18, %19, %20, %21, %22, %23, %24, %25, %26, %27, %28, %29, %30, %31}, {%32, %33, %34, %35}, %36, p, 1, 1, %38;\n}\n"
    : "+f"(d[0]), "+f"(d[1]), "+f"(d[2]), "+f"(d[3]), "+f"(d[4]), "+f"(d[5]), "+f"(d[6]), "+f"(d[7]), "+f"(d[8]), "+f"(d[9]), "+f"(d[10]), "+f"(d[11]), "+f"(d[12]), "+f"(d[13]), "+f"(d[14]), "+f"(d[15]), "+f"(d[16]), "+f"(d[17]), "+f"(d[18]), "+f"(d[19]), "+f"(d[20]), "+f"(d[21]), "+f"(d[22]), "+f"(d[23]), "+f"(d[24]), "+f"(d[25]), "+f"(d[26]), "+f"(d[27]), "+f"(d[28]), "+f"(d[29]), "+f"(d[30]), "+f"(d[31])
    : "r"(a0), "r"(a1), "r"(a2), "r"(a3), "l"(descB), "r"(scaleD), "n"(TB));
}

template <int TA, int TB> DEVI void wgmma_m64n96k16_ss(float (&d)[48], uint64_t descA, uint64_t descB, int scaleD) {
  asm volatile("{\n.reg .pred p;\nsetp.ne.b32 p, %50, 0;\nwgmma.mma_async.sync.aligned.m64n96k16.f32.bf16.bf16 {%0, %1, %2, %3, %4, %5, %6, %7, %8, %9, %10, %11, %12, %13, %14, %15, %16, %17, %18, %19, %20, %21, %22, %23, %24, %25, %26, %27, %28, %29, %30, %31, %32, %33, %34, %35, %36, %37, %38, %39, %40, %41, %42, %43, %44, %45, %46, %47}, %48, %49, p, 1, 1, %51, %52;\n}\n"
    : "+f"(d[0]), "+f"(d[1]), "+f"(d[2]), "+f"(d[3]), "+f"(d[4]), "+f"(d[5]), "+f"(d[6]), "+f"(d[7]), "+f"(d[8]), "+f"(d[9]), "+f"(d[10]), "+f"(d[11]), "+f"(d[12]), "+f"(d[13]), "+f"(d[14]), "+f"(d[15]), "+f"(d[16]), "+f"(d[17]), "+f"(d[18]), "+f"(d[19]), "+f"(d[20]), "+f"(d[21]), "+f"(d[22]), "+f"(d[23]), "+f"(d[24]), "+f"(d[25]), "+f"(d[26]), "+f"(d[27]), "+f"(d[28]), "+f"(d[29]), "+f"(d[30]), "+f"(d[31]), "+f"(d[32]), "+f"(d[33]), "+f"(d[34]), "+f"(d[35]), "+f"(d[36]), "+f"(d[37]), "+f"(d[38]), "+f"(d[39]), "+f"(d[40]), "+f"(d[41]), "+f"(d[42]), "+f"(d[43]), "+f"(d[44]), "+f"(d[45]), "+f"(d[46]), "+f"(d[47])
    : "l"(descA), "l"(descB), "r"(scaleD), "n"(TA), "n"(TB));
}

template <int TA, int TB> DEVI void wgmma_m64n48k16_ss(float (&d)[24], uint64_t descA, uint64_t descB, int scaleD) {
  asm volatile("{\n.reg .pred p;\nsetp.ne.b32 p, %26, 0;\nwgmma.mma_async.sync.aligned.m64n48k16.f32.bf16.bf16 {%0, %1, %2, %3, %4, %5, %6, %7, %8, %9, %10, %11, %12, %13, %14, %15, %16, %17, %18, %19, %20, %21, %22, %23}, %24, %25, p, 1, 1, %27, %28;\n}\n"
    : "+f"(d[0]), "+f"(d[1]), "+f"(d[2]), "+f"(d[3]), "+f"(d[4]), "+f"(d[5]), "+f"(d[6]), "+f"(d[7]), "+f"(d[8]), "+f"(d[9]), "+f"(d[10]), "+f"(d[11]), "+f"(d[12]), "+f"(d[13]), "+f"(d[14]), "+f"(d[15]), "+f"(d[16]), "+f"(d[17]), "+f"(d[18]), "+f"(d[19]), "+f"(d[20]), "+f"(d[21]), "+f"(d[22]), "+f"(d[23])
    : "l"(descA), "l"(descB), "r"(scaleD), "n"(TA), "n"(TB));
}

constexpr int kS = 112;
constexpr int kStripCtas = 112;
constexpr int kProjCtas = 20;
constexpr int kThreads = 512;
constexpr int kArr = 29;
constexpr int kExch = 27;
constexpr int kSteps = 28;
constexpr int kTiles = kSteps * 28;
constexpr int kOTileBytes = 64 * 192 * 2;
constexpr int kTailBands = 7;
constexpr int kTail0 = kSteps - kTailBands;
constexpr int kProjTiles = kTail0 * 28;
constexpr int kHaloBytes = 3 * 784 - 16, kHaloPitch = 2432;

__device__ __align__(1024) uint8_t g_o[(size_t)kTiles * kOTileBytes];
constexpr int kHaloRing = 10;
constexpr int kHaloBlock = (2 * kHaloRing + 1) * kHaloPitch;
__device__ __align__(1024) uint8_t g_halo[(size_t)kStripCtas * kHaloBlock];
__device__ __align__(1024) uint8_t g_wop[4 * 3 * 192 * 32];
__device__ uint32_t g_oflag[28 * 32];
__device__ uint32_t g_wflag[4 * 32];
__device__ uint32_t g_epoch[kProjCtas * 32];

DEVI uint32_t* halo_flags(int cta) {
  return reinterpret_cast<uint32_t*>(g_halo + (size_t)cta * kHaloBlock + 2 * kHaloRing * kHaloPitch);
}
DEVI const uint8_t* o_tile(int g, int ps) { return g_o + (size_t)(ps * kSteps + g) * kOTileBytes; }

DEVI int cta_role() {
  const int b = blockIdx.x, s = b >> 1, pat = s / 7, o = s - 7 * pat;
  return (o == 6 || s == 65) ? kStripCtas + 2 * pat + (b & 1) : 12 * pat + 2 * o + (b & 1);
}

namespace ka {
constexpr int kWAtom = 192 * 32;
constexpr int kWBytes = 9 * kWAtom;
constexpr int kXBytes = 64 * 384;
constexpr int kCol = 784;
constexpr int kQCol = 400;
constexpr int kSlot = 22 * kCol;
constexpr int kQSlot = 16 * kQCol;
constexpr int kQOff = 5 * kSlot + 32;
constexpr int kOffX = kWBytes;
constexpr int kOffRing = kOffX + 2 * kXBytes;
constexpr int kOffBar = kOffRing + kQOff + 6 * kQSlot;
constexpr int kOffStage = kOffX, kOffWo = kOffX + 2 * kWAtom;
constexpr int kOffDummy = kOffBar + 896;
DEVI uint32_t stage_buf(int i) { return i == 0 ? kOffStage : ((kOffRing + kQOff + 511) & ~511) + (i - 1) * 2 * kWAtom; }
DEVI uint32_t tail_buf(int i) { return i < 2 ? i * kOTileBytes : kOffRing + (i - 2) * 2 * kSlot; }
constexpr int kLastBytes = 3 * (16 + 2 * 15) * 128;
constexpr int kBarX = 0, kBarFull = 256, kBarO = 512, kBarT = 768, kBarOwn = 832, kBarJunk = 896;
constexpr int kSmemBytes = kOffBar + 896 + 704;
constexpr int kD = 6;
static_assert(kTailBands == 7, "one shared step + three per head pair; buffer reuse");
constexpr int kNbInit = 0, kNbMisc = 1, kNbBurst = 2, kNbTile = 7, kNbFirst = 13, kNbX = 14;
}

namespace kb {
constexpr int kWoBlk = 192 * 128;
constexpr int kStages = 6;
constexpr int kOffA = 3 * kWoBlk;
constexpr int kOffBar = kOffA + kStages * kOTileBytes;
constexpr int kSmemBytes = kOffBar + 192;
}

constexpr int kSmemBytes = ka::kSmemBytes > kb::kSmemBytes ? ka::kSmemBytes : kb::kSmemBytes;
static_assert(kSmemBytes <= 232448, "smem");

DEVI void mbar_wait_sleep(uint32_t bar, uint32_t parity) {
  uint32_t it = 0;
  while (!mbar_test_wait(bar, parity)) {
    __nanosleep(200);
    if (++it > LIMIT) { __trap(); break; }
  }
}

DEVI void publish_fence() {
  fence_proxy_async_global();
  fence_gpu();
}

DEVI uint32_t sched_fence() {
  uint32_t t;
  asm volatile("mov.u32 %0, %clock;" : "=r"(t)::"memory");
  return t;
}

struct AttnState {
  uint32_t kf[5][3][4];
  uint32_t vf[5][3][4];
  float bias[5][4];
  uint32_t p[5][2];
  uint32_t kaddr, vaddr, qaddr, bar, junk, fence;
  uint32_t ones[4];
  bool rdy;
  uint32_t pm;
  uint32_t* optr;
};

DEVI void store_o(AttnState& s, float (&o)[3][4], float i0, float i1, bool on) {
#pragma unroll
  for (int mt = 0; mt < 3; mt++) {
    stg32_if(s.optr + (2 * mt) * 32, pack_bf16(o[mt][0] * i0, o[mt][1] * i1), on);
    stg32_if(s.optr + (2 * mt + 1) * 32, pack_bf16(o[mt][2] * i0, o[mt][3] * i1), on);
  }
  s.optr += kOTileBytes / 4;
}

template <int PH>
DEVI void attn_step(AttnState& s, int g, int warp, const __nv_bfloat16* __restrict__ rpb) {
  using namespace ka;
  constexpr int R = (2 * PH) % 5, N0 = (R + 3) % 5, N1 = (R + 4) % 5;
  constexpr int SL = ((PH + 1) % 5) * kSlot;
  if (PH == 0 && g == 0) {
    {
      const int lane = threadIdx.x & 31, me = cta_role(), qc0 = 16 * ((me >> 2) % 7) + 2 * warp;
      const int kc = clampi(qc0 - 3, 0, kS - 8) + (lane >> 2);
      const unsigned short* r = reinterpret_cast<const unsigned short*>(rpb) + (me & 3) * 169 + (3 - (lane & 3)) * 13 + kc - qc0 + 6;
      const int sw0 = clampi(qc0 - 3, 0, kS - 7), sw1 = clampi(qc0 - 2, 0, kS - 7);
      const bool ok0 = kc >= sw0 && kc < sw0 + 7, ok1 = kc >= sw1 && kc < sw1 + 7;
#pragma unroll
      for (int i = 0; i < 10; i++) {
        const uint32_t v0 = ok0 ? (uint32_t)__ldg(r + i * 13) : 0xFF80u;
        const uint32_t v1 = ok1 ? (uint32_t)__ldg(r + i * 13 - 1) : 0xFF80u;
        s.bias[i >> 1][2 * (i & 1)] = __uint_as_float(v0 << 16) * 6.928203230275509f;
        s.bias[i >> 1][2 * (i & 1) + 1] = __uint_as_float(v1 << 16) * 6.928203230275509f;
      }
    }
    named_bar_sync(kNbMisc, 384);
    mbar_wait(s.bar + kBarFull, 0);
#pragma unroll
    for (int k = 0; k < 3; k++) {
      ldmatrix_x4(s.kf[1][k], s.kaddr + k * 32);
      ldmatrix_x4(s.kf[2][k], s.kaddr + 384 + k * 32);
      ldmatrix_x4_t(s.vf[1][k], s.vaddr + k * 32);
      ldmatrix_x4_t(s.vf[2][k], s.vaddr + 384 + k * 32);
      s.vf[0][k][0] = s.vf[0][k][1] = s.vf[0][k][2] = s.vf[0][k][3] = 0u;
    }
    named_bar_arrive(kNbFirst, 384);
    s.rdy = false;
    s.pm = (s.pm << 8) | (s.pm & 64);
  }
  if (!s.rdy) {
    mbar_wait(s.bar + kBarFull + 8 * (g + 1), 0);
    if (PH == 1 && g == 1) s.pm >>= 8;
    if (PH == 2 && g == kSteps - 1) s.pm |= 0x3Fu;
  }
  float t[5][4], o[3][4], z[4];
  uint32_t q[6];
  ldmatrix_x4(q[0], q[1], q[2], q[3], s.qaddr);
  ldmatrix_x2(q[4], q[5], s.qaddr + 64);
#define LDK(ks) { ldmatrix_x4(s.kf[N0][ks], s.kaddr + SL + (ks) * 32); ldmatrix_x4(s.kf[N1][ks], s.kaddr + SL + 384 + (ks) * 32); }
#define LDV(n) ldmatrix_x4_t(s.vf[(n) < 3 ? N0 : N1][(n) % 3], s.vaddr + SL + ((n) / 3) * 384 + ((n) % 3) * 32);
#define PV(i) { _Pragma("unroll") for (int mt = 0; mt < 3; mt++) { \
                  if ((i) == 0) mma16816_z(o[mt], s.vf[N0][mt], s.p[0][0], s.p[0][1]); \
                  else mma16816(o[mt], s.vf[(R + 3 + (i)) % 5][mt], s.p[i][0], s.p[i][1]); } \
                if ((i) == 0) mma16816_z(z, s.ones, s.p[0][0] | s.p[4][0], s.p[0][1] | s.p[4][1]); \
                else if ((i) < 4) mma16816(z, s.ones, s.p[i][0], s.p[i][1]); }
#define QK(ks) { _Pragma("unroll") for (int i = 0; i < 5; i++) { \
                   if ((ks) == 0) mma16816_c(t[i], s.kf[(R + i) % 5][0], q[0], q[1], s.bias[i]); \
                   else mma16816(t[i], s.kf[(R + i) % 5][ks], q[2 * (ks)], q[2 * (ks) + 1]); } }
#define FN(x) x = sched_fence();
  uint32_t f0 = 0, f1;
  if (PH == 1) {
    LDK(0) LDK(1) LDK(2) PV(0) PV(1) PV(2) PV(3) PV(4) FN(f1)
    LDV(5) LDV(4) LDV(3) LDV(2) LDV(1) LDV(0) QK(0) QK(1) FN(f0) QK(2)
  } else if (PH == 2) {
    LDK(0) LDK(1) LDK(2) PV(0) PV(1) PV(2) FN(f1)
    LDV(5) LDV(4) LDV(3) PV(3) PV(4) FN(f0) LDV(2) LDV(1) LDV(0) QK(0) QK(1) QK(2)
  } else {
    LDK(0) LDK(1) LDK(2) PV(0) PV(1) PV(2) PV(3) PV(4) FN(f1)
    LDV(5) LDV(4) LDV(3) LDV(2) LDV(1) LDV(0) QK(0) QK(1) QK(2)
  }
#undef LDK
#undef LDV
#undef PV
#undef QK
#undef FN
  const uint32_t f2 = sched_fence();
  named_bar_arrive(kNbBurst + (PH + kD) % 5, 384);
  const uint32_t fo = s.fence;
  s.fence = sched_fence();
  const uint32_t pm = s.pm;
  float x[7][2];
  sel2<1>(pm, x[0][0], x[0][1], t[0][0], t[0][1], t[3][2], t[3][3]);
  sel2<2>(pm, x[1][0], x[1][1], t[0][2], t[0][3], t[4][0], t[4][1]);
  sel2<4>(pm, x[2][0], x[2][1], t[1][0], t[1][1], t[4][2], t[4][3]);
#pragma unroll
  for (int e = 0; e < 2; e++) {
    x[3][e] = t[1][2 + e]; x[4][e] = t[2][e]; x[5][e] = t[2][2 + e]; x[6][e] = t[3][e];
  }
  float m0 = fmaxf(fmaxf(fmaxf(x[0][0], x[1][0]), fmaxf(x[2][0], x[3][0])), fmaxf(fmaxf(x[4][0], x[5][0]), x[6][0]));
  float m1 = fmaxf(fmaxf(fmaxf(x[0][1], x[1][1]), fmaxf(x[2][1], x[3][1])), fmaxf(fmaxf(x[4][1], x[5][1]), x[6][1]));
#pragma unroll
  for (int d = 4; d <= 16; d <<= 1) {
    m0 = fmaxf(m0, __shfl_xor_sync(0xffffffffu, m0, d));
    m1 = fmaxf(m1, __shfl_xor_sync(0xffffffffu, m1, d));
  }
  {
    int nx = kBarFull + 8 * (g + 2);
    if (PH >= 3 && g < 0) nx = kBarOwn + 8 * warp;
    if ((PH == 0 && g == 0) || (PH == 1 && g == kSteps - 2)) nx = kBarFull + 8 * 31;
    s.rdy = mbar_test_wait(s.bar + nx, 0);
  }
  const float c = 0.14433756729740643f * 1.4426950408889634f;
  const float n0 = -m0 * c, n1 = -m1 * c;
  uint32_t pt[7];
#pragma unroll
  for (int i = 0; i < 7; i++) {
    const float e0 = ex2(fmaf(x[i][0], c, n0)), e1 = ex2(fmaf(x[i][1], c, n1));
    pt[i] = movmatrix_t(pack_bf16(e0, e1));
  }
  split2<8>(pm, s.p[0][0], s.p[3][1], pt[0]);
  split2<16>(pm, s.p[0][1], s.p[4][0], pt[1]);
  split2<32>(pm, s.p[1][0], s.p[4][1], pt[2]);
  s.p[1][1] = pt[3]; s.p[2][0] = pt[4]; s.p[2][1] = pt[5]; s.p[3][0] = pt[6];
#pragma unroll
  for (int i = 0; i < 5; i++) asm volatile("" : "+r"(s.p[i][0]), "+r"(s.p[i][1])::"memory");
  const bool real = PH == 1 || PH == 2 || g > 0;
  store_o(s, o, rcp_approx(z[0]), rcp_approx(z[1]), real);
  __syncwarp();
  if ((s.pm & 64) && real) mbar_arrive(s.bar + kBarO + 8 * (g - 1));
  s.junk ^= fo ^ f0 ^ f1 ^ f2;
  s.qaddr += kQSlot;
  if (s.qaddr >= s.bar) s.qaddr -= 6 * kQSlot;
  asm volatile("" : "+r"(s.junk)::"memory");
}

__global__ void __launch_bounds__(kThreads, 1)
nat_kernel(const __nv_bfloat16* __restrict__ wqkv, const __nv_bfloat16* __restrict__ rpb,
           const __grid_constant__ CUtensorMap tm_x, const __grid_constant__ CUtensorMap tm_w,
           const __grid_constant__ CUtensorMap tm_h, const __grid_constant__ CUtensorMap tm_r,
           const __grid_constant__ CUtensorMap tm_wo, const __grid_constant__ CUtensorMap tm_out,
           const __grid_constant__ CUtensorMap tm_wo2, const __grid_constant__ CUtensorMap tm_o2,
           const __grid_constant__ CUtensorMap tm_o3) {
  extern __shared__ __align__(1024) uint8_t smem_raw[];
  const uint32_t sbase = smem_u32(smem_raw);
  if (sbase & 1023u) __trap();
  const int warp = __shfl_sync(0xffffffffu, (int)(threadIdx.x >> 5), 0), lane = threadIdx.x & 31;
  const int wg = warp >> 2, wl = warp & 3;
  const int cta = cta_role();
  const bool strip_cta = cta < kStripCtas;
  const int head = cta & 3, ps = cta >> 2, par = ps / 7, strip = ps - 7 * par;

  if (threadIdx.x == 416) prefetch_map(strip_cta ? &tm_w : &tm_wo2);
  const int wodd = head == 1 ? 0 : (head == 2 ? 2 : -1);
  if (strip_cta && threadIdx.x == 384) {
    using namespace ka;
    const uint32_t bar = sbase + kOffBar;
    mbar_init(bar + kBarX, 1);
    mbar_expect_tx(bar + kBarX, kXBytes + (wodd >= 0 ? 7 : 6) * kWAtom);
    tma_load_5d(sbase + kOffX, &tm_x, bar + kBarX, 0, 16 * strip, -1, 3 * (par & 1), par >> 1);
#pragma unroll
    for (int i = 3; i < 9; i++)
      tma_load_2d(sbase + i * kWAtom, &tm_w, bar + kBarX, (i / 3) * 192 + head * 48 + (i % 3) * 16, 0);
    if (wodd >= 0) tma_load_2d(sbase + wodd * kWAtom, &tm_w, bar + kBarX, head * 48 + wodd * 16, 0);
  }
  __syncwarp();
  if (strip_cta && wg == 2 && threadIdx.x < 256 + 96) {
    using namespace ka;
    uint4 v[12];
    const int wk = ((int)threadIdx.x - 256) / 6, wu = (int)threadIdx.x - 256 - 6 * wk;
    const uint8_t* src = reinterpret_cast<const uint8_t*>(wqkv) + wk * 1152 + head * 96 + wu * 16;
#pragma unroll
    for (int i = 0; i < 12; i++)
      if ((wu >> 1) != wodd) v[i] = ldg128(src + i * 16 * 1152);
    const uint32_t dst = sbase + (wu >> 1) * kWAtom + wk * 32 + (((wu ^ (wk >> 2)) & 1) << 4);
#pragma unroll
    for (int i = 0; i < 12; i++)
      if ((wu >> 1) != wodd) sts128(dst + i * 16 * 32, v[i]);
    fence_proxy_async();
  }

  if (strip_cta) {
    using namespace ka;
    const uint32_t bar = sbase + kOffBar, ring = sbase + kOffRing;
    const int tskip = (head ^ (head >> 1)) & 1, thalf = head >> 1;
    if (wg < 2) {
      reg_inc<184>();
      AttnState s;
      const int qc0 = 16 * strip + 2 * warp;
      const int kc0 = clampi(qc0 - 3, 0, kS - 8);
      const uint32_t colb = ring + (kc0 - (16 * strip - 3) + (lane & 7)) * kCol;
      s.kaddr = colb + ((lane >> 3) & 1) * 192 + (lane >> 4) * 16;
      s.vaddr = colb + 96 + (lane >> 4) * 192 + ((lane >> 3) & 1) * 16;
      {
        const int qr = (lane & 7) >> 1;
        const uint32_t qa = ring + kQOff + (2 * warp + (lane & 1)) * kQCol + (lane >> 3) * 16;
        s.qaddr = qa + (qr == 3 ? 5 * kQSlot : 4 * kQSlot + (qr + 1) * 96);
      }
      s.bar = bar;
      s.optr = reinterpret_cast<uint32_t*>(g_o + (size_t)ps * kSteps * kOTileBytes + head * 6144 + warp * 768) + lane - 3 * kOTileBytes / 4;
#pragma unroll
      for (int i = 0; i < 5; i++) {
        s.p[i][0] = s.p[i][1] = 0u;
        s.bias[i][0] = s.bias[i][1] = s.bias[i][2] = s.bias[i][3] = 0.f;
#pragma unroll
        for (int k = 0; k < 3; k++)
#pragma unroll
          for (int c = 0; c < 4; c++) s.kf[i][k][c] = s.vf[i][k][c] = 0u;
      }
      s.junk = s.fence = 0;
      s.rdy = true;
      if (lane == 0) {
        mbar_init(bar + kBarOwn + 8 * warp, 1);
        mbar_arrive(bar + kBarOwn + 8 * warp);
      }
      __syncwarp();
#pragma unroll
      for (int i = 0; i < 4; i++) s.ones[i] = 0x3F803F80u;
      s.pm = (7u << (lane & 3) & 7u) | ((7u << (lane >> 3) & 7u) << 3) | (lane == 0 ? 64u : 0u);
      s.pm = __shfl_sync(0xffffffffu, s.pm, lane);
      s.kaddr = __shfl_sync(0xffffffffu, s.kaddr, lane);
      s.vaddr = __shfl_sync(0xffffffffu, s.vaddr, lane);
#pragma unroll 1
      for (int g = -2; g < kSteps; g += 5) {
        attn_step<3>(s, g, warp, rpb);
        attn_step<4>(s, g + 1, warp, rpb);
        attn_step<0>(s, g + 2, warp, rpb);
        attn_step<1>(s, g + 3, warp, rpb);
        attn_step<2>(s, g + 4, warp, rpb);
      }
      {
        float o[3][4], z[4];
#pragma unroll
        for (int mt = 0; mt < 3; mt++) mma16816_z(o[mt], s.vf[4][mt], s.p[0][0], s.p[0][1]);
        mma16816_z(z, s.ones, s.p[0][0], s.p[0][1]);
#pragma unroll
        for (int i = 1; i < 5; i++) {
#pragma unroll
          for (int mt = 0; mt < 3; mt++) mma16816(o[mt], s.vf[i - 1][mt], s.p[i][0], s.p[i][1]);
          mma16816(z, s.ones, s.p[i][0], s.p[i][1]);
        }
        store_o(s, o, rcp_approx(z[0]), rcp_approx(z[1]), true);
        __syncwarp();
        if (lane == 0) mbar_arrive(bar + kBarO + 8 * (kSteps - 1));
      }
      s.junk ^= s.fence;
      if (s.junk == 0x9e3779b9u) sts32(bar + kBarJunk, 0);
      if (warp == 0) {
#pragma unroll 1
        for (int g = kTail0, i = 0; g < kSteps; g += i == 0 ? 2 - tskip : 2, i++) {
          named_bar_sync(kNbTile + i, 160);
          if (lane == 0) {
            if (i) tma_store_5d(&tm_o3, sbase + stage_buf(i), 0, 4 * g, 16 * strip, 6 * (par & 1) + 3 * thalf, par >> 1);
            else tma_store_5d(&tm_out, sbase + kOffStage, thalf * 96 + tskip * 48, 4 * g, 16 * strip, par & 1, par >> 1);
            bulk_commit();
          }
          __syncwarp();
        }
        if (lane == 0) bulk_wait<0>();
      }
    } else if (wg == 2) {
      reg_dec<104>();
      const int col = ((lane >> 3) & 1) * 8 + (lane & 7);
      uint32_t kva = ring + (3 + col) * kCol + wl * 192 + (lane >> 4) * 16;
      uint32_t qa = ring + kQOff + col * kQCol + wl * 96 + (lane >> 4) * 16;
      const uint32_t alo = (uint32_t)make_desc(sbase + kOffX, 16, 1024, 1), blo = (uint32_t)make_desc(sbase, kWAtom, 256, 3);
      constexpr uint32_t ahi = (1u << 30) | (1024 >> 4), bhi = (3u << 30) | (256 >> 4);
      uint32_t gj = 0, qprev = 0, qk[12];
#pragma unroll
      for (int j = 0; j < 12; j++) qk[j] = 0;
      int bid = kNbBurst, tid = kNbTile;
      named_bar_arrive(kNbBurst + (kD - 2) % 5, 384);
      named_bar_arrive(kNbBurst + (kD - 1) % 5, 384);
      named_bar_sync(kNbX, 160);
      mbar_wait(bar + kBarX, 0);
#pragma unroll 1
      for (int a = 0; a < kArr; a++) {
        float acc[72];
        const uint32_t al = alo + (a & 1) * (kXBytes >> 4);
        if (a >= kD) named_bar_sync(bid, 384);
        wg_fence();
#pragma unroll
        for (int k = 0; k < 12; k++)
          wgmma_m64n144k16_ss<0, 1>(acc, desc64(al + (((k >> 2) * 8192 + (k & 3) * 32) >> 4), ahi), desc64(blo + k * 32, bhi), k != 0);
        wg_commit();
        const uint32_t gjv = sched_fence();
        gj ^= gjv;
        if (a > 0) {
#pragma unroll
          for (int j = 0; j < 3; j++) stmatrix_x4(qprev + j * 32, qk[4 * j], qk[4 * j + 1], qk[4 * j + 2], qk[4 * j + 3]);
          __syncwarp();
          if (lane == 0 && a - 1 < kExch) mbar_arrive(bar + kBarFull + 8 * (a - 1));
        }
        bid = bid == kNbBurst + 4 ? kNbBurst : bid + 1;
        if (a == 0) named_bar_sync(kNbInit, 256);
        const bool xok = mbar_test_wait(bar + kBarX + 8 * (a + 1), 0);
        if (a == kArr - 1 && wl != 0) {
          const int r = col / 3, c = col - 3 * r;
          qa = sbase + kOffDummy + lane * 16;
          kva = col < 15 && wl < 3 ? ring + ((kExch + (r >> 2)) % 5) * kSlot + ((wl - 1) * 19 + c) * kCol + (r & 3) * 192 + (lane >> 4) * 16
                                   : qa;
        }
        wg_wait<0>();
        fence_regs(acc);
        named_bar_arrive(kNbX + (a & 1), 160);
        if (a == 5) named_bar_sync(kNbFirst, 384);
#pragma unroll
        for (int j = 3; j < 9; j++)
          stmatrix_x4(kva + (j - 3) * 32, pack_bf16(acc[8 * j + 0], acc[8 * j + 1]), pack_bf16(acc[8 * j + 2], acc[8 * j + 3]),
                      pack_bf16(acc[8 * j + 4], acc[8 * j + 5]), pack_bf16(acc[8 * j + 6], acc[8 * j + 7]));
#pragma unroll
        for (int j = 0; j < 12; j++) qk[j] = pack_bf16(acc[2 * j], acc[2 * j + 1]);
        qprev = qa;
        if (a < kExch) named_bar_arrive(tid, 160);
        tid = tid == kNbTile + 5 ? kNbTile : tid + 1;
        if (!xok && a + 1 < kArr) mbar_wait(bar + kBarX + 8 * (a + 1), 0);
        kva += kSlot;
        if (kva >= ring + 5 * kSlot) kva -= 5 * kSlot;
        qa += kQSlot;
        if (qa >= bar) qa -= 6 * kQSlot;
      }
#pragma unroll
      for (int j = 0; j < 3; j++) stmatrix_x4(qprev + j * 32, qk[4 * j], qk[4 * j + 1], qk[4 * j + 2], qk[4 * j + 3]);
      __syncwarp();
      if (lane < kArr - kExch) mbar_arrive(bar + kBarFull + 8 * (kExch + lane));
      if (gj == 0x9e3779b9u) sts32(bar + kBarJunk, 0);
#pragma unroll 1
      for (int g = kArr - kD; g < kSteps - 1; g++) {
        named_bar_arrive(bid, 384);
        bid = bid == kNbBurst + 4 ? kNbBurst : bid + 1;
      }
      {
        const uint32_t wlo = (uint32_t)make_desc(sbase + kOffWo, kWAtom, 256, 3);
        const int n = lane & 7, j = 2 * wl + ((lane >> 3) & 1);
        const uint32_t sta = sbase + ((2 * j + (n & 1)) * 4 + (n >> 1)) * 96 + (lane >> 4) * 16;
        const int spx = (2 * j + (n & 1)) * 4 + (n >> 1);
        const uint32_t stb = sbase + spx * 64, swz = (lane >> 4) ^ ((spx >> 1) & 3);
        mbar_wait(bar + kBarX + 8 * kArr, 0);
        named_bar_sync(bid, 384);
        mbar_wait(bar + kBarO + 8 * (kSteps - 1), 0);
        uint32_t pk[24];
        bool trdy;
        auto stage = [&](int i) {
#pragma unroll
          for (int jp = 0; jp < 6; jp++)
            stmatrix_x4(i ? stb + stage_buf(i) + (jp >> 1) * 4096 + (((2 * (jp & 1)) ^ swz) << 4) : sta + kOffStage + (jp % 3) * 32,
                        pk[4 * jp], pk[4 * jp + 1], pk[4 * jp + 2], pk[4 * jp + 3]);
          fence_proxy_async();
          named_bar_arrive(kNbTile + i, 160);
        };
        {
          float acc[24];
          mbar_wait(bar + kBarT, 0);
          const uint32_t tlo = (uint32_t)make_desc(sbase + tail_buf(0), 128, 768, 0), wq = wlo + tskip * 3 * (kWAtom >> 4);
          wg_fence();
#pragma unroll
          for (int k = 0; k < 12; k++)
            wgmma_m64n48k16_ss<1, 1>(acc, desc64(tlo + (((k / 3) * 6144 + (k % 3) * 256) >> 4), 768 >> 4), desc64(wq + k * 32, bhi), k != 0);
          wg_commit();
          trdy = mbar_test_wait(bar + kBarT + 8, 0);
          wg_wait<0>();
          fence_regs(acc);
#pragma unroll
          for (int j = 0; j < 12; j++) pk[j] = pk[12 + j] = pack_bf16(acc[2 * j], acc[2 * j + 1]);
        }
#pragma unroll 1
        for (int g = kTail0 + 2 - tskip, i = 1; g < kSteps; g += 2, i++) {
          float acc[48];
          const uint32_t tlo = (uint32_t)make_desc(sbase + tail_buf(i), 128, 768, 0);
          if (!trdy) mbar_wait(bar + kBarT + 8 * i, 0);
          wg_fence();
#pragma unroll
          for (int k = 0; k < 12; k++)
            wgmma_m64n96k16_ss<1, 1>(acc, desc64(tlo + (((k / 3) * 6144 + (k % 3) * 256) >> 4), 768 >> 4), desc64(wlo + k * 32, bhi), k != 0);
          wg_commit();
          stage(i - 1);
          trdy = mbar_test_wait(bar + kBarT + 8 * ((i + 1) & 3), 0);
          wg_wait<0>();
          fence_regs(acc);
#pragma unroll
          for (int j = 0; j < 24; j++) pk[j] = pack_bf16(acc[2 * j], acc[2 * j + 1]);
        }
        stage(3);
      }
    } else {
      reg_dec<40>();
      if (wl == 0) named_bar_arrive(kNbX, 160);
      if (lane == 0) {
        const uint32_t b0 = bar + 64 * wl;
        if (wl == 1 && head == 1) tma_prefetch_5d(&tm_x, 0, 16 * strip, 3, 3 * (par & 1), par >> 1);
#pragma unroll
        for (int i = 0; i < 64; i += 8) {
          if (i || wl) mbar_init(b0 + kBarX + i, 1);
          mbar_init(b0 + kBarFull + i, wl < 3 || i < 8 * (kExch - 24) ? 6 : 4);
          mbar_init(b0 + kBarO + i, 8);
          if (wl == 0 && i < 32) mbar_init(b0 + kBarT + i, 1);
        }
#pragma unroll
        for (int i = 0; i < 64; i += 8) {
          if (i || wl)
            mbar_expect_tx(b0 + kBarX + i, wl < 3 || i < 32 ? kXBytes : (i == 32 ? kLastBytes : 6 * kWAtom));
          if (wl == 0 && i < 32) mbar_expect_tx(bar + kBarT + i, kOTileBytes);
        }
        fence_mbar_init();
        if (wl == 0) {
          tma_load_5d(sbase + kOffX + kXBytes, &tm_x, bar + kBarX + 8, 0, 16 * strip, 3, 3 * (par & 1), par >> 1);
          tma_prefetch_5d(&tm_x, 0, 16 * strip, 4 * (2 + ((head - 2) & 3)) - 1, 3 * (par & 1), par >> 1);
        }
      }
      __syncwarp();
      const uint32_t ep = ld_relaxed(halo_flags(cta) + 32 + wl) * 32u;
      named_bar_arrive(kNbMisc, 384);
      named_bar_sync(kNbInit, 256);
      if (wl == 0) {
#pragma unroll 1
        for (int a = 2; a < kArr - 1; a++) {
          named_bar_sync(kNbX + (a & 1), 160);
          if (lane == 0) {
            tma_load_5d(sbase + kOffX + (a & 1) * kXBytes, &tm_x, bar + kBarX + 8 * a, 0, 16 * strip, 4 * a - 1,
                        3 * (par & 1), par >> 1);
            if (a == 20) {
              prefetch_map(&tm_h);
              prefetch_map(&tm_r);
              prefetch_map(&tm_out);
              prefetch_map(&tm_o3);
            }
            const int ap = a + 4;
            if (ap < kArr && (ap & 3) == head) tma_prefetch_5d(&tm_x, 0, 16 * strip, 4 * ap - 1, 3 * (par & 1), par >> 1);
          }
          __syncwarp();
        }
        {
          uint32_t it = 0;
          while (!__all_sync(0xffffffffu, (int)(ld_acquire(&g_wflag[(lane & 3) * 32]) - (ep + 1)) >= 0))
            if (++it > LIMIT) { __trap(); break; }
        }
        named_bar_sync(kNbX, 160);
        if (lane < 9) {
          const int kb = lane / 3, w = lane - 3 * kb;
          tma_load_5d(sbase + kOffX + kb * 8192 + w * 2048, w == 0 ? &tm_r : &tm_h, bar + kBarX + 8 * (kArr - 1), 0,
                      16 * strip + (w == 0 ? 0 : (w == 1 ? -3 : 16)), w == 0 ? kS - 1 : 4 * kExch - 1, 3 * (par & 1) + kb, par >> 1);
        }
        const uint8_t* wsrc = g_wop + thalf * 6 * kWAtom;
        named_bar_sync(kNbX + 1, 160);
        if (lane == 0) bulk_load(sbase + kOffWo + 2 * kWAtom, wsrc + 2 * kWAtom, 4 * kWAtom, bar + kBarX + 8 * kArr);
        uint32_t seen = ld_acquire(&g_oflag[ps * 32 + (lane & 3)]);
        named_bar_sync(kNbX, 160);
        if (lane == 0) bulk_load(sbase + kOffWo, wsrc, 2 * kWAtom, bar + kBarX + 8 * kArr);
#pragma unroll 1
        for (int g = kTail0, i = 0; g < kSteps; g += i == 0 ? 2 - tskip : 2, i++) {
          uint32_t it = 0;
          while (!__all_sync(0xffffffffu, (int)(seen - (ep + g + 1)) >= 0)) {
            seen = ld_acquire(&g_oflag[ps * 32 + (lane & 3)]);
            if (++it > LIMIT) { __trap(); break; }
          }
          if (lane == 0)
            bulk_load(sbase + tail_buf(i), o_tile(g, ps), kOTileBytes, bar + kBarT + 8 * i);
          __syncwarp();
        }
      } else {
        const int p = wl - 1;
        const bool on = lane == 0 ? strip > 0 : strip < 6;
        const int nb = on ? cta + (lane == 0 ? -4 : 4) : cta;
        const uint32_t bytes = (strip > 0 && strip < 6) ? 2 * kHaloBytes : kHaloBytes;
        int slot = p, g = 0;
#pragma unroll 1
        for (int a = p; a < kExch; a += 3) {
          named_bar_sync(kNbTile + a % 6, 160);
          const uint32_t sl = ring + slot * kSlot;
          if (lane < 2) {
            fence_proxy_async();
            if (on) bulk_store(g_halo + (size_t)cta * kHaloBlock + (lane * kHaloRing + a % kHaloRing) * kHaloPitch, sl + (3 + 13 * lane) * kCol, kHaloBytes);
            bulk_commit();
          }
          __syncwarp();
          g += __ffs(~__ballot_sync(0xffffffffu, lane < 4 && mbar_test_wait(bar + kBarO + 8 * (g + lane), 0))) - 1;
          __syncwarp();
          if (lane < 2) {
            bulk_wait<0>();
            if (lane == 0) mbar_expect_tx(bar + kBarFull + 8 * a, bytes);
            else mbar_arrive(bar + kBarFull + 8 * a);
            fence_proxy_async_global();
          }
          __syncwarp();
          if (lane < 3) red_max_release(lane < 2 ? halo_flags(cta) + 4 * lane + p : &g_oflag[ps * 32 + head], lane < 2 ? ep + a + 1 : ep + g);
          __syncwarp();
          {
            const uint32_t* fl = halo_flags(nb) + 4 * ((lane & 1) ^ 1) + p;
            uint32_t it = 0;
            while (!__all_sync(0xffffffffu, !(lane < 2 && on) || (int)(ld_acquire(fl) - (ep + a + 1)) >= 0))
              if (++it > LIMIT) { __trap(); break; }
          }
          if (lane < 2 && on)
            bulk_load(sl + lane * 19 * kCol, g_halo + (size_t)nb * kHaloBlock + ((lane ^ 1) * kHaloRing + a % kHaloRing) * kHaloPitch,
                      kHaloBytes, bar + kBarFull + 8 * a);
          __syncwarp();
          slot = slot >= 2 ? slot - 2 : slot + 3;
        }
        if (lane == 0) {
#pragma unroll 1
          for (g = kSteps - 7 + p; g < kSteps; g += 3) {
            if (g < kSteps - 3) mbar_wait_sleep(bar + kBarO + 8 * g, 0);
            else mbar_wait(bar + kBarO + 8 * g, 0);
            fence_proxy_async_global();
            red_max_release(&g_oflag[ps * 32 + head], ep + g + 1);
          }
        }
      }
      __syncwarp();
      if (lane == 0) st_relaxed(halo_flags(cta) + 32 + wl, (ep >> 5) + 1);
    }
  } else {
    using namespace kb;
    const uint32_t bar = sbase + kOffBar, sA = sbase + kOffA;
    const int k = cta - kStripCtas;
    if (wg < 3) {
      named_bar_sync(0, 512);
      uint32_t wf[12][4];
      mbar_wait(bar + 56, 0);
      {
        const int kr = (lane & 7) + ((lane >> 4) << 3);
        const uint32_t wa = sbase + wg * kWoBlk + kr * 128 + (((2 * wl + ((lane >> 3) & 1)) ^ (lane & 7)) << 4);
#pragma unroll
        for (int kk = 0; kk < 12; kk++) ldmatrix_x4_t(wf[kk], wa + kk * 2048);
      }
      named_bar_sync(3 + wg, 128);
      const int px = (2 * (lane >> 4) + (lane & 1)) * 4 + ((lane & 7) >> 1);
      const uint32_t sto = sbase + wg * kWoBlk + px * 128 + (((2 * wl + ((lane >> 3) & 1)) ^ (px & 7)) << 4);
      int st = 0, sb = 0;
      uint32_t ph = 0;
      uint32_t pk[16];
#pragma unroll
      for (int i = 0; i < 16; i++) pk[i] = 0u;
      auto store = [&](int tq) {
        const int g = tq / 28, tp = tq - 28 * g, tpar = tp / 7, tstrip = tp - 7 * tpar;
#pragma unroll
        for (int jp = 0; jp < 4; jp++)
          stmatrix_x4_t(sto + sb * 8192 + jp * 2048, pk[4 * jp], pk[4 * jp + 1], pk[4 * jp + 2], pk[4 * jp + 3]);
        fence_proxy_async();
        if (wl == 0 && lane == 0) bulk_wait_read1();
        named_bar_sync(3 + wg, 128);
        if (wl == 0 && lane == 0 && tq >= 0) {
          tma_store_5d(&tm_o2, sbase + wg * kWoBlk + sb * 8192, 0, 4 * g, 16 * tstrip, 3 * (tpar & 1) + wg, tpar >> 1);
          bulk_commit();
        }
        __syncwarp();
        sb = sb == 2 ? 0 : sb + 1;
      };
      int t = k, cur = -1;
#pragma unroll 1
      for (; t < kProjTiles; t += kProjCtas) {
        float acc[32];
        const bool rdy = mbar_test_wait(bar + 8 * st, ph);
        const uint32_t blo = (uint32_t)make_desc(sA + st * kOTileBytes, 128, 768, 0);
        if (t > k || wg) named_bar_sync(6 + wg, 256);
        if (!rdy) mbar_wait(bar + 8 * st, ph);
        wg_fence();
#pragma unroll
        for (int kk = 0; kk < 12; kk++)
          wgmma_m64n64k16_rs<1>(acc, wf[kk][0], wf[kk][1], wf[kk][2], wf[kk][3],
                                desc64(blo + (((kk / 3) * 6144 + (kk % 3) * 256) >> 4), 768 >> 4), kk != 0);
        wg_commit();
        if (wg < 2 || t + kProjCtas < kProjTiles) named_bar_arrive(6 + (wg == 2 ? 0 : wg + 1), 256);
        const int nxt = (int)lds32(bar + 128 + 4 * st);
        store(cur);
        cur = nxt;
        wg_wait<0>();
        fence_regs(acc);
        if (lane == 0) mbar_arrive(bar + 64 + 8 * st);
#pragma unroll
        for (int i = 0; i < 16; i++) pk[i] = pack_bf16(acc[2 * i], acc[2 * i + 1]);
        if (++st == kStages) { st = 0; ph ^= 1; }
      }
      store(cur);
      if (wl == 0 && lane == 0) bulk_wait<0>();
    } else {
      if (lane == 0) {
        mbar_init(bar + 16 * wl, 1);
        mbar_init(bar + 16 * wl + 8, 1);
        mbar_init(bar + 64 + 16 * wl, 12);
        mbar_init(bar + 64 + 16 * wl + 8, 12);
        sts32(bar + 160, 0);
        fence_mbar_init();
      }
      __syncwarp();
      named_bar_sync(0, 512);
      if (wl == 3 && lane == 0) {
        prefetch_map(&tm_o2);
        __nanosleep(2000);
        mbar_expect_tx(bar + 56, 3 * kWoBlk);
#pragma unroll 1
        for (int i = 0; i < 3; i++) tma_load_2d(sbase + i * kWoBlk, &tm_wo2, bar + 56, i * 64, 0);
      }
      __syncwarp();
      if (wl == 3 && k < 4) {
        if (lane == 0) {
          const uint32_t e0 = ld_relaxed(&g_epoch[k * 32 + 3]);
          const uint32_t stg = sA + (kStages - 1) * kOTileBytes;
          mbar_expect_tx(bar + 48, 3 * ka::kWAtom);
#pragma unroll 1
          for (int i = 0; i < 3; i++) tma_load_2d(stg + i * ka::kWAtom, &tm_wo, bar + 48, k * 48 + i * 16, 0);
          mbar_wait(bar + 48, 0);
          bulk_store(g_wop + k * 3 * ka::kWAtom, stg, 3 * ka::kWAtom);
          bulk_commit();
          bulk_wait<0>();
          publish_fence();
          st_relaxed(&g_wflag[k * 32], e0 * 32u + 1);
          st_relaxed(&g_epoch[k * 32 + 3], e0 + 1);
        }
        __syncwarp();
        named_bar_arrive(2, 128);
      }
      if (wl < 3 && k < 4) named_bar_sync(2, 128);
      if (wl < 3 && lane < 4) {
        const uint32_t e0 = ld_relaxed(&g_epoch[k * 32 + wl]);
#pragma unroll 1
        for (int it = wl;; it += 3) {
          const int t = k + it * kProjCtas;
          if (t >= kProjTiles) break;
          const int g = t / 28, tp = t - 28 * g;
          uint32_t sp = 0;
          while (true) {
            const bool ok = (int)(ld_acquire(&g_oflag[tp * 32 + lane]) - (e0 * 32u + g + 1)) >= 0;
            if (__all_sync(15u, ok)) break;
            if (++sp > LIMIT) { __trap(); break; }
          }
          if (lane == 0) {
            const int n = (int)atom_inc_shared(bar + 160), st = n % kStages;
            if (n >= kStages) mbar_wait_sleep(bar + 64 + 8 * st, ((n / kStages) & 1) ^ 1);
            sts32(bar + 128 + 4 * st, t);
            mbar_expect_tx(bar + 8 * st, kOTileBytes);
            bulk_load_hint(sA + st * kOTileBytes, o_tile(g, tp), kOTileBytes, bar + 8 * st, policy_evict_first());
          }
          __syncwarp(15u);
        }
        if (lane == 0) st_relaxed(&g_epoch[k * 32 + wl], e0 + 1);
      }
    }
  }
}

}

namespace {

typedef CUresult (*EncodeTiledFn)(CUtensorMap*, CUtensorMapDataType, cuuint32_t, void*, const cuuint64_t*,
                                  const cuuint64_t*, const cuuint32_t*, const cuuint32_t*, CUtensorMapInterleave,
                                  CUtensorMapSwizzle, CUtensorMapL2promotion, CUtensorMapFloatOOBfill);

EncodeTiledFn get_encode_fn() {
  static EncodeTiledFn fn = nullptr;
  if (!fn) {
    void* p = nullptr;
    cudaDriverEntryPointQueryResult qres;
    if (cudaGetDriverEntryPoint("cuTensorMapEncodeTiled", &p, cudaEnableDefault, &qres) == cudaSuccess)
      fn = reinterpret_cast<EncodeTiledFn>(p);
  }
  return fn;
}

CUtensorMap make_map(void* base, int rank, const cuuint64_t* dims, const cuuint64_t* strides, const cuuint32_t* box,
                     CUtensorMapSwizzle swz) {
  CUtensorMap m;
  cuuint32_t es[5] = {1, 1, 1, 1, 1};
  get_encode_fn()(&m, CU_TENSOR_MAP_DATA_TYPE_BFLOAT16, (cuuint32_t)rank, base, dims, strides, box, es,
                  CU_TENSOR_MAP_INTERLEAVE_NONE, swz, CU_TENSOR_MAP_L2_PROMOTION_L2_128B,
                  CU_TENSOR_MAP_FLOAT_OOB_FILL_NONE);
  return m;
}

}

extern "C" void kernel_launch(void* const* d_in, const int* in_sizes, int n_in, void* d_out, int out_size) {
  using namespace nat;
  (void)in_sizes; (void)n_in; (void)out_size;
  const __nv_bfloat16* x = (const __nv_bfloat16*)d_in[0];
  const __nv_bfloat16* wqkv = (const __nv_bfloat16*)d_in[1];
  const __nv_bfloat16* wo = (const __nv_bfloat16*)d_in[2];
  const __nv_bfloat16* rpb = (const __nv_bfloat16*)d_in[3];
  __nv_bfloat16* out = (__nv_bfloat16*)d_out;

  CUtensorMap tm_x, tm_h, tm_r, tm_w, tm_wo, tm_out, tm_wo2, tm_o2, tm_o3;
  {
    cuuint64_t dims[5] = {64, 112, 112, 6, 2};
    cuuint64_t str[4] = {768, 2ull * 224 * 384, 128, 224ull * 384};
    cuuint32_t box[5] = {64, 16, 4, 3, 1};
    tm_x = make_map((void*)x, 5, dims, str, box, CU_TENSOR_MAP_SWIZZLE_128B);
    cuuint32_t boxh[5] = {64, 3, 5, 1, 1}, boxr[5] = {64, 16, 1, 1, 1};
    tm_h = make_map((void*)x, 5, dims, str, boxh, CU_TENSOR_MAP_SWIZZLE_128B);
    tm_r = make_map((void*)x, 5, dims, str, boxr, CU_TENSOR_MAP_SWIZZLE_128B);
  }
  {
    cuuint64_t dims[2] = {576, 192};
    cuuint64_t str[1] = {1152};
    cuuint32_t box[2] = {16, 192};
    tm_w = make_map((void*)wqkv, 2, dims, str, box, CU_TENSOR_MAP_SWIZZLE_32B);
  }
  {
    cuuint64_t dims[2] = {192, 192};
    cuuint64_t str[1] = {384};
    cuuint32_t box[2] = {16, 192};
    tm_wo = make_map((void*)wo, 2, dims, str, box, CU_TENSOR_MAP_SWIZZLE_32B);
    cuuint32_t box2[2] = {64, 192};
    tm_wo2 = make_map((void*)wo, 2, dims, str, box2, CU_TENSOR_MAP_SWIZZLE_128B);
  }
  {
    cuuint64_t dims[5] = {192, 112, 112, 2, 2};
    cuuint64_t str[4] = {2ull * 224 * 384, 768, 384, 224ull * 384};
    cuuint32_t box[5] = {48, 4, 16, 1, 1};
    tm_out = make_map((void*)out, 5, dims, str, box, CU_TENSOR_MAP_SWIZZLE_NONE);
  }
  {
    cuuint64_t dims[5] = {64, 112, 112, 6, 2};
    cuuint64_t str[4] = {2ull * 224 * 384, 768, 128, 224ull * 384};
    cuuint32_t box[5] = {64, 4, 16, 1, 1};
    tm_o2 = make_map((void*)out, 5, dims, str, box, CU_TENSOR_MAP_SWIZZLE_128B);
  }
  {
    cuuint64_t dims[5] = {32, 112, 112, 12, 2};
    cuuint64_t str[4] = {2ull * 224 * 384, 768, 64, 224ull * 384};
    cuuint32_t box[5] = {32, 4, 16, 3, 1};
    tm_o3 = make_map((void*)out, 5, dims, str, box, CU_TENSOR_MAP_SWIZZLE_64B);
  }
  cudaFuncSetAttribute(nat_kernel, cudaFuncAttributeMaxDynamicSharedMemorySize, kSmemBytes);
  nat_kernel<<<kStripCtas + kProjCtas, kThreads, kSmemBytes>>>(wqkv, rpb, tm_x, tm_w, tm_h, tm_r, tm_wo, tm_out, tm_wo2, tm_o2, tm_o3);
}
```

```cpp
#include <cuda_runtime.h>
#include <cuda_bf16.h>
#include <cuda.h>
#include <stdint.h>

#define DEVI __device__ __forceinline__

namespace nat {

DEVI uint32_t smem_u32(const void* p) { return (uint32_t)__cvta_generic_to_shared(p); }

DEVI void mbar_init(uint32_t bar, uint32_t count) {
  asm volatile("mbarrier.init.shared::cta.b64 [%0], %1;" ::"r"(bar), "r"(count) : "memory");
}
DEVI void mbar_expect_tx(uint32_t bar, uint32_t bytes) {
  asm volatile("mbarrier.arrive.expect_tx.shared::cta.b64 _, [%0], %1;" ::"r"(bar), "r"(bytes) : "memory");
}
DEVI void mbar_arrive(uint32_t bar) {
  asm volatile("mbarrier.arrive.shared::cta.b64 _, [%0];" ::"r"(bar) : "memory");
}
DEVI bool mbar_try_wait(uint32_t bar, uint32_t parity) {
  uint32_t ok;
  asm volatile(
      "{\n.reg .pred p;\nmbarrier.try_wait.parity.shared::cta.b64 p, [%1], %2;\nselp.u32 %0, 1, 0, p;\n}\n"
      : "=r"(ok)
      : "r"(bar), "r"(parity)
      : "memory");
  return ok != 0;
}
DEVI bool mbar_test_wait(uint32_t bar, uint32_t parity) {
  uint32_t ok;
  asm volatile(
      "{\n.reg .pred p;\nmbarrier.test_wait.parity.shared::cta.b64 p, [%1], %2;\nselp.u32 %0, 1, 0, p;\n}\n"
      : "=r"(ok)
      : "r"(bar), "r"(parity)
      : "memory");
  return ok != 0;
}
#define LIMIT (1u << 20)
DEVI void mbar_wait(uint32_t bar, uint32_t parity) {
  uint32_t it = 0;
  while (!mbar_try_wait(bar, parity)) {
    if (++it > LIMIT) { __trap(); break; }
  }
}
DEVI void fence_mbar_init() { asm volatile("fence.mbarrier_init.release.cluster;" ::: "memory"); }

DEVI void tma_load_2d(uint32_t dst, const CUtensorMap* tm, uint32_t bar, int c0, int c1) {
  asm volatile(
      "cp.async.bulk.tensor.2d.shared::cluster.global.mbarrier::complete_tx::bytes [%0], [%1, {%3, %4}], [%2];"
      ::"r"(dst), "l"(tm), "r"(bar), "r"(c0), "r"(c1)
      : "memory");
}
DEVI void tma_store_5d(const CUtensorMap* tm, uint32_t src, int c0, int c1, int c2, int c3, int c4) {
  asm volatile("cp.async.bulk.tensor.5d.global.shared::cta.bulk_group [%0, {%2, %3, %4, %5, %6}], [%1];"
               ::"l"(tm), "r"(src), "r"(c0), "r"(c1), "r"(c2), "r"(c3), "r"(c4)
               : "memory");
}
DEVI void bulk_wait_read1() { asm volatile("cp.async.bulk.wait_group.read 1;" ::: "memory"); }
DEVI void tma_load_5d(uint32_t dst, const CUtensorMap* tm, uint32_t bar, int c0, int c1, int c2, int c3, int c4) {
  asm volatile(
      "cp.async.bulk.tensor.5d.shared::cluster.global.mbarrier::complete_tx::bytes [%0], [%1, {%3, %4, %5, %6, %7}], [%2];"
      ::"r"(dst), "l"(tm), "r"(bar), "r"(c0), "r"(c1), "r"(c2), "r"(c3), "r"(c4)
      : "memory");
}
DEVI uint64_t policy_evict_first() {
  uint64_t p;
  asm("createpolicy.fractional.L2::evict_first.b64 %0, 1.0;" : "=l"(p));
  return p;
}
DEVI void bulk_load_hint(uint32_t dst, const void* src, uint32_t bytes, uint32_t bar, uint64_t pol) {
  asm volatile("cp.async.bulk.shared::cluster.global.mbarrier::complete_tx::bytes.L2::cache_hint [%0], [%1], %2, [%3], %4;"
               ::"r"(dst), "l"(src), "r"(bytes), "r"(bar), "l"(pol) : "memory");
}
DEVI void prefetch_map(const CUtensorMap* tm) {
  asm volatile("prefetch.tensormap [%0];" ::"l"(tm) : "memory");
}
DEVI void tma_prefetch_5d(const CUtensorMap* tm, int c0, int c1, int c2, int c3, int c4) {
  asm volatile("cp.async.bulk.prefetch.tensor.5d.L2.global [%0, {%1, %2, %3, %4, %5}];"
               ::"l"(tm), "r"(c0), "r"(c1), "r"(c2), "r"(c3), "r"(c4)
               : "memory");
}
DEVI void bulk_load(uint32_t dst, const void* src, uint32_t bytes, uint32_t bar) {
  asm volatile("cp.async.bulk.shared::cluster.global.mbarrier::complete_tx::bytes [%0], [%1], %2, [%3];"
               ::"r"(dst), "l"(src), "r"(bytes), "r"(bar) : "memory");
}
DEVI void bulk_store(void* dst, uint32_t src, uint32_t bytes) {
  asm volatile("cp.async.bulk.global.shared::cta.bulk_group [%0], [%1], %2;" ::"l"(dst), "r"(src), "r"(bytes) : "memory");
}
DEVI void bulk_commit() { asm volatile("cp.async.bulk.commit_group;" ::: "memory"); }
template <int N>
DEVI void bulk_wait() { asm volatile("cp.async.bulk.wait_group %0;" ::"n"(N) : "memory"); }

template <int N>
DEVI void reg_dec() { asm volatile("setmaxnreg.dec.sync.aligned.u32 %0;" ::"n"(N)); }
template <int N>
DEVI void reg_inc() { asm volatile("setmaxnreg.inc.sync.aligned.u32 %0;" ::"n"(N)); }

DEVI void wg_fence() { asm volatile("wgmma.fence.sync.aligned;" ::: "memory"); }
DEVI void wg_commit() { asm volatile("wgmma.commit_group.sync.aligned;" ::: "memory"); }
template <int N>
DEVI void wg_wait() { asm volatile("wgmma.wait_group.sync.aligned %0;" ::"n"(N) : "memory"); }
template <int N>
DEVI void fence_regs(float (&d)[N]) {
#pragma unroll
  for (int i = 0; i < N; i++) asm volatile("" : "+f"(d[i])::"memory");
}

DEVI uint64_t make_desc(uint32_t addr, uint32_t lbo, uint32_t sbo, uint32_t swz) {
  return (uint64_t)((addr & 0x3FFFFu) >> 4) | ((uint64_t)((lbo & 0x3FFFFu) >> 4) << 16) |
         ((uint64_t)((sbo & 0x3FFFFu) >> 4) << 32) | ((uint64_t)swz << 62);
}

DEVI uint64_t desc64(uint32_t lo, uint32_t hi) {
  uint64_t d;
  asm("mov.b64 %0, {%1, %2};" : "=l"(d) : "r"(lo), "r"(hi));
  return d;
}
DEVI uint32_t pack_bf16(float lo, float hi) {
  uint32_t r;
  asm("cvt.rn.bf16x2.f32 %0, %1, %2;" : "=r"(r) : "f"(hi), "f"(lo));
  return r;
}
DEVI float ex2(float x) {
  float r;
  asm("ex2.approx.ftz.f32 %0, %1;" : "=f"(r) : "f"(x));
  return r;
}
DEVI float rcp_approx(float x) {
  float r;
  asm("rcp.approx.ftz.f32 %0, %1;" : "=f"(r) : "f"(x));
  return r;
}
DEVI uint32_t movmatrix_t(uint32_t a) {
  uint32_t r;
  asm("movmatrix.sync.aligned.m8n8.trans.b16 %0, %1;" : "=r"(r) : "r"(a));
  return r;
}
DEVI void ldmatrix_x4(uint32_t (&r)[4], uint32_t addr) {
  asm volatile("ldmatrix.sync.aligned.m8n8.x4.shared.b16 {%0, %1, %2, %3}, [%4];"
               : "=r"(r[0]), "=r"(r[1]), "=r"(r[2]), "=r"(r[3]) : "r"(addr) : "memory");
}
DEVI void ldmatrix_x4(uint32_t& r0, uint32_t& r1, uint32_t& r2, uint32_t& r3, uint32_t addr) {
  asm volatile("ldmatrix.sync.aligned.m8n8.x4.shared.b16 {%0, %1, %2, %3}, [%4];"
               : "=r"(r0), "=r"(r1), "=r"(r2), "=r"(r3) : "r"(addr) : "memory");
}
DEVI void ldmatrix_x2(uint32_t& r0, uint32_t& r1, uint32_t addr) {
  asm volatile("ldmatrix.sync.aligned.m8n8.x2.shared.b16 {%0, %1}, [%2];"
               : "=r"(r0), "=r"(r1) : "r"(addr) : "memory");
}
DEVI void ldmatrix_x4_t(uint32_t (&r)[4], uint32_t addr) {
  asm volatile("ldmatrix.sync.aligned.m8n8.x4.trans.shared.b16 {%0, %1, %2, %3}, [%4];"
               : "=r"(r[0]), "=r"(r[1]), "=r"(r[2]), "=r"(r[3]) : "r"(addr) : "memory");
}
DEVI void stmatrix_x4(uint32_t addr, uint32_t r0, uint32_t r1, uint32_t r2, uint32_t r3) {
  asm volatile("stmatrix.sync.aligned.m8n8.x4.shared.b16 [%0], {%1, %2, %3, %4};"
               ::"r"(addr), "r"(r0), "r"(r1), "r"(r2), "r"(r3) : "memory");
}
DEVI void stmatrix_x4_t(uint32_t addr, uint32_t r0, uint32_t r1, uint32_t r2, uint32_t r3) {
  asm volatile("stmatrix.sync.aligned.m8n8.x4.trans.shared.b16 [%0], {%1, %2, %3, %4};"
               ::"r"(addr), "r"(r0), "r"(r1), "r"(r2), "r"(r3) : "memory");
}
DEVI void mma16816(float (&d)[4], const uint32_t (&a)[4], uint32_t b0, uint32_t b1) {
  asm volatile("mma.sync.aligned.m16n8k16.row.col.f32.bf16.bf16.f32 {%0, %1, %2, %3}, {%4, %5, %6, %7}, {%8, %9}, {%0, %1, %2, %3};"
               : "+f"(d[0]), "+f"(d[1]), "+f"(d[2]), "+f"(d[3])
               : "r"(a[0]), "r"(a[1]), "r"(a[2]), "r"(a[3]), "r"(b0), "r"(b1));
}
DEVI void mma16816_z(float (&d)[4], const uint32_t (&a)[4], uint32_t b0, uint32_t b1) {
  asm volatile("mma.sync.aligned.m16n8k16.row.col.f32.bf16.bf16.f32 {%0, %1, %2, %3}, {%4, %5, %6, %7}, {%8, %9}, {%10, %10, %10, %10};"
               : "=f"(d[0]), "=f"(d[1]), "=f"(d[2]), "=f"(d[3])
               : "r"(a[0]), "r"(a[1]), "r"(a[2]), "r"(a[3]), "r"(b0), "r"(b1), "f"(0.f));
}
DEVI void mma16816_c(float (&d)[4], const uint32_t (&a)[4], uint32_t b0, uint32_t b1, const float (&c)[4]) {
  asm volatile("mma.sync.aligned.m16n8k16.row.col.f32.bf16.bf16.f32 {%0, %1, %2, %3}, {%4, %5, %6, %7}, {%8, %9}, {%10, %11, %12, %13};"
               : "=f"(d[0]), "=f"(d[1]), "=f"(d[2]), "=f"(d[3])
               : "r"(a[0]), "r"(a[1]), "r"(a[2]), "r"(a[3]), "r"(b0), "r"(b1), "f"(c[0]), "f"(c[1]), "f"(c[2]), "f"(c[3]));
}
template <int BIT>
DEVI void sel2(uint32_t mask, float& r0, float& r1, float a0, float a1, float b0, float b1) {
  asm("{\n.reg .pred p;\n.reg .b32 t;\nand.b32 t, %2, %7;\nsetp.ne.b32 p, t, 0;\nselp.f32 %0, %3, %5, p;\nselp.f32 %1, %4, %6, p;\n}"
      : "=f"(r0), "=f"(r1) : "r"(mask), "f"(a0), "f"(a1), "f"(b0), "f"(b1), "n"(BIT));
}
template <int BIT>
DEVI void split2(uint32_t mask, uint32_t& r0, uint32_t& r1, uint32_t v) {
  asm("{\n.reg .pred p;\n.reg .b32 t;\nand.b32 t, %2, %4;\nsetp.ne.b32 p, t, 0;\nselp.b32 %0, %3, 0, p;\nselp.b32 %1, 0, %3, p;\n}"
      : "=r"(r0), "=r"(r1) : "r"(mask), "r"(v), "n"(BIT));
}
DEVI void stg32_if(uint32_t* p, uint32_t v, bool on) {
  asm volatile("{\n.reg .pred q;\nsetp.ne.u32 q, %2, 0;\n@q st.global.u32 [%0], %1;\n}" ::"l"(p), "r"(v), "r"((uint32_t)on) : "memory");
}
DEVI uint4 ldg128(const void* p) {
  uint4 v;
  asm volatile("ld.global.nc.v4.u32 {%0, %1, %2, %3}, [%4];" : "=r"(v.x), "=r"(v.y), "=r"(v.z), "=r"(v.w) : "l"(p));
  return v;
}
DEVI uint32_t ld_acquire(const uint32_t* p) {
  uint32_t v;
  asm volatile("ld.acquire.gpu.global.u32 %0, [%1];" : "=r"(v) : "l"(p) : "memory");
  return v;
}
DEVI uint32_t ld_relaxed(const uint32_t* p) {
  uint32_t v;
  asm volatile("ld.relaxed.gpu.global.u32 %0, [%1];" : "=r"(v) : "l"(p) : "memory");
  return v;
}
DEVI void st_relaxed(uint32_t* p, uint32_t v) {
  asm volatile("st.relaxed.gpu.global.u32 [%0], %1;" ::"l"(p), "r"(v) : "memory");
}
DEVI void red_max_release(uint32_t* p, uint32_t v) {
  asm volatile("red.release.gpu.global.max.u32 [%0], %1;" ::"l"(p), "r"(v) : "memory");
}
DEVI void red_max(uint32_t* p, uint32_t v) {
  asm volatile("red.relaxed.gpu.global.max.u32 [%0], %1;" ::"l"(p), "r"(v) : "memory");
}
DEVI void red_add1(uint32_t* p) {
  asm volatile("red.relaxed.gpu.global.add.u32 [%0], 1;" ::"l"(p) : "memory");
}
DEVI bool named_bar_or(int id, int n, bool v) {
  uint32_t r;
  asm volatile("{\n.reg .pred p, q;\nsetp.ne.u32 p, %1, 0;\nbar.red.or.pred q, %2, %3, p;\nselp.u32 %0, 1, 0, q;\n}"
               : "=r"(r) : "r"((uint32_t)v), "r"(id), "r"(n) : "memory");
  return r != 0;
}
DEVI uint4 lds128(uint32_t addr) {
  uint4 v;
  asm volatile("ld.shared.v4.u32 {%0, %1, %2, %3}, [%4];" : "=r"(v.x), "=r"(v.y), "=r"(v.z), "=r"(v.w) : "r"(addr) : "memory");
  return v;
}
DEVI void fence_gpu() { asm volatile("fence.acq_rel.gpu;" ::: "memory"); }
DEVI uint32_t lds32(uint32_t addr) {
  uint32_t v;
  asm volatile("ld.shared.u32 %0, [%1];" : "=r"(v) : "r"(addr) : "memory");
  return v;
}
DEVI uint32_t atom_inc_shared(uint32_t addr) {
  uint32_t v;
  asm volatile("atom.shared.add.u32 %0, [%1], 1;" : "=r"(v) : "r"(addr) : "memory");
  return v;
}
DEVI void sts32(uint32_t addr, uint32_t v) {
  asm volatile("st.shared.u32 [%0], %1;" ::"r"(addr), "r"(v) : "memory");
}
DEVI void sts128(uint32_t addr, uint4 v) {
  asm volatile("st.shared.v4.u32 [%0], {%1, %2, %3, %4};" ::"r"(addr), "r"(v.x), "r"(v.y), "r"(v.z), "r"(v.w) : "memory");
}
DEVI void named_bar_arrive(int id, int n) { asm volatile("bar.arrive %0, %1;" ::"r"(id), "r"(n) : "memory"); }
DEVI void named_bar_sync(int id, int n) { asm volatile("bar.sync %0, %1;" ::"r"(id), "r"(n) : "memory"); }
DEVI void fence_proxy_async() { asm volatile("fence.proxy.async.shared::cta;" ::: "memory"); }
DEVI void fence_proxy_async_global() { asm volatile("fence.proxy.async.global;" ::: "memory"); }
DEVI int clampi(int v, int lo, int hi) { return v < lo ? lo : (v > hi ? hi : v); }

template <int TA, int TB> DEVI void wgmma_m64n144k16_ss(float (&d)[72], uint64_t descA, uint64_t descB, int scaleD) {
  asm volatile("{\n.reg .pred p;\nsetp.ne.b32 p, %74, 0;\nwgmma.mma_async.sync.aligned.m64n144k16.f32.bf16.bf16 {%0, %1, %2, %3, %4, %5, %6, %7, %8, %9, %10, %11, %12, %13, %14, %15, %16, %17, %18, %19, %20, %21, %22, %23, %24, %25, %26, %27, %28, %29, %30, %31, %32, %33, %34, %35, %36, %37, %38, %39, %40, %41, %42, %43, %44, %45, %46, %47, %48, %49, %50, %51, %52, %53, %54, %55, %56, %57, %58, %59, %60, %61, %62, %63, %64, %65, %66, %67, %68, %69, %70, %71}, %72, %73, p, 1, 1, %75, %76;\n}\n"
    : "+f"(d[0]), "+f"(d[1]), "+f"(d[2]), "+f"(d[3]), "+f"(d[4]), "+f"(d[5]), "+f"(d[6]), "+f"(d[7]), "+f"(d[8]), "+f"(d[9]), "+f"(d[10]), "+f"(d[11]), "+f"(d[12]), "+f"(d[13]), "+f"(d[14]), "+f"(d[15]), "+f"(d[16]), "+f"(d[17]), "+f"(d[18]), "+f"(d[19]), "+f"(d[20]), "+f"(d[21]), "+f"(d[22]), "+f"(d[23]), "+f"(d[24]), "+f"(d[25]), "+f"(d[26]), "+f"(d[27]), "+f"(d[28]), "+f"(d[29]), "+f"(d[30]), "+f"(d[31]), "+f"(d[32]), "+f"(d[33]), "+f"(d[34]), "+f"(d[35]), "+f"(d[36]), "+f"(d[37]), "+f"(d[38]), "+f"(d[39]), "+f"(d[40]), "+f"(d[41]), "+f"(d[42]), "+f"(d[43]), "+f"(d[44]), "+f"(d[45]), "+f"(d[46]), "+f"(d[47]), "+f"(d[48]), "+f"(d[49]), "+f"(d[50]), "+f"(d[51]), "+f"(d[52]), "+f"(d[53]), "+f"(d[54]), "+f"(d[55]), "+f"(d[56]), "+f"(d[57]), "+f"(d[58]), "+f"(d[59]), "+f"(d[60]), "+f"(d[61]), "+f"(d[62]), "+f"(d[63]), "+f"(d[64]), "+f"(d[65]), "+f"(d[66]), "+f"(d[67]), "+f"(d[68]), "+f"(d[69]), "+f"(d[70]), "+f"(d[71])
    : "l"(descA), "l"(descB), "r"(scaleD), "n"(TA), "n"(TB));
}

template <int TB> DEVI void wgmma_m64n64k16_rs(float (&d)[32], uint32_t a0, uint32_t a1, uint32_t a2, uint32_t a3, uint64_t descB, int scaleD) {
  asm volatile("{\n.reg .pred p;\nsetp.ne.b32 p, %37, 0;\nwgmma.mma_async.sync.aligned.m64n64k16.f32.bf16.bf16 {%0, %1, %2, %3, %4, %5, %6, %7, %8, %9, %10, %11, %12, %13, %14, %15, %16, %17, %18, %19, %20, %21, %22, %23, %24, %25, %26, %27, %28, %29, %30, %31}, {%32, %33, %34, %35}, %36, p, 1, 1, %38;\n}\n"
    : "+f"(d[0]), "+f"(d[1]), "+f"(d[2]), "+f"(d[3]), "+f"(d[4]), "+f"(d[5]), "+f"(d[6]), "+f"(d[7]), "+f"(d[8]), "+f"(d[9]), "+f"(d[10]), "+f"(d[11]), "+f"(d[12]), "+f"(d[13]), "+f"(d[14]), "+f"(d[15]), "+f"(d[16]), "+f"(d[17]), "+f"(d[18]), "+f"(d[19]), "+f"(d[20]), "+f"(d[21]), "+f"(d[22]), "+f"(d[23]), "+f"(d[24]), "+f"(d[25]), "+f"(d[26]), "+f"(d[27]), "+f"(d[28]), "+f"(d[29]), "+f"(d[30]), "+f"(d[31])
    : "r"(a0), "r"(a1), "r"(a2), "r"(a3), "l"(descB), "r"(scaleD), "n"(TB));
}

template <int TA, int TB> DEVI void wgmma_m64n96k16_ss(float (&d)[48], uint64_t descA, uint64_t descB, int scaleD) {
  asm volatile("{\n.reg .pred p;\nsetp.ne.b32 p, %50, 0;\nwgmma.mma_async.sync.aligned.m64n96k16.f32.bf16.bf16 {%0, %1, %2, %3, %4, %5, %6, %7, %8, %9, %10, %11, %12, %13, %14, %15, %16, %17, %18, %19, %20, %21, %22, %23, %24, %25, %26, %27, %28, %29, %30, %31, %32, %33, %34, %35, %36, %37, %38, %39, %40, %41, %42, %43, %44, %45, %46, %47}, %48, %49, p, 1, 1, %51, %52;\n}\n"
    : "+f"(d[0]), "+f"(d[1]), "+f"(d[2]), "+f"(d[3]), "+f"(d[4]), "+f"(d[5]), "+f"(d[6]), "+f"(d[7]), "+f"(d[8]), "+f"(d[9]), "+f"(d[10]), "+f"(d[11]), "+f"(d[12]), "+f"(d[13]), "+f"(d[14]), "+f"(d[15]), "+f"(d[16]), "+f"(d[17]), "+f"(d[18]), "+f"(d[19]), "+f"(d[20]), "+f"(d[21]), "+f"(d[22]), "+f"(d[23]), "+f"(d[24]), "+f"(d[25]), "+f"(d[26]), "+f"(d[27]), "+f"(d[28]), "+f"(d[29]), "+f"(d[30]), "+f"(d[31]), "+f"(d[32]), "+f"(d[33]), "+f"(d[34]), "+f"(d[35]), "+f"(d[36]), "+f"(d[37]), "+f"(d[38]), "+f"(d[39]), "+f"(d[40]), "+f"(d[41]), "+f"(d[42]), "+f"(d[43]), "+f"(d[44]), "+f"(d[45]), "+f"(d[46]), "+f"(d[47])
    : "l"(descA), "l"(descB), "r"(scaleD), "n"(TA), "n"(TB));
}

template <int TA, int TB> DEVI void wgmma_m64n48k16_ss(float (&d)[24], uint64_t descA, uint64_t descB, int scaleD) {
  asm volatile("{\n.reg .pred p;\nsetp.ne.b32 p, %26, 0;\nwgmma.mma_async.sync.aligned.m64n48k16.f32.bf16.bf16 {%0, %1, %2, %3, %4, %5, %6, %7, %8, %9, %10, %11, %12, %13, %14, %15, %16, %17, %18, %19, %20, %21, %22, %23}, %24, %25, p, 1, 1, %27, %28;\n}\n"
    : "+f"(d[0]), "+f"(d[1]), "+f"(d[2]), "+f"(d[3]), "+f"(d[4]), "+f"(d[5]), "+f"(d[6]), "+f"(d[7]), "+f"(d[8]), "+f"(d[9]), "+f"(d[10]), "+f"(d[11]), "+f"(d[12]), "+f"(d[13]), "+f"(d[14]), "+f"(d[15]), "+f"(d[16]), "+f"(d[17]), "+f"(d[18]), "+f"(d[19]), "+f"(d[20]), "+f"(d[21]), "+f"(d[22]), "+f"(d[23])
    : "l"(descA), "l"(descB), "r"(scaleD), "n"(TA), "n"(TB));
}

constexpr int kS = 112;
constexpr int kStripCtas = 112;
constexpr int kProjCtas = 20;
constexpr int kThreads = 512;
constexpr int kArr = 29;
constexpr int kExch = 27;
constexpr int kSteps = 28;
constexpr int kTiles = kSteps * 28;
constexpr int kOTileBytes = 64 * 192 * 2;
constexpr int kTailBands = 7;
constexpr int kTail0 = kSteps - kTailBands;
constexpr int kFast0 = kSteps - 3;
static_assert(kFast0 >= 25 && kFast0 <= kSteps, "filler ordering");
constexpr int kProjTiles = kTail0 * 28;
constexpr int kHaloBytes = 3 * 784 - 16, kHaloPitch = 2432;

__device__ __align__(1024) uint8_t g_o[(size_t)kTiles * kOTileBytes];
constexpr int kHaloRing = 10;
constexpr int kHaloBlock = (2 * kHaloRing + 1) * kHaloPitch;
__device__ __align__(1024) uint8_t g_halo[(size_t)kStripCtas * kHaloBlock];
__device__ __align__(1024) uint8_t g_wop[4 * 3 * 192 * 32];
__device__ uint32_t g_oflag[28 * 32];
__device__ uint32_t g_wflag[5 * 32];
__device__ uint32_t g_epoch[kProjCtas * 32];

DEVI uint32_t* halo_flags(int cta) {
  return reinterpret_cast<uint32_t*>(g_halo + (size_t)cta * kHaloBlock + 2 * kHaloRing * kHaloPitch);
}
DEVI const uint8_t* o_tile(int g, int ps) { return g_o + (size_t)(ps * kSteps + g) * kOTileBytes; }

DEVI int cta_role() {
  const int b = blockIdx.x, s = b >> 1, pat = s / 7, o = s - 7 * pat;
  return (o == 6 || s == 65) ? kStripCtas + 2 * pat + (b & 1) : 12 * pat + 2 * o + (b & 1);
}

namespace ka {
constexpr int kWAtom = 192 * 32;
constexpr int kWBytes = 9 * kWAtom;
constexpr int kXBytes = 64 * 384;
constexpr int kCol = 784;
constexpr int kQCol = 400;
constexpr int kSlot = 22 * kCol;
constexpr int kQSlot = 16 * kQCol;
constexpr int kQOff = 5 * kSlot + 32;
constexpr int kOffX = kWBytes;
constexpr int kOffRing = kOffX + 2 * kXBytes;
constexpr int kOffBar = kOffRing + kQOff + 6 * kQSlot;
constexpr int kOffStage = kOffX, kOffWo = kOffX + 2 * kWAtom;
constexpr int kOffDummy = kOffBar + 896;
DEVI uint32_t stage_buf(int i) { return i == 0 ? kOffStage : ((kOffRing + kQOff + 511) & ~511) + (i - 1) * 2 * kWAtom; }
DEVI uint32_t tail_buf(int i) { return i < 2 ? i * kOTileBytes : kOffRing + (i - 2) * 2 * kSlot; }
constexpr int kLastBytes = 3 * (16 + 2 * 15) * 128;
constexpr int kBarX = 0, kBarFull = 256, kBarO = 512, kBarT = 768, kBarU = 800, kBarOwn = 832, kBarJunk = 896;
constexpr int kSmemBytes = kOffBar + 896 + 704;
constexpr int kD = 6;
static_assert(kTailBands == 7, "one shared step + three per head pair; buffer reuse");
constexpr int kNbInit = 0, kNbMisc = 1, kNbBurst = 2, kNbTile = 7, kNbFirst = 13, kNbX = 14;
}

namespace kb {
constexpr int kWoBlk = 192 * 128;
constexpr int kStages = 6;
constexpr int kOffA = 3 * kWoBlk;
constexpr int kOffBar = kOffA + kStages * kOTileBytes;
constexpr int kSmemBytes = kOffBar + 192;
}

constexpr int kSmemBytes = ka::kSmemBytes > kb::kSmemBytes ? ka::kSmemBytes : kb::kSmemBytes;
static_assert(kSmemBytes <= 232448, "smem");

DEVI void mbar_wait_sleep(uint32_t bar, uint32_t parity) {
  uint32_t it = 0;
  while (!mbar_test_wait(bar, parity)) {
    __nanosleep(200);
    if (++it > LIMIT) { __trap(); break; }
  }
}

DEVI void publish_fence() {
  fence_proxy_async_global();
  fence_gpu();
}

DEVI uint32_t sched_fence() {
  uint32_t t;
  asm volatile("mov.u32 %0, %clock;" : "=r"(t)::"memory");
  return t;
}

struct AttnState {
  uint32_t kf[5][3][4];
  uint32_t vf[5][3][4];
  float bias[5][4];
  uint32_t p[5][2];
  uint32_t kaddr, vaddr, qaddr, bar, junk, fence;
  uint32_t ones[4];
  bool rdy;
  uint32_t pm;
  uint32_t* optr;
};

DEVI void store_o(AttnState& s, float (&o)[3][4], float i0, float i1, bool on) {
#pragma unroll
  for (int mt = 0; mt < 3; mt++) {
    stg32_if(s.optr + (2 * mt) * 32, pack_bf16(o[mt][0] * i0, o[mt][1] * i1), on);
    stg32_if(s.optr + (2 * mt + 1) * 32, pack_bf16(o[mt][2] * i0, o[mt][3] * i1), on);
  }
  s.optr += kOTileBytes / 4;
}

template <int PH>
DEVI void attn_step(AttnState& s, int g, int warp, const __nv_bfloat16* __restrict__ rpb) {
  using namespace ka;
  constexpr int R = (2 * PH) % 5, N0 = (R + 3) % 5, N1 = (R + 4) % 5;
  constexpr int SL = ((PH + 1) % 5) * kSlot;
  if (PH == 0 && g == 0) {
    {
      const int lane = threadIdx.x & 31, me = cta_role(), qc0 = 16 * ((me >> 2) % 7) + 2 * warp;
      const int kc = clampi(qc0 - 3, 0, kS - 8) + (lane >> 2);
      const unsigned short* r = reinterpret_cast<const unsigned short*>(rpb) + (me & 3) * 169 + (3 - (lane & 3)) * 13 + kc - qc0 + 6;
      const int sw0 = clampi(qc0 - 3, 0, kS - 7), sw1 = clampi(qc0 - 2, 0, kS - 7);
      const bool ok0 = kc >= sw0 && kc < sw0 + 7, ok1 = kc >= sw1 && kc < sw1 + 7;
#pragma unroll
      for (int i = 0; i < 10; i++) {
        const uint32_t v0 = ok0 ? (uint32_t)__ldg(r + i * 13) : 0xFF80u;
        const uint32_t v1 = ok1 ? (uint32_t)__ldg(r + i * 13 - 1) : 0xFF80u;
        s.bias[i >> 1][2 * (i & 1)] = __uint_as_float(v0 << 16) * 6.928203230275509f;
        s.bias[i >> 1][2 * (i & 1) + 1] = __uint_as_float(v1 << 16) * 6.928203230275509f;
      }
    }
    named_bar_sync(kNbMisc, 384);
    mbar_wait(s.bar + kBarFull, 0);
#pragma unroll
    for (int k = 0; k < 3; k++) {
      ldmatrix_x4(s.kf[1][k], s.kaddr + k * 32);
      ldmatrix_x4(s.kf[2][k], s.kaddr + 384 + k * 32);
      ldmatrix_x4_t(s.vf[1][k], s.vaddr + k * 32);
      ldmatrix_x4_t(s.vf[2][k], s.vaddr + 384 + k * 32);
      s.vf[0][k][0] = s.vf[0][k][1] = s.vf[0][k][2] = s.vf[0][k][3] = 0u;
    }
    named_bar_arrive(kNbFirst, 384);
    s.rdy = false;
    s.pm = (s.pm << 8) | (s.pm & 64);
  }
  if (!s.rdy) {
    mbar_wait(s.bar + kBarFull + 8 * (g + 1), 0);
    if (PH == 1 && g == 1) s.pm >>= 8;
    if (PH == 2 && g == kSteps - 1) s.pm |= 0x3Fu;
  }
  float t[5][4], o[3][4], z[4];
  uint32_t q[6];
  ldmatrix_x4(q[0], q[1], q[2], q[3], s.qaddr);
  ldmatrix_x2(q[4], q[5], s.qaddr + 64);
#define LDK(ks) { ldmatrix_x4(s.kf[N0][ks], s.kaddr + SL + (ks) * 32); ldmatrix_x4(s.kf[N1][ks], s.kaddr + SL + 384 + (ks) * 32); }
#define LDV(n) ldmatrix_x4_t(s.vf[(n) < 3 ? N0 : N1][(n) % 3], s.vaddr + SL + ((n) / 3) * 384 + ((n) % 3) * 32);
#define PV(i) { _Pragma("unroll") for (int mt = 0; mt < 3; mt++) { \
                  if ((i) == 0) mma16816_z(o[mt], s.vf[N0][mt], s.p[0][0], s.p[0][1]); \
                  else mma16816(o[mt], s.vf[(R + 3 + (i)) % 5][mt], s.p[i][0], s.p[i][1]); } \
                if ((i) == 0) mma16816_z(z, s.ones, s.p[0][0] | s.p[4][0], s.p[0][1] | s.p[4][1]); \
                else if ((i) < 4) mma16816(z, s.ones, s.p[i][0], s.p[i][1]); }
#define QK(ks) { _Pragma("unroll") for (int i = 0; i < 5; i++) { \
                   if ((ks) == 0) mma16816_c(t[i], s.kf[(R + i) % 5][0], q[0], q[1], s.bias[i]); \
                   else mma16816(t[i], s.kf[(R + i) % 5][ks], q[2 * (ks)], q[2 * (ks) + 1]); } }
#define FN(x) x = sched_fence();
  uint32_t f0 = 0, f1;
  if (PH == 1) {
    LDK(0) LDK(1) LDK(2) PV(0) PV(1) PV(2) PV(3) PV(4) FN(f1)
    LDV(5) LDV(4) LDV(3) LDV(2) LDV(1) LDV(0) QK(0) QK(1) FN(f0) QK(2)
  } else if (PH == 2) {
    LDK(0) LDK(1) LDK(2) PV(0) PV(1) PV(2) FN(f1)
    LDV(5) LDV(4) LDV(3) PV(3) PV(4) FN(f0) LDV(2) LDV(1) LDV(0) QK(0) QK(1) QK(2)
  } else {
    LDK(0) LDK(1) LDK(2) PV(0) PV(1) PV(2) PV(3) PV(4) FN(f1)
    LDV(5) LDV(4) LDV(3) LDV(2) LDV(1) LDV(0) QK(0) QK(1) QK(2)
  }
#undef LDK
#undef LDV
#undef PV
#undef QK
#undef FN
  const uint32_t f2 = sched_fence();
  named_bar_arrive(kNbBurst + (PH + kD) % 5, 384);
  const uint32_t fo = s.fence;
  s.fence = sched_fence();
  const uint32_t pm = s.pm;
  float x[7][2];
  sel2<1>(pm, x[0][0], x[0][1], t[0][0], t[0][1], t[3][2], t[3][3]);
  sel2<2>(pm, x[1][0], x[1][1], t[0][2], t[0][3], t[4][0], t[4][1]);
  sel2<4>(pm, x[2][0], x[2][1], t[1][0], t[1][1], t[4][2], t[4][3]);
#pragma unroll
  for (int e = 0; e < 2; e++) {
    x[3][e] = t[1][2 + e]; x[4][e] = t[2][e]; x[5][e] = t[2][2 + e]; x[6][e] = t[3][e];
  }
  float m0 = fmaxf(fmaxf(fmaxf(x[0][0], x[1][0]), fmaxf(x[2][0], x[3][0])), fmaxf(fmaxf(x[4][0], x[5][0]), x[6][0]));
  float m1 = fmaxf(fmaxf(fmaxf(x[0][1], x[1][1]), fmaxf(x[2][1], x[3][1])), fmaxf(fmaxf(x[4][1], x[5][1]), x[6][1]));
#pragma unroll
  for (int d = 4; d <= 16; d <<= 1) {
    m0 = fmaxf(m0, __shfl_xor_sync(0xffffffffu, m0, d));
    m1 = fmaxf(m1, __shfl_xor_sync(0xffffffffu, m1, d));
  }
  {
    int nx = kBarFull + 8 * (g + 2);
    if (PH >= 3 && g < 0) nx = kBarOwn + 8 * warp;
    if ((PH == 0 && g == 0) || (PH == 1 && g == kSteps - 2)) nx = kBarFull + 8 * 31;
    s.rdy = mbar_test_wait(s.bar + nx, 0);
  }
  const float c = 0.14433756729740643f * 1.4426950408889634f;
  const float n0 = -m0 * c, n1 = -m1 * c;
  uint32_t pt[7];
#pragma unroll
  for (int i = 0; i < 7; i++) {
    const float e0 = ex2(fmaf(x[i][0], c, n0)), e1 = ex2(fmaf(x[i][1], c, n1));
    pt[i] = movmatrix_t(pack_bf16(e0, e1));
  }
  split2<8>(pm, s.p[0][0], s.p[3][1], pt[0]);
  split2<16>(pm, s.p[0][1], s.p[4][0], pt[1]);
  split2<32>(pm, s.p[1][0], s.p[4][1], pt[2]);
  s.p[1][1] = pt[3]; s.p[2][0] = pt[4]; s.p[2][1] = pt[5]; s.p[3][0] = pt[6];
#pragma unroll
  for (int i = 0; i < 5; i++) asm volatile("" : "+r"(s.p[i][0]), "+r"(s.p[i][1])::"memory");
  const bool real = PH == 1 || PH == 2 || g > 0;
  store_o(s, o, rcp_approx(z[0]), rcp_approx(z[1]), real);
  __syncwarp();
  if ((s.pm & 64) && real) mbar_arrive(s.bar + kBarO + 8 * (g - 1));
  s.junk ^= fo ^ f0 ^ f1 ^ f2;
  s.qaddr += kQSlot;
  if (s.qaddr >= s.bar) s.qaddr -= 6 * kQSlot;
  asm volatile("" : "+r"(s.junk)::"memory");
}

__global__ void __launch_bounds__(kThreads, 1)
nat_kernel(const __nv_bfloat16* __restrict__ wqkv, const __nv_bfloat16* __restrict__ rpb,
           const __grid_constant__ CUtensorMap tm_x, const __grid_constant__ CUtensorMap tm_w,
           const __grid_constant__ CUtensorMap tm_h, const __grid_constant__ CUtensorMap tm_r,
           const __grid_constant__ CUtensorMap tm_wo, const __grid_constant__ CUtensorMap tm_out,
           const __grid_constant__ CUtensorMap tm_wo2, const __grid_constant__ CUtensorMap tm_o2,
           const __grid_constant__ CUtensorMap tm_o3) {
  extern __shared__ __align__(1024) uint8_t smem_raw[];
  const uint32_t sbase = smem_u32(smem_raw);
  if (sbase & 1023u) __trap();
  const int warp = __shfl_sync(0xffffffffu, (int)(threadIdx.x >> 5), 0), lane = threadIdx.x & 31;
  const int wg = warp >> 2, wl = warp & 3;
  const int cta = cta_role();
  const bool strip_cta = cta < kStripCtas;
  const int head = cta & 3, ps = cta >> 2, par = ps / 7, strip = ps - 7 * par;

  if (threadIdx.x == 416) prefetch_map(strip_cta ? &tm_w : &tm_wo2);
  const int wodd = head == 1 ? 0 : (head == 2 ? 2 : -1);
  if (strip_cta && threadIdx.x == 384) {
    using namespace ka;
    const uint32_t bar = sbase + kOffBar;
    mbar_init(bar + kBarX, 1);
    mbar_expect_tx(bar + kBarX, kXBytes + (wodd >= 0 ? 7 : 6) * kWAtom);
    tma_load_5d(sbase + kOffX, &tm_x, bar + kBarX, 0, 16 * strip, -1, 3 * (par & 1), par >> 1);
#pragma unroll
    for (int i = 3; i < 9; i++)
      tma_load_2d(sbase + i * kWAtom, &tm_w, bar + kBarX, (i / 3) * 192 + head * 48 + (i % 3) * 16, 0);
    if (wodd >= 0) tma_load_2d(sbase + wodd * kWAtom, &tm_w, bar + kBarX, head * 48 + wodd * 16, 0);
  }
  __syncwarp();
  if (strip_cta && wg == 2 && threadIdx.x < 256 + 96) {
    using namespace ka;
    uint4 v[12];
    const int wk = ((int)threadIdx.x - 256) / 6, wu = (int)threadIdx.x - 256 - 6 * wk;
    const uint8_t* src = reinterpret_cast<const uint8_t*>(wqkv) + wk * 1152 + head * 96 + wu * 16;
#pragma unroll
    for (int i = 0; i < 12; i++)
      if ((wu >> 1) != wodd) v[i] = ldg128(src + i * 16 * 1152);
    const uint32_t dst = sbase + (wu >> 1) * kWAtom + wk * 32 + (((wu ^ (wk >> 2)) & 1) << 4);
#pragma unroll
    for (int i = 0; i < 12; i++)
      if ((wu >> 1) != wodd) sts128(dst + i * 16 * 32, v[i]);
    fence_proxy_async();
  }

  if (strip_cta) {
    using namespace ka;
    const uint32_t bar = sbase + kOffBar, ring = sbase + kOffRing;
    const int tskip = (head ^ (head >> 1)) & 1, thalf = head >> 1;
    if (wg < 2) {
      reg_inc<184>();
      AttnState s;
      const int qc0 = 16 * strip + 2 * warp;
      const int kc0 = clampi(qc0 - 3, 0, kS - 8);
      const uint32_t colb = ring + (kc0 - (16 * strip - 3) + (lane & 7)) * kCol;
      s.kaddr = colb + ((lane >> 3) & 1) * 192 + (lane >> 4) * 16;
      s.vaddr = colb + 96 + (lane >> 4) * 192 + ((lane >> 3) & 1) * 16;
      {
        const int qr = (lane & 7) >> 1;
        const uint32_t qa = ring + kQOff + (2 * warp + (lane & 1)) * kQCol + (lane >> 3) * 16;
        s.qaddr = qa + (qr == 3 ? 5 * kQSlot : 4 * kQSlot + (qr + 1) * 96);
      }
      s.bar = bar;
      s.optr = reinterpret_cast<uint32_t*>(g_o + (size_t)ps * kSteps * kOTileBytes + head * 6144 + warp * 768) + lane - 3 * kOTileBytes / 4;
#pragma unroll
      for (int i = 0; i < 5; i++) {
        s.p[i][0] = s.p[i][1] = 0u;
        s.bias[i][0] = s.bias[i][1] = s.bias[i][2] = s.bias[i][3] = 0.f;
#pragma unroll
        for (int k = 0; k < 3; k++)
#pragma unroll
          for (int c = 0; c < 4; c++) s.kf[i][k][c] = s.vf[i][k][c] = 0u;
      }
      s.junk = s.fence = 0;
      s.rdy = true;
      if (lane == 0) {
        mbar_init(bar + kBarOwn + 8 * warp, 1);
        mbar_arrive(bar + kBarOwn + 8 * warp);
      }
      __syncwarp();
#pragma unroll
      for (int i = 0; i < 4; i++) s.ones[i] = 0x3F803F80u;
      s.pm = (7u << (lane & 3) & 7u) | ((7u << (lane >> 3) & 7u) << 3) | (lane == 0 ? 64u : 0u);
      s.pm = __shfl_sync(0xffffffffu, s.pm, lane);
      s.kaddr = __shfl_sync(0xffffffffu, s.kaddr, lane);
      s.vaddr = __shfl_sync(0xffffffffu, s.vaddr, lane);
#pragma unroll 1
      for (int g = -2; g < kSteps; g += 5) {
        attn_step<3>(s, g, warp, rpb);
        attn_step<4>(s, g + 1, warp, rpb);
        attn_step<0>(s, g + 2, warp, rpb);
        attn_step<1>(s, g + 3, warp, rpb);
        attn_step<2>(s, g + 4, warp, rpb);
      }
      {
        float o[3][4], z[4];
#pragma unroll
        for (int mt = 0; mt < 3; mt++) mma16816_z(o[mt], s.vf[4][mt], s.p[0][0], s.p[0][1]);
        mma16816_z(z, s.ones, s.p[0][0], s.p[0][1]);
#pragma unroll
        for (int i = 1; i < 5; i++) {
#pragma unroll
          for (int mt = 0; mt < 3; mt++) mma16816(o[mt], s.vf[i - 1][mt], s.p[i][0], s.p[i][1]);
          mma16816(z, s.ones, s.p[i][0], s.p[i][1]);
        }
        store_o(s, o, rcp_approx(z[0]), rcp_approx(z[1]), true);
        __syncwarp();
        if (lane == 0) mbar_arrive(bar + kBarO + 8 * (kSteps - 1));
      }
      s.junk ^= s.fence;
      if (s.junk == 0x9e3779b9u) sts32(bar + kBarJunk, 0);
      if (wg == 1) {
#pragma unroll 1
        for (int g = kTail0 + 2 - tskip, i = 1; g < kSteps; g += 2, i++) {
          if (g < kFast0) continue;
          const uint32_t tb = sbase + tail_buf(i);
#pragma unroll 1
          for (uint32_t ph = 0;; ph++) {
            mbar_wait(bar + kBarU + 8 * i, ph & 1);
            bool bad = false;
#pragma unroll
            for (int u = 0; u < 12; u++) {
              const uint4 v = lds128(tb + (wl * 12 + u) * 512 + lane * 16);
              bad |= v.x == ~0u || v.y == ~0u || v.z == ~0u || v.w == ~0u;
            }
            if (!named_bar_or(kNbMisc, 128, bad)) break;
            if (threadIdx.x == 128) {
              fence_proxy_async();
              mbar_expect_tx(bar + kBarU + 8 * i, kOTileBytes);
              bulk_load(tb, o_tile(g, ps), kOTileBytes, bar + kBarU + 8 * i);
            }
            __syncwarp();
            if (ph > LIMIT) { __trap(); break; }
          }
          if (threadIdx.x == 128) mbar_arrive(bar + kBarT + 8 * i);
          __syncwarp();
        }
      }
      if (warp == 0) {
#pragma unroll 1
        for (int g = kTail0, i = 0; g < kSteps; g += i == 0 ? 2 - tskip : 2, i++) {
          named_bar_sync(kNbTile + i, 160);
          if (lane == 0) {
            if (i) tma_store_5d(&tm_o3, sbase + stage_buf(i), 0, 4 * g, 16 * strip, 6 * (par & 1) + 3 * thalf, par >> 1);
            else tma_store_5d(&tm_out, sbase + kOffStage, thalf * 96 + tskip * 48, 4 * g, 16 * strip, par & 1, par >> 1);
            bulk_commit();
          }
          __syncwarp();
        }
        if (lane == 0) bulk_wait<0>();
      }
    } else if (wg == 2) {
      reg_dec<104>();
      const int col = ((lane >> 3) & 1) * 8 + (lane & 7);
      uint32_t kva = ring + (3 + col) * kCol + wl * 192 + (lane >> 4) * 16;
      uint32_t qa = ring + kQOff + col * kQCol + wl * 96 + (lane >> 4) * 16;
      const uint32_t alo = (uint32_t)make_desc(sbase + kOffX, 16, 1024, 1), blo = (uint32_t)make_desc(sbase, kWAtom, 256, 3);
      constexpr uint32_t ahi = (1u << 30) | (1024 >> 4), bhi = (3u << 30) | (256 >> 4);
      uint32_t gj = 0, qprev = 0, qk[12];
#pragma unroll
      for (int j = 0; j < 12; j++) qk[j] = 0;
      int bid = kNbBurst, tid = kNbTile;
      named_bar_arrive(kNbBurst + (kD - 2) % 5, 384);
      named_bar_arrive(kNbBurst + (kD - 1) % 5, 384);
      named_bar_sync(kNbX, 160);
      mbar_wait(bar + kBarX, 0);
#pragma unroll 1
      for (int a = 0; a < kArr; a++) {
        float acc[72];
        const uint32_t al = alo + (a & 1) * (kXBytes >> 4);
        if (a >= kD) named_bar_sync(bid, 384);
        wg_fence();
#pragma unroll
        for (int k = 0; k < 12; k++)
          wgmma_m64n144k16_ss<0, 1>(acc, desc64(al + (((k >> 2) * 8192 + (k & 3) * 32) >> 4), ahi), desc64(blo + k * 32, bhi), k != 0);
        wg_commit();
        const uint32_t gjv = sched_fence();
        gj ^= gjv;
        if (a > 0) {
#pragma unroll
          for (int j = 0; j < 3; j++) stmatrix_x4(qprev + j * 32, qk[4 * j], qk[4 * j + 1], qk[4 * j + 2], qk[4 * j + 3]);
          __syncwarp();
          if (lane == 0 && a - 1 < kExch) mbar_arrive(bar + kBarFull + 8 * (a - 1));
        }
        bid = bid == kNbBurst + 4 ? kNbBurst : bid + 1;
        if (a == 0) named_bar_sync(kNbInit, 256);
        const bool xok = mbar_test_wait(bar + kBarX + 8 * (a + 1), 0);
        if (a == kArr - 1 && wl != 0) {
          const int r = col / 3, c = col - 3 * r;
          qa = sbase + kOffDummy + lane * 16;
          kva = col < 15 && wl < 3 ? ring + ((kExch + (r >> 2)) % 5) * kSlot + ((wl - 1) * 19 + c) * kCol + (r & 3) * 192 + (lane >> 4) * 16
                                   : qa;
        }
        wg_wait<0>();
        fence_regs(acc);
        named_bar_arrive(kNbX + (a & 1), 160);
        if (a == 5) named_bar_sync(kNbFirst, 384);
#pragma unroll
        for (int j = 3; j < 9; j++)
          stmatrix_x4(kva + (j - 3) * 32, pack_bf16(acc[8 * j + 0], acc[8 * j + 1]), pack_bf16(acc[8 * j + 2], acc[8 * j + 3]),
                      pack_bf16(acc[8 * j + 4], acc[8 * j + 5]), pack_bf16(acc[8 * j + 6], acc[8 * j + 7]));
#pragma unroll
        for (int j = 0; j < 12; j++) qk[j] = pack_bf16(acc[2 * j], acc[2 * j + 1]);
        qprev = qa;
        if (a < kExch) named_bar_arrive(tid, 160);
        tid = tid == kNbTile + 5 ? kNbTile : tid + 1;
        if (!xok && a + 1 < kArr) mbar_wait(bar + kBarX + 8 * (a + 1), 0);
        kva += kSlot;
        if (kva >= ring + 5 * kSlot) kva -= 5 * kSlot;
        qa += kQSlot;
        if (qa >= bar) qa -= 6 * kQSlot;
      }
#pragma unroll
      for (int j = 0; j < 3; j++) stmatrix_x4(qprev + j * 32, qk[4 * j], qk[4 * j + 1], qk[4 * j + 2], qk[4 * j + 3]);
      __syncwarp();
      if (lane < kArr - kExch) mbar_arrive(bar + kBarFull + 8 * (kExch + lane));
      if (gj == 0x9e3779b9u) sts32(bar + kBarJunk, 0);
#pragma unroll 1
      for (int g = kArr - kD; g < kSteps - 1; g++) {
        named_bar_arrive(bid, 384);
        bid = bid == kNbBurst + 4 ? kNbBurst : bid + 1;
      }
      {
        const uint32_t wlo = (uint32_t)make_desc(sbase + kOffWo, kWAtom, 256, 3);
        const int n = lane & 7, j = 2 * wl + ((lane >> 3) & 1);
        const uint32_t sta = sbase + ((2 * j + (n & 1)) * 4 + (n >> 1)) * 96 + (lane >> 4) * 16;
        const int spx = (2 * j + (n & 1)) * 4 + (n >> 1);
        const uint32_t stb = sbase + spx * 64, swz = (lane >> 4) ^ ((spx >> 1) & 3);
        mbar_wait(bar + kBarX + 8 * kArr, 0);
        named_bar_sync(bid, 384);
        mbar_wait(bar + kBarO + 8 * (kSteps - 1), 0);
        uint32_t pk[24];
        bool trdy;
        auto stage = [&](int i) {
#pragma unroll
          for (int jp = 0; jp < 6; jp++)
            stmatrix_x4(i ? stb + stage_buf(i) + (jp >> 1) * 4096 + (((2 * (jp & 1)) ^ swz) << 4) : sta + kOffStage + (jp % 3) * 32,
                        pk[4 * jp], pk[4 * jp + 1], pk[4 * jp + 2], pk[4 * jp + 3]);
          fence_proxy_async();
          named_bar_arrive(kNbTile + i, 160);
        };
        {
          float acc[24];
          mbar_wait(bar + kBarT, 0);
          const uint32_t tlo = (uint32_t)make_desc(sbase + tail_buf(0), 128, 768, 0), wq = wlo + tskip * 3 * (kWAtom >> 4);
          wg_fence();
#pragma unroll
          for (int k = 0; k < 12; k++)
            wgmma_m64n48k16_ss<1, 1>(acc, desc64(tlo + (((k / 3) * 6144 + (k % 3) * 256) >> 4), 768 >> 4), desc64(wq + k * 32, bhi), k != 0);
          wg_commit();
          trdy = mbar_test_wait(bar + kBarT + 8, 0);
          wg_wait<0>();
          fence_regs(acc);
#pragma unroll
          for (int j = 0; j < 12; j++) pk[j] = pk[12 + j] = pack_bf16(acc[2 * j], acc[2 * j + 1]);
        }
#pragma unroll 1
        for (int g = kTail0 + 2 - tskip, i = 1; g < kSteps; g += 2, i++) {
          float acc[48];
          const uint32_t tlo = (uint32_t)make_desc(sbase + tail_buf(i), 128, 768, 0);
          if (!trdy) mbar_wait(bar + kBarT + 8 * i, 0);
          wg_fence();
#pragma unroll
          for (int k = 0; k < 12; k++)
            wgmma_m64n96k16_ss<1, 1>(acc, desc64(tlo + (((k / 3) * 6144 + (k % 3) * 256) >> 4), 768 >> 4), desc64(wlo + k * 32, bhi), k != 0);
          wg_commit();
          stage(i - 1);
          trdy = mbar_test_wait(bar + kBarT + 8 * ((i + 1) & 3), 0);
          wg_wait<0>();
          fence_regs(acc);
#pragma unroll
          for (int j = 0; j < 24; j++) pk[j] = pack_bf16(acc[2 * j], acc[2 * j + 1]);
        }
        stage(3);
      }
    } else {
      reg_dec<40>();
      if (wl == 0) named_bar_arrive(kNbX, 160);
      if (lane == 0) {
        const uint32_t b0 = bar + 64 * wl;
        if (wl == 1 && head == 1) tma_prefetch_5d(&tm_x, 0, 16 * strip, 3, 3 * (par & 1), par >> 1);
#pragma unroll
        for (int i = 0; i < 64; i += 8) {
          if (i || wl) mbar_init(b0 + kBarX + i, 1);
          mbar_init(b0 + kBarFull + i, wl < 3 || i < 8 * (kExch - 24) ? 6 : 4);
          mbar_init(b0 + kBarO + i, 8);
          if (wl == 0) mbar_init(b0 + kBarT + i, 1);
        }
#pragma unroll
        for (int i = 0; i < 64; i += 8) {
          if (i || wl)
            mbar_expect_tx(b0 + kBarX + i, wl < 3 || i < 32 ? kXBytes : (i == 32 ? kLastBytes : 6 * kWAtom));
          if (wl == 0 && i < 32) mbar_expect_tx(bar + (i && kTail0 + i / 4 - tskip >= kFast0 ? kBarU : kBarT) + i, kOTileBytes);
        }
        fence_mbar_init();
        if (wl == 0) {
          tma_load_5d(sbase + kOffX + kXBytes, &tm_x, bar + kBarX + 8, 0, 16 * strip, 3, 3 * (par & 1), par >> 1);
          tma_prefetch_5d(&tm_x, 0, 16 * strip, 4 * (2 + ((head - 2) & 3)) - 1, 3 * (par & 1), par >> 1);
        }
      }
      __syncwarp();
      const uint32_t ep = ld_relaxed(halo_flags(cta) + 32 + wl) * 32u;
      named_bar_arrive(kNbMisc, 384);
      named_bar_sync(kNbInit, 256);
      if (wl == 0) {
#pragma unroll 1
        for (int a = 2; a < kArr - 1; a++) {
          named_bar_sync(kNbX + (a & 1), 160);
          if (lane == 0) {
            tma_load_5d(sbase + kOffX + (a & 1) * kXBytes, &tm_x, bar + kBarX + 8 * a, 0, 16 * strip, 4 * a - 1,
                        3 * (par & 1), par >> 1);
            if (a == 20) {
              prefetch_map(&tm_h);
              prefetch_map(&tm_r);
              prefetch_map(&tm_out);
              prefetch_map(&tm_o3);
            }
            const int ap = a + 4;
            if (ap < kArr && (ap & 3) == head) tma_prefetch_5d(&tm_x, 0, 16 * strip, 4 * ap - 1, 3 * (par & 1), par >> 1);
          }
          __syncwarp();
        }
        {
          const uint32_t want = lane < 4 ? ep + 1 : ((ep >> 5) + 1) * kProjCtas;
          uint32_t it = 0;
          while (!__all_sync(0xffffffffu, lane > 4 || (int)(ld_acquire(&g_wflag[lane * 32]) - want) >= 0))
            if (++it > LIMIT) { __trap(); break; }
        }
        named_bar_sync(kNbX, 160);
        if (lane < 9) {
          const int kb = lane / 3, w = lane - 3 * kb;
          tma_load_5d(sbase + kOffX + kb * 8192 + w * 2048, w == 0 ? &tm_r : &tm_h, bar + kBarX + 8 * (kArr - 1), 0,
                      16 * strip + (w == 0 ? 0 : (w == 1 ? -3 : 16)), w == 0 ? kS - 1 : 4 * kExch - 1, 3 * (par & 1) + kb, par >> 1);
        }
        const uint8_t* wsrc = g_wop + thalf * 6 * kWAtom;
        named_bar_sync(kNbX + 1, 160);
        if (lane == 0) bulk_load(sbase + kOffWo + 2 * kWAtom, wsrc + 2 * kWAtom, 4 * kWAtom, bar + kBarX + 8 * kArr);
        uint32_t seen = ld_acquire(&g_oflag[ps * 32 + (lane & 3)]);
        named_bar_sync(kNbX, 160);
        if (lane == 0) bulk_load(sbase + kOffWo, wsrc, 2 * kWAtom, bar + kBarX + 8 * kArr);
#pragma unroll 1
        for (int g = kTail0, i = 0; g < kSteps; g += i == 0 ? 2 - tskip : 2, i++) {
          uint32_t it = 0;
          while (!__all_sync(0xffffffffu, (int)(seen - (ep + g + 1)) >= 0)) {
            seen = ld_acquire(&g_oflag[ps * 32 + (g < kFast0 ? 0 : 4) + (lane & 3)]);
            if (++it > LIMIT) { __trap(); break; }
          }
          if (g >= kFast0) mbar_wait(bar + kBarO + 8 * g, 0);
          if (lane == 0)
            bulk_load(sbase + tail_buf(i), o_tile(g, ps), kOTileBytes, bar + (g < kFast0 ? kBarT : kBarU) + 8 * i);
          __syncwarp();
        }
      } else {
        const int p = wl - 1;
        const bool on = lane == 0 ? strip > 0 : strip < 6;
        const int nb = on ? cta + (lane == 0 ? -4 : 4) : cta;
        const uint32_t bytes = (strip > 0 && strip < 6) ? 2 * kHaloBytes : kHaloBytes;
        int slot = p, g = 0;
#pragma unroll 1
        for (int a = p; a < kExch; a += 3) {
          named_bar_sync(kNbTile + a % 6, 160);
          const uint32_t sl = ring + slot * kSlot;
          if (lane < 2) {
            fence_proxy_async();
            if (on) bulk_store(g_halo + (size_t)cta * kHaloBlock + (lane * kHaloRing + a % kHaloRing) * kHaloPitch, sl + (3 + 13 * lane) * kCol, kHaloBytes);
            bulk_commit();
          }
          __syncwarp();
          g += __ffs(~__ballot_sync(0xffffffffu, lane < 4 && mbar_test_wait(bar + kBarO + 8 * (g + lane), 0))) - 1;
          __syncwarp();
          if (lane < 2) {
            bulk_wait<0>();
            if (lane == 0) mbar_expect_tx(bar + kBarFull + 8 * a, bytes);
            else mbar_arrive(bar + kBarFull + 8 * a);
            fence_proxy_async_global();
          }
          __syncwarp();
          if (lane < 3) red_max_release(lane < 2 ? halo_flags(cta) + 4 * lane + p : &g_oflag[ps * 32 + head], lane < 2 ? ep + a + 1 : ep + g);
          __syncwarp();
          {
            const uint32_t* fl = halo_flags(nb) + 4 * ((lane & 1) ^ 1) + p;
            uint32_t it = 0;
            while (!__all_sync(0xffffffffu, !(lane < 2 && on) || (int)(ld_acquire(fl) - (ep + a + 1)) >= 0))
              if (++it > LIMIT) { __trap(); break; }
          }
          if (lane < 2 && on)
            bulk_load(sl + lane * 19 * kCol, g_halo + (size_t)nb * kHaloBlock + ((lane ^ 1) * kHaloRing + a % kHaloRing) * kHaloPitch,
                      kHaloBytes, bar + kBarFull + 8 * a);
          __syncwarp();
          slot = slot >= 2 ? slot - 2 : slot + 3;
        }
        if (lane == 0) {
#pragma unroll 1
          for (g = kSteps - 7 + p; g < kSteps; g += 3) {
            if (g < kSteps - 3) mbar_wait_sleep(bar + kBarO + 8 * g, 0);
            else mbar_wait(bar + kBarO + 8 * g, 0);
            if (g < kFast0) {
              fence_proxy_async_global();
              red_max_release(&g_oflag[ps * 32 + head], ep + g + 1);
            } else {
              red_max(&g_oflag[ps * 32 + 4 + head], ep + g + 1);
            }
          }
        }
      }
      __syncwarp();
      if (lane == 0) st_relaxed(halo_flags(cta) + 32 + wl, (ep >> 5) + 1);
    }
  } else {
    using namespace kb;
    const uint32_t bar = sbase + kOffBar, sA = sbase + kOffA;
    const int k = cta - kStripCtas;
    if (wg < 3) {
      named_bar_sync(0, 512);
      uint32_t wf[12][4];
      mbar_wait(bar + 56, 0);
#pragma unroll 1
      for (int f = k; f < 28 * (kSteps - kFast0); f += kProjCtas) {
        uint4* d = reinterpret_cast<uint4*>(const_cast<uint8_t*>(o_tile(kFast0 + f / 28, f % 28))) + threadIdx.x;
#pragma unroll
        for (int i = 0; i < 4; i++) d[i * 384] = make_uint4(~0u, ~0u, ~0u, ~0u);
      }
      named_bar_sync(1, 384);
      if (threadIdx.x == 0) {
        publish_fence();
        red_add1(&g_wflag[4 * 32]);
      }
      __syncwarp();
      {
        const int kr = (lane & 7) + ((lane >> 4) << 3);
        const uint32_t wa = sbase + wg * kWoBlk + kr * 128 + (((2 * wl + ((lane >> 3) & 1)) ^ (lane & 7)) << 4);
#pragma unroll
        for (int kk = 0; kk < 12; kk++) ldmatrix_x4_t(wf[kk], wa + kk * 2048);
      }
      named_bar_sync(3 + wg, 128);
      const int px = (2 * (lane >> 4) + (lane & 1)) * 4 + ((lane & 7) >> 1);
      const uint32_t sto = sbase + wg * kWoBlk + px * 128 + (((2 * wl + ((lane >> 3) & 1)) ^ (px & 7)) << 4);
      int st = 0, sb = 0;
      uint32_t ph = 0;
      uint32_t pk[16];
#pragma unroll
      for (int i = 0; i < 16; i++) pk[i] = 0u;
      auto store = [&](int tq) {
        const int g = tq / 28, tp = tq - 28 * g, tpar = tp / 7, tstrip = tp - 7 * tpar;
#pragma unroll
        for (int jp = 0; jp < 4; jp++)
          stmatrix_x4_t(sto + sb * 8192 + jp * 2048, pk[4 * jp], pk[4 * jp + 1], pk[4 * jp + 2], pk[4 * jp + 3]);
        fence_proxy_async();
        if (wl == 0 && lane == 0) bulk_wait_read1();
        named_bar_sync(3 + wg, 128);
        if (wl == 0 && lane == 0 && tq >= 0) {
          tma_store_5d(&tm_o2, sbase + wg * kWoBlk + sb * 8192, 0, 4 * g, 16 * tstrip, 3 * (tpar & 1) + wg, tpar >> 1);
          bulk_commit();
        }
        __syncwarp();
        sb = sb == 2 ? 0 : sb + 1;
      };
      int t = k, cur = -1;
#pragma unroll 1
      for (; t < kProjTiles; t += kProjCtas) {
        float acc[32];
        const bool rdy = mbar_test_wait(bar + 8 * st, ph);
        const uint32_t blo = (uint32_t)make_desc(sA + st * kOTileBytes, 128, 768, 0);
        if (t > k || wg) named_bar_sync(6 + wg, 256);
        if (!rdy) mbar_wait(bar + 8 * st, ph);
        wg_fence();
#pragma unroll
        for (int kk = 0; kk < 12; kk++)
          wgmma_m64n64k16_rs<1>(acc, wf[kk][0], wf[kk][1], wf[kk][2], wf[kk][3],
                                desc64(blo + (((kk / 3) * 6144 + (kk % 3) * 256) >> 4), 768 >> 4), kk != 0);
        wg_commit();
        if (wg < 2 || t + kProjCtas < kProjTiles) named_bar_arrive(6 + (wg == 2 ? 0 : wg + 1), 256);
        const int nxt = (int)lds32(bar + 128 + 4 * st);
        store(cur);
        cur = nxt;
        wg_wait<0>();
        fence_regs(acc);
        if (lane == 0) mbar_arrive(bar + 64 + 8 * st);
#pragma unroll
        for (int i = 0; i < 16; i++) pk[i] = pack_bf16(acc[2 * i], acc[2 * i + 1]);
        if (++st == kStages) { st = 0; ph ^= 1; }
      }
      store(cur);
      if (wl == 0 && lane == 0) bulk_wait<0>();
    } else {
      if (lane == 0) {
        mbar_init(bar + 16 * wl, 1);
        mbar_init(bar + 16 * wl + 8, 1);
        mbar_init(bar + 64 + 16 * wl, 12);
        mbar_init(bar + 64 + 16 * wl + 8, 12);
        sts32(bar + 160, 0);
        fence_mbar_init();
      }
      __syncwarp();
      named_bar_sync(0, 512);
      if (wl == 3 && lane == 0) {
        prefetch_map(&tm_o2);
        __nanosleep(2000);
        mbar_expect_tx(bar + 56, 3 * kWoBlk);
#pragma unroll 1
        for (int i = 0; i < 3; i++) tma_load_2d(sbase + i * kWoBlk, &tm_wo2, bar + 56, i * 64, 0);
      }
      __syncwarp();
      if (wl == 3 && k < 4) {
        if (lane == 0) {
          const uint32_t e0 = ld_relaxed(&g_epoch[k * 32 + 3]);
          const uint32_t stg = sA + (kStages - 1) * kOTileBytes;
          mbar_expect_tx(bar + 48, 3 * ka::kWAtom);
#pragma unroll 1
          for (int i = 0; i < 3; i++) tma_load_2d(stg + i * ka::kWAtom, &tm_wo, bar + 48, k * 48 + i * 16, 0);
          mbar_wait(bar + 48, 0);
          bulk_store(g_wop + k * 3 * ka::kWAtom, stg, 3 * ka::kWAtom);
          bulk_commit();
          bulk_wait<0>();
          publish_fence();
          st_relaxed(&g_wflag[k * 32], e0 * 32u + 1);
          st_relaxed(&g_epoch[k * 32 + 3], e0 + 1);
        }
        __syncwarp();
        named_bar_arrive(2, 128);
      }
      if (wl < 3 && k < 4) named_bar_sync(2, 128);
      if (wl < 3 && lane < 4) {
        const uint32_t e0 = ld_relaxed(&g_epoch[k * 32 + wl]);
#pragma unroll 1
        for (int it = wl;; it += 3) {
          const int t = k + it * kProjCtas;
          if (t >= kProjTiles) break;
          const int g = t / 28, tp = t - 28 * g;
          uint32_t sp = 0;
          while (true) {
            const bool ok = (int)(ld_acquire(&g_oflag[tp * 32 + lane]) - (e0 * 32u + g + 1)) >= 0;
            if (__all_sync(15u, ok)) break;
            if (++sp > LIMIT) { __trap(); break; }
          }
          if (lane == 0) {
            const int n = (int)atom_inc_shared(bar + 160), st = n % kStages;
            if (n >= kStages) mbar_wait_sleep(bar + 64 + 8 * st, ((n / kStages) & 1) ^ 1);
            sts32(bar + 128 + 4 * st, t);
            mbar_expect_tx(bar + 8 * st, kOTileBytes);
            bulk_load_hint(sA + st * kOTileBytes, o_tile(g, tp), kOTileBytes, bar + 8 * st, policy_evict_first());
          }
          __syncwarp(15u);
        }
        if (lane == 0) st_relaxed(&g_epoch[k * 32 + wl], e0 + 1);
      }
    }
  }
}

}

namespace {

typedef CUresult (*EncodeTiledFn)(CUtensorMap*, CUtensorMapDataType, cuuint32_t, void*, const cuuint64_t*,
                                  const cuuint64_t*, const cuuint32_t*, const cuuint32_t*, CUtensorMapInterleave,
                                  CUtensorMapSwizzle, CUtensorMapL2promotion, CUtensorMapFloatOOBfill);

EncodeTiledFn get_encode_fn() {
  static EncodeTiledFn fn = nullptr;
  if (!fn) {
    void* p = nullptr;
    cudaDriverEntryPointQueryResult qres;
    if (cudaGetDriverEntryPoint("cuTensorMapEncodeTiled", &p, cudaEnableDefault, &qres) == cudaSuccess)
      fn = reinterpret_cast<EncodeTiledFn>(p);
  }
  return fn;
}

CUtensorMap make_map(void* base, int rank, const cuuint64_t* dims, const cuuint64_t* strides, const cuuint32_t* box,
                     CUtensorMapSwizzle swz) {
  CUtensorMap m;
  cuuint32_t es[5] = {1, 1, 1, 1, 1};
  get_encode_fn()(&m, CU_TENSOR_MAP_DATA_TYPE_BFLOAT16, (cuuint32_t)rank, base, dims, strides, box, es,
                  CU_TENSOR_MAP_INTERLEAVE_NONE, swz, CU_TENSOR_MAP_L2_PROMOTION_L2_128B,
                  CU_TENSOR_MAP_FLOAT_OOB_FILL_NONE);
  return m;
}

}

extern "C" void kernel_launch(void* const* d_in, const int* in_sizes, int n_in, void* d_out, int out_size) {
  using namespace nat;
  (void)in_sizes; (void)n_in; (void)out_size;
  const __nv_bfloat16* x = (const __nv_bfloat16*)d_in[0];
  const __nv_bfloat16* wqkv = (const __nv_bfloat16*)d_in[1];
  const __nv_bfloat16* wo = (const __nv_bfloat16*)d_in[2];
  const __nv_bfloat16* rpb = (const __nv_bfloat16*)d_in[3];
  __nv_bfloat16* out = (__nv_bfloat16*)d_out;

  CUtensorMap tm_x, tm_h, tm_r, tm_w, tm_wo, tm_out, tm_wo2, tm_o2, tm_o3;
  {
    cuuint64_t dims[5] = {64, 112, 112, 6, 2};
    cuuint64_t str[4] = {768, 2ull * 224 * 384, 128, 224ull * 384};
    cuuint32_t box[5] = {64, 16, 4, 3, 1};
    tm_x = make_map((void*)x, 5, dims, str, box, CU_TENSOR_MAP_SWIZZLE_128B);
    cuuint32_t boxh[5] = {64, 3, 5, 1, 1}, boxr[5] = {64, 16, 1, 1, 1};
    tm_h = make_map((void*)x, 5, dims, str, boxh, CU_TENSOR_MAP_SWIZZLE_128B);
    tm_r = make_map((void*)x, 5, dims, str, boxr, CU_TENSOR_MAP_SWIZZLE_128B);
  }
  {
    cuuint64_t dims[2] = {576, 192};
    cuuint64_t str[1] = {1152};
    cuuint32_t box[2] = {16, 192};
    tm_w = make_map((void*)wqkv, 2, dims, str, box, CU_TENSOR_MAP_SWIZZLE_32B);
  }
  {
    cuuint64_t dims[2] = {192, 192};
    cuuint64_t str[1] = {384};
    cuuint32_t box[2] = {16, 192};
    tm_wo = make_map((void*)wo, 2, dims, str, box, CU_TENSOR_MAP_SWIZZLE_32B);
    cuuint32_t box2[2] = {64, 192};
    tm_wo2 = make_map((void*)wo, 2, dims, str, box2, CU_TENSOR_MAP_SWIZZLE_128B);
  }
  {
    cuuint64_t dims[5] = {192, 112, 112, 2, 2};
    cuuint64_t str[4] = {2ull * 224 * 384, 768, 384, 224ull * 384};
    cuuint32_t box[5] = {48, 4, 16, 1, 1};
    tm_out = make_map((void*)out, 5, dims, str, box, CU_TENSOR_MAP_SWIZZLE_NONE);
  }
  {
    cuuint64_t dims[5] = {64, 112, 112, 6, 2};
    cuuint64_t str[4] = {2ull * 224 * 384, 768, 128, 224ull * 384};
    cuuint32_t box[5] = {64, 4, 16, 1, 1};
    tm_o2 = make_map((void*)out, 5, dims, str, box, CU_TENSOR_MAP_SWIZZLE_128B);
  }
  {
    cuuint64_t dims[5] = {32, 112, 112, 12, 2};
    cuuint64_t str[4] = {2ull * 224 * 384, 768, 64, 224ull * 384};
    cuuint32_t box[5] = {32, 4, 16, 3, 1};
    tm_o3 = make_map((void*)out, 5, dims, str, box, CU_TENSOR_MAP_SWIZZLE_64B);
  }
  cudaFuncSetAttribute(nat_kernel, cudaFuncAttributeMaxDynamicSharedMemorySize, kSmemBytes);
  nat_kernel<<<kStripCtas + kProjCtas, kThreads, kSmemBytes>>>(wqkv, rpb, tm_x, tm_w, tm_h, tm_r, tm_wo, tm_out, tm_wo2, tm_o2, tm_o3);
}
```
